```python
import torch

def _softmax(x, axis=-1):
    return torch.softmax(x, dim=axis)

def _gelu(x):
    return torch.nn.functional.gelu(x, approximate='tanh')

def _silu(x):
    return torch.nn.functional.silu(x)

def _sigmoid(x):
    return torch.sigmoid(x)

def _layernorm(x, axis=-1, eps=1e-05):
    m = x.mean(dim=axis, keepdim=True)
    v = x.var(dim=axis, keepdim=True, unbiased=False)
    return (x - m) / torch.sqrt(v + eps)

def _scatter_add(tgt, idx, src, axis=0):
    return tgt.clone().index_add_(axis, idx, src)

def _segment_sum(src, seg, n):
    out = torch.zeros((n,) + src.shape[1:], dtype=src.dtype)
    return out.index_add_(0, seg, src)

def _pad(x, pw):
    flat = tuple((v for pair in reversed(pw) for v in pair))
    return torch.nn.functional.pad(x, flat)
kernel_name = 'gated_mix__linear_kernel_hedgehog__memory_aug_recurrent_mem_tr__prompt'

def setup_inputs():

    _w = lambda a: (lambda t: t.to(torch.bfloat16) if t.is_floating_point() else t)(torch.as_tensor(a))

    def _A_setup():
        B, S, D, H = (1, 2048, 448, 16)
        Dh = D // H
        return {'x': _w((lambda *s: torch.randn(*s, dtype=torch.bfloat16) * 0.05)(B, S, D)), 'wqkv': _w((lambda *s: torch.randn(*s, dtype=torch.bfloat16) * 1.6)(D, 3 * D)), 'w_phi': _w((lambda *s: torch.randn(*s, dtype=torch.bfloat16) * 1.6)(H, Dh, Dh) * Dh ** (-0.5)), 'wo': _w((lambda *s: torch.randn(*s, dtype=torch.bfloat16) * 0.05)(D, D))}
    _A_in = _A_setup()

    def _B_setup():
        B, S, Dm = (1, 2048, 448)
        H, Dh = (16, 256)
        M, seg = (8, 32)
        seg = min(seg, S)
        S = S // seg * seg
        return {'x': _w((lambda *s: torch.randn(*s, dtype=torch.bfloat16) * 0.05)(B, S, Dm)), 'mem0': _w((lambda *s: torch.randn(*s, dtype=torch.bfloat16) * 0.8)(B, M, Dm)), 'Wq': _w((lambda *s: torch.randn(*s, dtype=torch.bfloat16) * 1.6)(Dm, H, Dh) * Dm ** (-0.5)), 'Wk': _w((lambda *s: torch.randn(*s, dtype=torch.bfloat16) * 1.6)(Dm, H, Dh) * Dm ** (-0.5)), 'Wv': _w((lambda *s: torch.randn(*s, dtype=torch.bfloat16) * 0.8)(Dm, H, Dh) * Dm ** (-0.5)), 'Wo': _w((lambda *s: torch.randn(*s, dtype=torch.bfloat16) * 0.8)(H, Dh, Dm) * (H * Dh) ** (-0.5)), 'seg_len': seg}
    _B_in = _B_setup()
    return {'A_x': _A_in['x'], 'A_wqkv': _A_in['wqkv'], 'A_w_phi': _A_in['w_phi'], 'A_wo': _A_in['wo'], 'B_x': _B_in['x'], 'B_mem0': _B_in['mem0'], 'B_Wq': _B_in['Wq'], 'B_Wk': _B_in['Wk'], 'B_Wv': _B_in['Wv'], 'B_Wo': _B_in['Wo'], 'B_seg_len': _B_in['seg_len'], 'gate_w': _w((lambda *s: torch.randn(*s, dtype=torch.bfloat16) * 0.05)(448) * 16.0)}

def reference(A_x, A_wqkv, A_w_phi, A_wo, B_x, B_mem0, B_Wq, B_Wk, B_Wv, B_Wo, B_seg_len, gate_w):

    def _A_ref(x, wqkv, w_phi, wo):
        B, S, D = x.shape
        H = 16
        Dh = D // H
        qkv = (lambda x, *d: x.permute(*d))((x @ wqkv).reshape(B, S, 3, H, Dh), 2, 0, 3, 1, 4)
        q, k, v = (qkv[0], qkv[1], qkv[2])
        pq = torch.einsum('bhsd,hdf->bhsf', q, w_phi)
        pk = torch.einsum('bhsd,hdf->bhsf', k, w_phi)
        phi_q = torch.concatenate([_softmax(pq, axis=-1), _softmax(-pq, axis=-1)], axis=-1)
        phi_k = torch.concatenate([_softmax(pk, axis=-1), _softmax(-pk, axis=-1)], axis=-1)
        kv = torch.einsum('bhsf,bhsd->bhfd', phi_k, v)
        z = torch.einsum('bhsf->bhf', phi_k)
        num = torch.einsum('bhqf,bhfd->bhqd', phi_q, kv)
        den = torch.einsum('bhqf,bhf->bhq', phi_q, z)[..., None] + 1e-06
        o = num / den
        return (lambda x, *d: x.permute(*d))(o, 0, 2, 1, 3).reshape(B, S, D) @ wo

    def _B_ref(x, mem0, Wq, Wk, Wv, Wo, seg_len):
        B, S, Dm = x.shape
        H, Dh = (Wq.shape[1], Wq.shape[2])
        M = mem0.shape[1]
        scale = Dh ** (-0.5)
        n_seg = S // seg_len
        L = M + seg_len
        idx = torch.arange(L)
        mask = (idx[:, None] < M) | (idx[:, None] >= idx[None, :])
        mem = mem0
        outs = []
        for s in range(n_seg):
            xs = x[:, s * seg_len:(s + 1) * seg_len, :].clone()
            h = torch.concatenate([mem, xs], axis=1)
            q = torch.einsum('btd,dhe->bhte', h, Wq)
            k = torch.einsum('btd,dhe->bhte', h, Wk)
            v = torch.einsum('btd,dhe->bhte', h, Wv)
            scores = torch.einsum('bhqe,bhke->bhqk', q, k) * scale
            scores = torch.where(mask[None, None], scores, -1000000000.0)
            p = _softmax(scores, axis=-1)
            o = torch.einsum('bhqk,bhke->bhqe', p, v)
            o = torch.einsum('bhte,hed->btd', o, Wo)
            mem = o[:, :M, :].clone()
            outs.append(o[:, M:, :])
        return torch.concatenate(outs, axis=1)
    x = A_x
    g = _sigmoid((x * gate_w).sum(-1, keepdims=True))
    a = _A_ref(x, A_wqkv, A_w_phi, A_wo)
    b = _B_ref(x, B_mem0, B_Wq, B_Wk, B_Wv, B_Wo, B_seg_len)
    return g * a + (1 - g) * b
```

```cpp
#include <cuda_runtime.h>
#include <cuda_bf16.h>
#include <stdint.h>

typedef __nv_bfloat16 bf16;
#define S_LEN 2048
#define DM 448
#define NH 16
#define NSEG 64
#define SPIN_LIMIT (1 << 22)

__device__ uint4 g_WF[2 * NH * 28 * 28 * 32];
__device__ uint2 g_KF[NSEG * NH * 28 * 4 * 32];
__device__ uint4 g_VF[NSEG * NH * 56 * 32];
__device__ uint2 g_KMF[NSEG * NH * 4 * 16 * 32];
__device__ uint32_t g_UF[NSEG * NH * 56 * 32];
__device__ float4 g_ACC[NSEG * 40 * 32];
__device__ float g_qkv[S_LEN * 1344];
__device__ float g_phiq[S_LEN * NH * 56];
__device__ float g_phik[S_LEN * NH * 56];
__device__ float g_kv[NH * 56 * 29];
__device__ float g_oa[S_LEN * DM];
__device__ int g_err;
__device__ unsigned g_ts[64 * 64 * 16];

__device__ __forceinline__ uint32_t pack_bf16(float lo, float hi) {
  uint32_t r; asm("cvt.rn.bf16x2.f32 %0, %1, %2;" : "=r"(r) : "f"(hi), "f"(lo)); return r;
}
__device__ __forceinline__ float bf_lo(uint32_t v) { return __uint_as_float(v << 16); }
__device__ __forceinline__ float bf_hi(uint32_t v) { return __uint_as_float(v & 0xffff0000u); }
__device__ __forceinline__ float b2f(bf16 v) { return __bfloat162float(v); }

__global__ void n_prep(const bf16* Wq, const bf16* Wk, const bf16* Wv, const bf16* Wo) {
  int idx = blockIdx.x * blockDim.x + threadIdx.x;
  if (idx >= 2 * NH * 28 * 28 * 32) return;
  int lane = idx & 31, r = idx >> 5;
  int ks = r % 28; r /= 28; int tile = r % 28; r /= 28; int h = r % NH; int mat = r / NH;
  int g = lane >> 2, tq = lane & 3;
  float v[8];
  for (int i = 0; i < 8; i++) {
    int row = tile * 16 + g + ((i >> 1) & 1) * 8;
    int col = ks * 16 + tq * 2 + (i & 1) + (i >> 2) * 8;
    float acc = 0.f;
    if (mat == 0) { for (int e = 0; e < 256; e++) acc += b2f(Wq[(row * NH + h) * 256 + e]) * b2f(Wk[(col * NH + h) * 256 + e]); acc *= 0.0625f; }
    else { for (int e = 0; e < 256; e++) acc += b2f(Wo[(h * 256 + e) * DM + row]) * b2f(Wv[(col * NH + h) * 256 + e]); }
    v[i] = acc;
  }
  g_WF[idx] = make_uint4(pack_bf16(v[0], v[1]), pack_bf16(v[2], v[3]), pack_bf16(v[4], v[5]), pack_bf16(v[6], v[7]));
}
__device__ __forceinline__ float wf_elem(int mat, int h, int row, int col) {
  int tile = row >> 4, ks = col >> 4, rr = row & 15, cc = col & 15;
  int lane = (rr & 7) * 4 + ((cc & 7) >> 1);
  int reg = (rr >> 3) + (cc >> 3) * 2;
  uint32_t w = ((const uint32_t*)g_WF)[((((mat * NH + h) * 28 + tile) * 28 + ks) * 32 + lane) * 4 + reg];
  return (cc & 1) ? bf_hi(w) : bf_lo(w);
}
__device__ __forceinline__ void mma16816(float* d, uint32_t a0, uint32_t a1, uint32_t a2, uint32_t a3, uint32_t b0, uint32_t b1) {
  asm volatile("mma.sync.aligned.m16n8k16.row.col.f32.bf16.bf16.f32 {%0,%1,%2,%3}, {%4,%5,%6,%7}, {%8,%9}, {%0,%1,%2,%3};"
    : "+f"(d[0]), "+f"(d[1]), "+f"(d[2]), "+f"(d[3]) : "r"(a0), "r"(a1), "r"(a2), "r"(a3), "r"(b0), "r"(b1));
}
__device__ __forceinline__ void mma1688(float* d, uint32_t a0, uint32_t a1, uint32_t b0) {
  asm volatile("mma.sync.aligned.m16n8k8.row.col.f32.bf16.bf16.f32 {%0,%1,%2,%3}, {%4,%5}, {%6}, {%0,%1,%2,%3};"
    : "+f"(d[0]), "+f"(d[1]), "+f"(d[2]), "+f"(d[3]) : "r"(a0), "r"(a1), "r"(b0));
}
__device__ __forceinline__ uint32_t movm(uint32_t a) { uint32_t d; asm volatile("movmatrix.sync.aligned.m8n8.trans.b16 %0, %1;" : "=r"(d) : "r"(a)); return d; }

__global__ void n_xgemm(const bf16* x) {
  int wid = (blockIdx.x * blockDim.x + threadIdx.x) >> 5, lane = threadIdx.x & 31;
  int seg = wid % NSEG; int r = wid / NSEG;
  int tile = r % 28; r /= 28; int h = r % NH; int mat = r / NH;
  if (mat >= 2) return;
  int g = lane >> 2, tq = lane & 3;
  float d[4][4] = {};
  const uint4* wf = g_WF + (((mat * NH + h) * 28 + tile) * 28) * 32 + lane;
  for (int ks = 0; ks < 28; ks++) {
    uint4 a = wf[ks * 32];
    for (int kg = 0; kg < 4; kg++) {
      const uint32_t* xr = (const uint32_t*)(x + (seg * 32 + kg * 8 + g) * DM + ks * 16 + tq * 2);
      mma16816(d[kg], a.x, a.y, a.z, a.w, xr[0], xr[4]);
    }
  }
  if (mat == 0) {
    for (int kg = 0; kg < 4; kg++) {
      uint32_t b0 = movm(pack_bf16(d[kg][0], d[kg][1])), b1 = movm(pack_bf16(d[kg][2], d[kg][3]));
      g_KF[(((seg * NH + h) * 28 + tile) * 4 + kg) * 32 + lane] = make_uint2(b0, b1);
    }
  } else {
    g_VF[((seg * NH + h) * 56 + tile * 2) * 32 + lane] = make_uint4(pack_bf16(d[0][0], d[0][1]), pack_bf16(d[1][0], d[1][1]), pack_bf16(d[2][0], d[2][1]), pack_bf16(d[3][0], d[3][1]));
    g_VF[((seg * NH + h) * 56 + tile * 2 + 1) * 32 + lane] = make_uint4(pack_bf16(d[0][2], d[0][3]), pack_bf16(d[1][2], d[1][3]), pack_bf16(d[2][2], d[2][3]), pack_bf16(d[3][2], d[3][3]));
  }
}
__global__ void n_zero() {
  int i = blockIdx.x * blockDim.x + threadIdx.x;
  if (i < NSEG * 40 * 32) g_ACC[i] = make_float4(0.f, 0.f, 0.f, 0.f);
  if (i < NH * 56 * 29) g_kv[i] = 0.f;
}
__global__ void n_qkv(const bf16* x, const bf16* w) {
  int i = blockIdx.x * blockDim.x + threadIdx.x;
  if (i >= S_LEN * 1344) return;
  int n = i % 1344, t = i / 1344;
  float acc = 0.f;
  for (int k = 0; k < DM; k++) acc += b2f(x[t * DM + k]) * b2f(w[k * 1344 + n]);
  g_qkv[i] = acc;
}
__global__ void n_phi(const bf16* wphi) {
  int i = blockIdx.x * blockDim.x + threadIdx.x;
  if (i >= S_LEN * 2 * NH) return;
  int h = i % NH, which = (i / NH) % 2, t = i / (2 * NH);
  float p[28]; float mx = -1e30f, mn = 1e30f;
  for (int f = 0; f < 28; f++) {
    float acc = 0.f;
    for (int d = 0; d < 28; d++) acc += g_qkv[t * 1344 + which * 448 + h * 28 + d] * b2f(wphi[(h * 28 + d) * 28 + f]);
    p[f] = acc; mx = fmaxf(mx, acc); mn = fminf(mn, acc);
  }
  float s1 = 0.f, s2 = 0.f;
  for (int f = 0; f < 28; f++) { s1 += __expf(p[f] - mx); s2 += __expf(mn - p[f]); }
  float* o = (which ? g_phik : g_phiq) + (t * NH + h) * 56;
  for (int f = 0; f < 28; f++) { o[f] = __expf(p[f] - mx) / s1; o[28 + f] = __expf(mn - p[f]) / s2; }
}
__global__ void n_kv() {
  int i = blockIdx.x * blockDim.x + threadIdx.x;
  if (i >= 32 * NH * 56 * 29) return;
  int d = i % 29, f = (i / 29) % 56, h = (i / (29 * 56)) % NH, ch = i / (29 * 56 * NH);
  float acc = 0.f;
  for (int t = ch * 64; t < ch * 64 + 64; t++) acc += g_phik[(t * NH + h) * 56 + f] * (d < 28 ? g_qkv[t * 1344 + 896 + h * 28 + d] : 1.f);
  atomicAdd(&g_kv[(h * 56 + f) * 29 + d], acc);
}
__global__ void n_oa() {
  int i = blockIdx.x * blockDim.x + threadIdx.x;
  if (i >= S_LEN * DM) return;
  int c = i % DM, t = i / DM, h = c / 28, d = c % 28;
  float num = 0.f, den = 0.f;
  for (int f = 0; f < 56; f++) { float p = g_phiq[(t * NH + h) * 56 + f]; num += p * g_kv[(h * 56 + f) * 29 + d]; den += p * g_kv[(h * 56 + f) * 29 + 28]; }
  g_oa[i] = num / (den + 1e-6f);
}

__global__ void __launch_bounds__(512) n_x3(const bf16* x, const bf16* wo, const bf16* gate_w, bf16* out) {
  __shared__ uint32_t sP[NH][2][32][10];
  __shared__ float sG[32];
  int seg = blockIdx.x, w = threadIdx.x >> 5, lane = threadIdx.x & 31, g = lane >> 2, tq = lane & 3;
  for (int r = w; r < 32; r += 16) {
    float acc = 0.f;
    for (int k = lane; k < DM; k += 32) acc += b2f(x[(seg * 32 + r) * DM + k]) * b2f(gate_w[k]);
    for (int o = 16; o; o >>= 1) acc += __shfl_xor_sync(0xffffffffu, acc, o);
    if (lane == 0) sG[r] = 1.f / (1.f + __expf(-acc));
  }
  {
    int h = w;
    float s[2][5][4] = {};
    for (int ct = 0; ct < 28; ct++) {
      uint32_t a[2][4];
      for (int m = 0; m < 2; m++) {
        const uint32_t* r0 = (const uint32_t*)(x + (seg * 32 + m * 16 + g) * DM + ct * 16 + tq * 2);
        const uint32_t* r1 = (const uint32_t*)(x + (seg * 32 + m * 16 + g + 8) * DM + ct * 16 + tq * 2);
        a[m][0] = r0[0]; a[m][1] = r1[0]; a[m][2] = r0[4]; a[m][3] = r1[4];
      }
      for (int kg = 0; kg < 4; kg++) {
        uint2 b = g_KF[(((seg * NH + h) * 28 + ct) * 4 + kg) * 32 + lane];
        for (int m = 0; m < 2; m++) mma16816(s[m][1 + kg], a[m][0], a[m][1], a[m][2], a[m][3], b.x, b.y);
      }
      int j = ct / 7, i = ct % 7;
      if (i < 4) {
        uint2 b = g_KMF[(((seg * NH + h) * 4 + j) * 16 + i * 4) * 32 + lane];
        for (int m = 0; m < 2; m++) mma16816(s[m][0], a[m][0], a[m][1], a[m][2], a[m][3], b.x, b.y);
      } else {
        for (int q = 0; q < 4; q++) {
          uint2 b = g_KMF[(((seg * NH + h) * 4 + j) * 16 + q * 4 + (i - 3)) * 32 + lane];
          for (int m = 0; m < 2; m++) mma16816(s[m][0], a[m][0], a[m][1], a[m][2], a[m][3], b.x, b.y);
        }
      }
    }
    for (int m = 0; m < 2; m++) for (int hf = 0; hf < 2; hf++) {
      int t = m * 16 + hf * 8 + g;
      float v[10]; float mx = -1e30f;
      for (int n = 0; n < 5; n++) for (int e = 0; e < 2; e++) {
        float val = s[m][n][hf * 2 + e];
        if (n > 0 && (n - 1) * 8 + tq * 2 + e > t) val = -1e30f;
        v[n * 2 + e] = val; mx = fmaxf(mx, val);
      }
      mx = fmaxf(mx, __shfl_xor_sync(0xffffffffu, mx, 1)); mx = fmaxf(mx, __shfl_xor_sync(0xffffffffu, mx, 2));
      float z = 0.f;
      for (int i = 0; i < 10; i++) { v[i] = __expf(v[i] - mx); z += v[i]; }
      z += __shfl_xor_sync(0xffffffffu, z, 1); z += __shfl_xor_sync(0xffffffffu, z, 2);
      float iz = 1.f / z;
      sP[h][m][lane][hf] = pack_bf16(v[0] * iz, v[1] * iz);
      sP[h][m][lane][2 + hf] = pack_bf16(v[2] * iz, v[3] * iz);
      sP[h][m][lane][4 + hf] = pack_bf16(v[4] * iz, v[5] * iz);
      sP[h][m][lane][6 + hf] = pack_bf16(v[6] * iz, v[7] * iz);
      sP[h][m][lane][8 + hf] = pack_bf16(v[8] * iz, v[9] * iz);
    }
  }
  __syncthreads();
  if (w < 14) {
    float o[2][4][4] = {};
    for (int h = 0; h < NH; h++) {
      for (int n = 0; n < 4; n++) {
        int nt = w * 4 + n;
        uint4 v = g_VF[((seg * NH + h) * 56 + nt) * 32 + lane];
        uint32_t u = g_UF[((seg * NH + h) * 56 + nt) * 32 + lane];
        for (int m = 0; m < 2; m++) {
          const uint32_t* p = sP[h][m][lane];
          mma1688(o[m][n], p[0], p[1], u);
          mma16816(o[m][n], p[2], p[3], p[4], p[5], v.x, v.y);
          mma16816(o[m][n], p[6], p[7], p[8], p[9], v.z, v.w);
        }
      }
    }
    for (int m = 0; m < 2; m++) for (int n = 0; n < 4; n++) for (int i = 0; i < 4; i++) {
      int r = m * 16 + (i >> 1) * 8 + g, c = (w * 4 + n) * 8 + tq * 2 + (i & 1);
      int t = seg * 32 + r;
      float a = 0.f;
      for (int k = 0; k < DM; k++) a += g_oa[t * DM + k] * b2f(wo[k * DM + c]);
      float gt = sG[r];
      out[t * DM + c] = __float2bfloat16(gt * a + (1.f - gt) * o[m][n][i]);
    }
  }
}

__device__ __forceinline__ uint32_t smem_u32(const void* p) { return (uint32_t)__cvta_generic_to_shared(p); }
__device__ __forceinline__ uint32_t mapa(uint32_t a, uint32_t r) { uint32_t o; asm volatile("mapa.shared::cluster.u32 %0, %1, %2;" : "=r"(o) : "r"(a), "r"(r)); return o; }
__device__ __forceinline__ bool try_wait(uint32_t bar, uint32_t parity) {
  uint32_t ok; asm volatile("{\n.reg .pred p;\nmbarrier.try_wait.parity.shared::cta.b64 p, [%1], %2;\nselp.u32 %0, 1, 0, p;\n}" : "=r"(ok) : "r"(bar), "r"(parity) : "memory"); return ok; }
__device__ __forceinline__ void wait_bar(uint32_t bar, uint32_t parity) {
  int n = 0; while (!try_wait(bar, parity)) { if (++n > SPIN_LIMIT) { g_err = 1; break; } } }
__device__ __forceinline__ void arm_bar(uint32_t bar, uint32_t bytes) { asm volatile("mbarrier.arrive.expect_tx.shared::cta.b64 _, [%0], %1;" :: "r"(bar), "r"(bytes) : "memory"); }
__device__ __forceinline__ float4 ld_relaxed4(const void* p) { float4 v; asm volatile("ld.relaxed.gpu.global.v4.f32 {%0,%1,%2,%3}, [%4];" : "=f"(v.x), "=f"(v.y), "=f"(v.z), "=f"(v.w) : "l"(p) : "memory"); return v; }
__device__ __forceinline__ void red4(void* p, float a, float b, float c, float d) { asm volatile("red.relaxed.gpu.global.add.v4.f32 [%0], {%1,%2,%3,%4};" :: "l"(p), "f"(a), "f"(b), "f"(c), "f"(d) : "memory"); }
__device__ __forceinline__ void st_async2(uint32_t dst, float a, float b, uint32_t bar) { asm volatile("st.async.shared::cluster.mbarrier::complete_tx::bytes.v2.f32 [%0], {%1,%2}, [%3];" :: "r"(dst), "f"(a), "f"(b), "r"(bar) : "memory"); }
__device__ __forceinline__ void bulk_g2s(uint32_t dst, const void* src, uint32_t bytes, uint32_t bar) {
  asm volatile("cp.async.bulk.shared::cluster.global.mbarrier::complete_tx::bytes [%0], [%1], %2, [%3];" :: "r"(dst), "l"(src), "r"(bytes), "r"(bar) : "memory"); }
__device__ __forceinline__ unsigned clk() { unsigned c; asm volatile("mov.u32 %0, %%clock;" : "=r"(c) :: "memory"); return c; }
__device__ __forceinline__ float ex2(float x) { float y; asm("ex2.approx.ftz.f32 %0, %1;" : "=f"(y) : "f"(x)); return y; }

#define NST 4
struct RSmem {
  uint2 kf[NST][7][4][32];
  uint4 vf[NST][14][32];
  uint2 memF[28][32];
  float2 sx[2][4][4][32];
  float2 sm[2][4][32];
  float2 sred[4][32];
  uint32_t uF[8][32];
  float2 uP[6][4][32];
  unsigned long long bar_ld[NST], bar_sx[2], bar_sm[2];
};
#define POLL_DELAY 300
#define STAMP(i)

__global__ void __cluster_dims__(4, 1, 1) __launch_bounds__(256, 1) r_kernel(const bf16* mem0, int poll_delay) {
  extern __shared__ __align__(128) unsigned char smem_raw[];
  RSmem& sm = *reinterpret_cast<RSmem*>(smem_raw);
  const int h = blockIdx.x >> 2, j = blockIdx.x & 3;
  const int w = threadIdx.x >> 5, lane = threadIdx.x & 31, q = w & 3, g = lane >> 2, tq = lane & 3;
  const bool isA = w < 4;
  const uint32_t bar_ld = smem_u32(sm.bar_ld), bar_sx = smem_u32(sm.bar_sx), bar_sm = smem_u32(sm.bar_sm);
  if (threadIdx.x == 0) {
    for (int i = 0; i < NST; i++) asm volatile("mbarrier.init.shared::cta.b64 [%0], 1;" :: "r"(bar_ld + 8 * i));
    for (int i = 0; i < 2; i++) {
      asm volatile("mbarrier.init.shared::cta.b64 [%0], 1;" :: "r"(bar_sx + 8 * i));
      asm volatile("mbarrier.init.shared::cta.b64 [%0], 1;" :: "r"(bar_sm + 8 * i));
    }
    asm volatile("fence.mbarrier_init.release.cluster;" ::: "memory");
    for (int i = 0; i < 2; i++) { arm_bar(bar_sx + 8 * i, 4096); arm_bar(bar_sm + 8 * i, 1024); }
    for (int s = 0; s < NST - 1; s++) {
      arm_bar(bar_ld + 8 * s, 14336);
      bulk_g2s(smem_u32(sm.kf[s]), g_KF + ((s * NH + h) * 28 + 7 * j) * 128, 7168, bar_ld + 8 * s);
      bulk_g2s(smem_u32(sm.vf[s]), g_VF + ((s * NH + h) * 56 + 14 * j) * 32, 7168, bar_ld + 8 * s);
    }
  }
  uint4 W[49];
  {
    const uint4* wf = g_WF + (((isA ? 0 : 1) * NH + h) * 28) * 28 * 32 + lane;
#pragma unroll
    for (int i = 0; i < 28; i++) W[i] = wf[((7 * j + q) * 28 + ((i & ~3) | ((i + q) & 3))) * 32];
#pragma unroll
    for (int e = 0; e < 7; e++)
#pragma unroll
      for (int x = 0; x < 3; x++) W[28 + e * 3 + x] = wf[((7 * j + 4 + x) * 28 + 4 * e + q) * 32];
  }
  for (int i = threadIdx.x; i < 28 * 32; i += 256) {
    int ks = i >> 5, l = i & 31;
    const uint32_t* r = (const uint32_t*)(mem0 + (l >> 2) * DM + ks * 16 + (l & 3) * 2);
    sm.memF[ks][l] = make_uint2(r[0], r[4]);
  }
  const uint32_t memF_a = smem_u32(sm.memF);
  const int jj = w >> 1, vb = (w & 1) * 5;
  auto nt_addr = [&](int nt) { int n = jj * 14 + nt; return memF_a + (n >> 1) * 256 + lane * 8 + (n & 1) * 4; };
  asm volatile("barrier.cluster.arrive.release.aligned;\nbarrier.cluster.wait.acquire.aligned;" ::: "memory");

  const uint32_t rot[4] = { (uint32_t)((0 + q) & 3) * 256, (uint32_t)((1 + q) & 3) * 256, (uint32_t)((2 + q) & 3) * 256, (uint32_t)((3 + q) & 3) * 256 };
  const float LOG2E = 1.4426950408889634f;

  for (int s = 0; s < NSEG; s++) {
    const int b = s & 1; const uint32_t par = (s >> 1) & 1;
    const int st = s % NST;
    STAMP(0);
    if (s > 0) {
      const float4* p = g_ACC + (s * 40 + jj * 10 + vb) * 32 + lane;
      float4 v[5];
      int n = 0; bool done;
      do {
#pragma unroll
        for (int i = 0; i < 5; i++) v[i] = ld_relaxed4(p + i * 32);
        bool ok = true;
#pragma unroll
        for (int i = 0; i < 5; i++) ok = ok && (v[i].w == 16.f);
        done = __all_sync(0xffffffffu, ok);
      } while (!done && ++n < SPIN_LIMIT);
      if (!done) g_err = 2;
      if ((w & 1) == 0) {
        asm volatile("st.shared.u32 [%0], %1;" :: "r"(nt_addr(0)), "r"(pack_bf16(v[0].x, v[0].y)) : "memory");
        asm volatile("st.shared.u32 [%0], %1;" :: "r"(nt_addr(1)), "r"(pack_bf16(v[1].x, v[1].y)) : "memory");
        asm volatile("st.shared.u32 [%0], %1;" :: "r"(nt_addr(2)), "r"(pack_bf16(v[0].z, v[1].z)) : "memory");
        asm volatile("st.shared.u32 [%0], %1;" :: "r"(nt_addr(3)), "r"(pack_bf16(v[2].x, v[2].y)) : "memory");
        asm volatile("st.shared.u32 [%0], %1;" :: "r"(nt_addr(4)), "r"(pack_bf16(v[3].x, v[3].y)) : "memory");
        asm volatile("st.shared.u32 [%0], %1;" :: "r"(nt_addr(5)), "r"(pack_bf16(v[4].x, v[4].y)) : "memory");
        asm volatile("st.shared.u32 [%0], %1;" :: "r"(nt_addr(6)), "r"(pack_bf16(v[3].z, v[4].z)) : "memory");
      } else {
        asm volatile("st.shared.u32 [%0], %1;" :: "r"(nt_addr(7)), "r"(pack_bf16(v[0].x, v[0].y)) : "memory");
        asm volatile("st.shared.u32 [%0], %1;" :: "r"(nt_addr(8)), "r"(pack_bf16(v[1].x, v[1].y)) : "memory");
        asm volatile("st.shared.u32 [%0], %1;" :: "r"(nt_addr(9)), "r"(pack_bf16(v[2].x, v[2].y)) : "memory");
        asm volatile("st.shared.u32 [%0], %1;" :: "r"(nt_addr(10)), "r"(pack_bf16(v[1].z, v[2].z)) : "memory");
        asm volatile("st.shared.u32 [%0], %1;" :: "r"(nt_addr(11)), "r"(pack_bf16(v[3].x, v[3].y)) : "memory");
        asm volatile("st.shared.u32 [%0], %1;" :: "r"(nt_addr(12)), "r"(pack_bf16(v[4].x, v[4].y)) : "memory");
        asm volatile("st.shared.u32 [%0], %1;" :: "r"(nt_addr(13)), "r"(pack_bf16(v[3].z, v[4].z)) : "memory");
      }
    }
    STAMP(1);
    __syncthreads();
    STAMP(2);
    if (!isA) {
      if (threadIdx.x == 128 && s + NST - 1 < NSEG) {
        int s2 = s + NST - 1, st2 = s2 % NST;
        arm_bar(bar_ld + 8 * st2, 14336);
        bulk_g2s(smem_u32(sm.kf[st2]), g_KF + ((s2 * NH + h) * 28 + 7 * j) * 128, 7168, bar_ld + 8 * st2);
        bulk_g2s(smem_u32(sm.vf[st2]), g_VF + ((s2 * NH + h) * 56 + 14 * j) * 32, 7168, bar_ld + 8 * st2);
      }
      __syncwarp();
      if (s < NSEG - 1) {
        wait_bar(bar_ld + 8 * st, (s / NST) & 1);
        float d0[4] = {0.f, 0.f, 0.f, 0.f}, d1[4] = {0.f, 0.f, 0.f, 0.f};
#pragma unroll
        for (int i = 0; i < 7; i++) {
          uint2 a = sm.memF[7 * j + i][lane]; uint2 kb = sm.kf[st][i][q][lane];
          mma16816((i & 1) ? d1 : d0, a.x, 0u, a.y, 0u, kb.x, kb.y);
        }
        float s0 = d0[0] + d1[0], s1 = d0[1] + d1[1];
        uint32_t dst = smem_u32(&sm.sx[b][j][q][lane]);
#pragma unroll
        for (int r = 0; r < 4; r++) st_async2(mapa(dst, r), s0, s1, mapa(bar_sx + 8 * b, r));
      }
      STAMP(3);
      asm volatile("bar.sync 1, 256;" ::: "memory");
    }
    float am0[4] = {0.f, 0.f, 0.f, 0.f}, am1[4] = {0.f, 0.f, 0.f, 0.f}, ae[3][4] = {};
    {
      const uint32_t base = memF_a + lane * 8;
#pragma unroll
      for (int e = 0; e < 7; e++) {
        uint32_t b0[4], b1[4];
#pragma unroll
        for (int i = 0; i < 4; i++) asm volatile("ld.shared.v2.u32 {%0,%1}, [%2];" : "=r"(b0[i]), "=r"(b1[i]) : "r"(base + e * 1024 + rot[i]) : "memory");
        mma16816(am0, W[4 * e].x, W[4 * e].y, W[4 * e].z, W[4 * e].w, b0[0], b1[0]);
        mma16816(ae[0], W[28 + 3 * e].x, W[28 + 3 * e].y, W[28 + 3 * e].z, W[28 + 3 * e].w, b0[0], b1[0]);
        mma16816(am1, W[4 * e + 1].x, W[4 * e + 1].y, W[4 * e + 1].z, W[4 * e + 1].w, b0[1], b1[1]);
        mma16816(ae[1], W[29 + 3 * e].x, W[29 + 3 * e].y, W[29 + 3 * e].z, W[29 + 3 * e].w, b0[0], b1[0]);
        mma16816(am0, W[4 * e + 2].x, W[4 * e + 2].y, W[4 * e + 2].z, W[4 * e + 2].w, b0[2], b1[2]);
        mma16816(ae[2], W[30 + 3 * e].x, W[30 + 3 * e].y, W[30 + 3 * e].z, W[30 + 3 * e].w, b0[0], b1[0]);
        mma16816(am1, W[4 * e + 3].x, W[4 * e + 3].y, W[4 * e + 3].z, W[4 * e + 3].w, b0[3], b1[3]);
      }
    }
    if (isA) {
      asm volatile("bar.arrive 1, 256;" ::: "memory");
      STAMP(3);
      uint32_t kb[4][2];
      kb[0][0] = movm(pack_bf16(am0[0] + am1[0], am0[1] + am1[1])); kb[0][1] = movm(pack_bf16(am0[2] + am1[2], am0[3] + am1[3]));
#pragma unroll
      for (int x = 0; x < 3; x++) { kb[1 + x][0] = movm(pack_bf16(ae[x][0], ae[x][1])); kb[1 + x][1] = movm(pack_bf16(ae[x][2], ae[x][3])); }
      if (s < NSEG - 1) {
        float d0[4] = {0.f, 0.f, 0.f, 0.f}, d1[4] = {0.f, 0.f, 0.f, 0.f};
        uint2 a0 = sm.memF[7 * j + q][lane], a1 = sm.memF[7 * j + 4][lane], a2 = sm.memF[7 * j + 5][lane], a3 = sm.memF[7 * j + 6][lane];
        mma16816(d0, a1.x, 0u, a1.y, 0u, kb[1][0], kb[1][1]);
        mma16816(d1, a2.x, 0u, a2.y, 0u, kb[2][0], kb[2][1]);
        mma16816(d0, a3.x, 0u, a3.y, 0u, kb[3][0], kb[3][1]);
        mma16816(d1, a0.x, 0u, a0.y, 0u, kb[0][0], kb[0][1]);
        sm.sred[q][lane] = make_float2(d0[0] + d1[0], d0[1] + d1[1]);
        asm volatile("bar.sync 2, 128;" ::: "memory");
        float2 r0 = sm.sred[0][lane], r1 = sm.sred[1][lane], r2 = sm.sred[2][lane], r3 = sm.sred[3][lane];
        st_async2(mapa(smem_u32(&sm.sm[b][j][lane]), q), (r0.x + r1.x) + (r2.x + r3.x), (r0.y + r1.y) + (r2.y + r3.y), mapa(bar_sm + 8 * b, q));
      }
      STAMP(4);
      {
        uint2* kmf = g_KMF + (((s * NH + h) * 4 + j) * 16 + q * 4) * 32 + lane;
#pragma unroll
        for (int a = 0; a < 4; a++) kmf[a * 32] = make_uint2(kb[a][0], kb[a][1]);
      }
      const int nt0 = q < 2 ? q * 4 : 8 + (q - 2) * 3;
      float o[4][4] = {};
      float mx = 0.f, zx = 0.f;
      if (s < NSEG - 1) {
        wait_bar(bar_sx + 8 * b, par);
        float sx[8];
#pragma unroll
        for (int kg = 0; kg < 4; kg++) {
          float2 p0 = sm.sx[b][0][kg][lane], p1 = sm.sx[b][1][kg][lane], p2 = sm.sx[b][2][kg][lane], p3 = sm.sx[b][3][kg][lane];
          sx[2 * kg] = ((p0.x + p1.x) + (p2.x + p3.x)) * LOG2E; sx[2 * kg + 1] = ((p0.y + p1.y) + (p2.y + p3.y)) * LOG2E;
        }
        mx = fmaxf(fmaxf(fmaxf(sx[0], sx[1]), fmaxf(sx[2], sx[3])), fmaxf(fmaxf(sx[4], sx[5]), fmaxf(sx[6], sx[7])));
        mx = fmaxf(mx, __shfl_xor_sync(0xffffffffu, mx, 1)); mx = fmaxf(mx, __shfl_xor_sync(0xffffffffu, mx, 2));
#pragma unroll
        for (int i = 0; i < 8; i++) { sx[i] = ex2(sx[i] - mx); zx += sx[i]; }
        uint32_t p0 = pack_bf16(sx[0], sx[1]), p1 = pack_bf16(sx[2], sx[3]), p2 = pack_bf16(sx[4], sx[5]), p3 = pack_bf16(sx[6], sx[7]);
        wait_bar(bar_ld + 8 * st, (s / NST) & 1);
#pragma unroll
        for (int n = 0; n < 4; n++) if (n < 3 || q < 2) {
          uint4 v = sm.vf[st][nt0 + n][lane];
          mma16816(o[n], p0, 0u, p1, 0u, v.x, v.y);
          mma16816(o[n], p2, 0u, p3, 0u, v.z, v.w);
        }
      }
      STAMP(5);
      asm volatile("bar.sync 3, 256;" ::: "memory");
      uint32_t u[4];
      if (q < 2) {
#pragma unroll
        for (int n = 0; n < 4; n++) u[n] = sm.uF[nt0 + n][lane];
      } else {
#pragma unroll
        for (int n = 0; n < 3; n++) {
          const float2* pp = &sm.uP[nt0 - 8 + n][0][lane];
          float2 r0 = pp[0], r1 = pp[32], r2 = pp[64], r3 = pp[96];
          u[n] = pack_bf16((r0.x + r1.x) + (r2.x + r3.x), (r0.y + r1.y) + (r2.y + r3.y));
        }
        u[3] = 0;
      }
      STAMP(6);
      if (s < NSEG - 1) {
        wait_bar(bar_sm + 8 * b, par);
        STAMP(7);
        float2 r0 = sm.sm[b][0][lane], r1 = sm.sm[b][1][lane], r2 = sm.sm[b][2][lane], r3 = sm.sm[b][3][lane];
        float s0 = ((r0.x + r1.x) + (r2.x + r3.x)) * LOG2E, s1 = ((r0.y + r1.y) + (r2.y + r3.y)) * LOG2E;
        float m = fmaxf(s0, s1);
        m = fmaxf(m, __shfl_xor_sync(0xffffffffu, m, 1)); m = fmaxf(m, __shfl_xor_sync(0xffffffffu, m, 2));
        m = fmaxf(m, mx);
        float e0 = ex2(s0 - m), e1 = ex2(s1 - m), al = ex2(mx - m);
        uint32_t pm = pack_bf16(e0, e1);
#pragma unroll
        for (int n = 0; n < 4; n++) { o[n][0] *= al; o[n][1] *= al; mma1688(o[n], pm, 0u, u[n]); }
        float z = zx * al + e0 + e1;
        z += __shfl_xor_sync(0xffffffffu, z, 1); z += __shfl_xor_sync(0xffffffffu, z, 2);
        float iz = __frcp_rn(z);
        float4* dst = g_ACC + ((s + 1) * 40 + j * 10 + (q < 2 ? q * 3 : 6 + (q - 2) * 2)) * 32 + lane;
        red4(dst, o[0][0] * iz, o[0][1] * iz, o[2][0] * iz, 1.f);
        red4(dst + 32, o[1][0] * iz, o[1][1] * iz, o[2][1] * iz, 1.f);
        if (q < 2) red4(dst + 64, o[3][0] * iz, o[3][1] * iz, 0.f, 1.f);
        STAMP(8);
        if (threadIdx.x == 0) { arm_bar(bar_sx + 8 * b, 4096); arm_bar(bar_sm + 8 * b, 1024); }
      }
      {
        uint32_t* uf = g_UF + ((s * NH + h) * 56 + 14 * j + nt0) * 32 + lane;
#pragma unroll
        for (int n = 0; n < 4; n++) if (n < 3 || q < 2) uf[n * 32] = u[n];
      }
      asm volatile("bar.arrive 4, 256;" ::: "memory");
    } else {
      STAMP(4);
      sm.uF[2 * q][lane] = pack_bf16(am0[0] + am1[0], am0[1] + am1[1]);
      sm.uF[2 * q + 1][lane] = pack_bf16(am0[2] + am1[2], am0[3] + am1[3]);
#pragma unroll
      for (int x = 0; x < 3; x++) { sm.uP[2 * x][q][lane] = make_float2(ae[x][0], ae[x][1]); sm.uP[2 * x + 1][q][lane] = make_float2(ae[x][2], ae[x][3]); }
      asm volatile("bar.arrive 3, 256;" ::: "memory");
      STAMP(5);
      asm volatile("bar.sync 4, 256;" ::: "memory");
    }
    { unsigned t = clk(); while (clk() - t < (unsigned)poll_delay) {} }
  }
  asm volatile("barrier.cluster.arrive.release.aligned;\nbarrier.cluster.wait.acquire.aligned;" ::: "memory");
}

int g_poll_delay = POLL_DELAY;
extern "C" void kernel_launch(void* const* d_in, const int* in_sizes, int n_in, void* d_out, int out_size) {
  const bf16* x = (const bf16*)d_in[0];
  const bf16* wqkv = (const bf16*)d_in[1];
  const bf16* wphi = (const bf16*)d_in[2];
  const bf16* wo_a = (const bf16*)d_in[3];
  const bf16* mem0 = (const bf16*)d_in[5];
  const bf16* Wq = (const bf16*)d_in[6];
  const bf16* Wk = (const bf16*)d_in[7];
  const bf16* Wv = (const bf16*)d_in[8];
  const bf16* Wo = (const bf16*)d_in[9];
  const bf16* gate_w = (const bf16*)d_in[11];
  bf16* out = (bf16*)d_out;
  cudaFuncSetAttribute(r_kernel, cudaFuncAttributeMaxDynamicSharedMemorySize, (int)sizeof(RSmem));
  n_zero<<<(NSEG * 40 * 32 + 255) / 256, 256>>>();
  n_prep<<<(2 * NH * 28 * 28 * 32 + 255) / 256, 256>>>(Wq, Wk, Wv, Wo);
  n_xgemm<<<2 * NH * 28 * NSEG * 32 / 256, 256>>>(x);
  r_kernel<<<64, 256, sizeof(RSmem)>>>(mem0, g_poll_delay);
  n_qkv<<<(S_LEN * 1344 + 255) / 256, 256>>>(x, wqkv);
  n_phi<<<(S_LEN * 2 * NH + 255) / 256, 256>>>(wphi);
  n_kv<<<(32 * NH * 56 * 29 + 255) / 256, 256>>>();
  n_oa<<<(S_LEN * DM + 255) / 256, 256>>>();
  n_x3<<<NSEG, 512>>>(x, wo_a, gate_w, out);
}
```

```cpp
#include <cuda_runtime.h>
#include <cuda_bf16.h>
#include <stdint.h>
#include <stddef.h>

typedef __nv_bfloat16 bf16;
#define S_LEN 2048
#define DM 448
#define NH 16
#define NSEG 64
#define SPIN_LIMIT (1 << 22)

__device__ uint4 g_WF[2 * NH * 28 * 28 * 32];
__device__ uint2 g_KF[NSEG * NH * 28 * 4 * 32];
__device__ uint4 g_VF[NSEG * NH * 56 * 32];
__device__ uint2 g_KMF[NSEG * NH * 4 * 16 * 32];
__device__ uint32_t g_UF[NSEG * NH * 56 * 32];
__device__ uint4 g_ACC16[NSEG * 16 * 32];
__device__ float g_xmax[NSEG];
__device__ float g_bmax;
__device__ float g_qkv[S_LEN * 1344];
__device__ float g_phiq[S_LEN * NH * 56];
__device__ float g_phik[S_LEN * NH * 56];
__device__ float g_kv[NH * 56 * 29];
__device__ float g_oa[S_LEN * DM];
__device__ int g_err;
__device__ unsigned g_ts[64 * 64 * 16];

__device__ __forceinline__ uint32_t pack_bf16(float lo, float hi) {
  uint32_t r; asm("cvt.rn.bf16x2.f32 %0, %1, %2;" : "=r"(r) : "f"(hi), "f"(lo)); return r;
}
__device__ __forceinline__ float bf_lo(uint32_t v) { return __uint_as_float(v << 16); }
__device__ __forceinline__ float bf_hi(uint32_t v) { return __uint_as_float(v & 0xffff0000u); }
__device__ __forceinline__ float b2f(bf16 v) { return __bfloat162float(v); }

__global__ void n_prep(const bf16* Wq, const bf16* Wk, const bf16* Wv, const bf16* Wo) {
  int idx = blockIdx.x * blockDim.x + threadIdx.x;
  if (idx >= 2 * NH * 28 * 28 * 32) return;
  int lane = idx & 31, r = idx >> 5;
  int ks = r % 28; r /= 28; int tile = r % 28; r /= 28; int h = r % NH; int mat = r / NH;
  int g = lane >> 2, tq = lane & 3;
  float v[8];
  for (int i = 0; i < 8; i++) {
    int row = tile * 16 + g + ((i >> 1) & 1) * 8;
    int col = ks * 16 + tq * 2 + (i & 1) + (i >> 2) * 8;
    float acc = 0.f;
    if (mat == 0) { for (int e = 0; e < 256; e++) acc += b2f(Wq[(row * NH + h) * 256 + e]) * b2f(Wk[(col * NH + h) * 256 + e]); acc *= 0.0625f; }
    else { for (int e = 0; e < 256; e++) acc += b2f(Wo[(h * 256 + e) * DM + row]) * b2f(Wv[(col * NH + h) * 256 + e]); }
    v[i] = acc;
  }
  g_WF[idx] = make_uint4(pack_bf16(v[0], v[1]), pack_bf16(v[2], v[3]), pack_bf16(v[4], v[5]), pack_bf16(v[6], v[7]));
}
__device__ __forceinline__ float wf_elem(int mat, int h, int row, int col) {
  int tile = row >> 4, ks = col >> 4, rr = row & 15, cc = col & 15;
  int lane = (rr & 7) * 4 + ((cc & 7) >> 1);
  int reg = (rr >> 3) + (cc >> 3) * 2;
  uint32_t w = ((const uint32_t*)g_WF)[((((mat * NH + h) * 28 + tile) * 28 + ks) * 32 + lane) * 4 + reg];
  return (cc & 1) ? bf_hi(w) : bf_lo(w);
}
__device__ __forceinline__ void mma16816(float* d, uint32_t a0, uint32_t a1, uint32_t a2, uint32_t a3, uint32_t b0, uint32_t b1) {
  asm volatile("mma.sync.aligned.m16n8k16.row.col.f32.bf16.bf16.f32 {%0,%1,%2,%3}, {%4,%5,%6,%7}, {%8,%9}, {%0,%1,%2,%3};"
    : "+f"(d[0]), "+f"(d[1]), "+f"(d[2]), "+f"(d[3]) : "r"(a0), "r"(a1), "r"(a2), "r"(a3), "r"(b0), "r"(b1));
}
__device__ __forceinline__ void mma1688(float* d, uint32_t a0, uint32_t a1, uint32_t b0) {
  asm volatile("mma.sync.aligned.m16n8k8.row.col.f32.bf16.bf16.f32 {%0,%1,%2,%3}, {%4,%5}, {%6}, {%0,%1,%2,%3};"
    : "+f"(d[0]), "+f"(d[1]), "+f"(d[2]), "+f"(d[3]) : "r"(a0), "r"(a1), "r"(b0));
}
__device__ __forceinline__ uint32_t movm(uint32_t a) { uint32_t d; asm volatile("movmatrix.sync.aligned.m8n8.trans.b16 %0, %1;" : "=r"(d) : "r"(a)); return d; }

__global__ void n_xgemm(const bf16* x) {
  int wid = (blockIdx.x * blockDim.x + threadIdx.x) >> 5, lane = threadIdx.x & 31;
  int seg = wid % NSEG; int r = wid / NSEG;
  int tile = r % 28; r /= 28; int h = r % NH; int mat = r / NH;
  if (mat >= 2) return;
  int g = lane >> 2, tq = lane & 3;
  float d[4][4] = {};
  const uint4* wf = g_WF + (((mat * NH + h) * 28 + tile) * 28) * 32 + lane;
  for (int ks = 0; ks < 28; ks++) {
    uint4 a = wf[ks * 32];
    for (int kg = 0; kg < 4; kg++) {
      const uint32_t* xr = (const uint32_t*)(x + (seg * 32 + kg * 8 + g) * DM + ks * 16 + tq * 2);
      mma16816(d[kg], a.x, a.y, a.z, a.w, xr[0], xr[4]);
    }
  }
  if (mat == 0) {
    for (int kg = 0; kg < 4; kg++) {
      uint32_t b0 = movm(pack_bf16(d[kg][0], d[kg][1])), b1 = movm(pack_bf16(d[kg][2], d[kg][3]));
      g_KF[(((seg * NH + h) * 28 + tile) * 4 + kg) * 32 + lane] = make_uint2(b0, b1);
    }
  } else {
    g_VF[((seg * NH + h) * 56 + tile * 2) * 32 + lane] = make_uint4(pack_bf16(d[0][0], d[0][1]), pack_bf16(d[1][0], d[1][1]), pack_bf16(d[2][0], d[2][1]), pack_bf16(d[3][0], d[3][1]));
    g_VF[((seg * NH + h) * 56 + tile * 2 + 1) * 32 + lane] = make_uint4(pack_bf16(d[0][2], d[0][3]), pack_bf16(d[1][2], d[1][3]), pack_bf16(d[2][2], d[2][3]), pack_bf16(d[3][2], d[3][3]));
  }
}
__global__ void n_zero() {
  int i = blockIdx.x * blockDim.x + threadIdx.x;
  if (i < NSEG * 16 * 32) g_ACC16[i] = make_uint4(0, 0, 0, 0);
  if (i < NSEG) g_xmax[i] = 0.f;
  if (i == 0) g_bmax = 0.f;
  if (i < NH * 56 * 29) g_kv[i] = 0.f;
}
__global__ void n_qkv(const bf16* x, const bf16* w) {
  int i = blockIdx.x * blockDim.x + threadIdx.x;
  if (i >= S_LEN * 1344) return;
  int n = i % 1344, t = i / 1344;
  float acc = 0.f;
  for (int k = 0; k < DM; k++) acc += b2f(x[t * DM + k]) * b2f(w[k * 1344 + n]);
  g_qkv[i] = acc;
}
__global__ void n_phi(const bf16* wphi) {
  int i = blockIdx.x * blockDim.x + threadIdx.x;
  if (i >= S_LEN * 2 * NH) return;
  int h = i % NH, which = (i / NH) % 2, t = i / (2 * NH);
  float p[28]; float mx = -1e30f, mn = 1e30f;
  for (int f = 0; f < 28; f++) {
    float acc = 0.f;
    for (int d = 0; d < 28; d++) acc += g_qkv[t * 1344 + which * 448 + h * 28 + d] * b2f(wphi[(h * 28 + d) * 28 + f]);
    p[f] = acc; mx = fmaxf(mx, acc); mn = fminf(mn, acc);
  }
  float s1 = 0.f, s2 = 0.f;
  for (int f = 0; f < 28; f++) { s1 += __expf(p[f] - mx); s2 += __expf(mn - p[f]); }
  float* o = (which ? g_phik : g_phiq) + (t * NH + h) * 56;
  for (int f = 0; f < 28; f++) { o[f] = __expf(p[f] - mx) / s1; o[28 + f] = __expf(mn - p[f]) / s2; }
}
__global__ void n_kv() {
  int i = blockIdx.x * blockDim.x + threadIdx.x;
  if (i >= 32 * NH * 56 * 29) return;
  int d = i % 29, f = (i / 29) % 56, h = (i / (29 * 56)) % NH, ch = i / (29 * 56 * NH);
  float acc = 0.f;
  for (int t = ch * 64; t < ch * 64 + 64; t++) acc += g_phik[(t * NH + h) * 56 + f] * (d < 28 ? g_qkv[t * 1344 + 896 + h * 28 + d] : 1.f);
  atomicAdd(&g_kv[(h * 56 + f) * 29 + d], acc);
}
__global__ void n_oa() {
  int i = blockIdx.x * blockDim.x + threadIdx.x;
  if (i >= S_LEN * DM) return;
  int c = i % DM, t = i / DM, h = c / 28, d = c % 28;
  float num = 0.f, den = 0.f;
  for (int f = 0; f < 56; f++) { float p = g_phiq[(t * NH + h) * 56 + f]; num += p * g_kv[(h * 56 + f) * 29 + d]; den += p * g_kv[(h * 56 + f) * 29 + 28]; }
  g_oa[i] = num / (den + 1e-6f);
}

__global__ void __launch_bounds__(512) n_x3(const bf16* x, const bf16* wo, const bf16* gate_w, bf16* out) {
  __shared__ uint32_t sP[NH][2][32][10];
  __shared__ float sG[32];
  int seg = blockIdx.x, w = threadIdx.x >> 5, lane = threadIdx.x & 31, g = lane >> 2, tq = lane & 3;
  for (int r = w; r < 32; r += 16) {
    float acc = 0.f;
    for (int k = lane; k < DM; k += 32) acc += b2f(x[(seg * 32 + r) * DM + k]) * b2f(gate_w[k]);
    for (int o = 16; o; o >>= 1) acc += __shfl_xor_sync(0xffffffffu, acc, o);
    if (lane == 0) sG[r] = 1.f / (1.f + __expf(-acc));
  }
  {
    int h = w;
    float s[2][5][4] = {};
    for (int ct = 0; ct < 28; ct++) {
      uint32_t a[2][4];
      for (int m = 0; m < 2; m++) {
        const uint32_t* r0 = (const uint32_t*)(x + (seg * 32 + m * 16 + g) * DM + ct * 16 + tq * 2);
        const uint32_t* r1 = (const uint32_t*)(x + (seg * 32 + m * 16 + g + 8) * DM + ct * 16 + tq * 2);
        a[m][0] = r0[0]; a[m][1] = r1[0]; a[m][2] = r0[4]; a[m][3] = r1[4];
      }
      for (int kg = 0; kg < 4; kg++) {
        uint2 b = g_KF[(((seg * NH + h) * 28 + ct) * 4 + kg) * 32 + lane];
        for (int m = 0; m < 2; m++) mma16816(s[m][1 + kg], a[m][0], a[m][1], a[m][2], a[m][3], b.x, b.y);
      }
      int j = ct / 7, i = ct % 7;
      if (i < 4) {
        uint2 b = g_KMF[(((seg * NH + h) * 4 + j) * 16 + i * 4) * 32 + lane];
        for (int m = 0; m < 2; m++) mma16816(s[m][0], a[m][0], a[m][1], a[m][2], a[m][3], b.x, b.y);
      } else {
        for (int q = 0; q < 4; q++) {
          uint2 b = g_KMF[(((seg * NH + h) * 4 + j) * 16 + q * 4 + (i - 3)) * 32 + lane];
          for (int m = 0; m < 2; m++) mma16816(s[m][0], a[m][0], a[m][1], a[m][2], a[m][3], b.x, b.y);
        }
      }
    }
    for (int m = 0; m < 2; m++) for (int hf = 0; hf < 2; hf++) {
      int t = m * 16 + hf * 8 + g;
      float v[10]; float mx = -1e30f;
      for (int n = 0; n < 5; n++) for (int e = 0; e < 2; e++) {
        float val = s[m][n][hf * 2 + e];
        if (n > 0 && (n - 1) * 8 + tq * 2 + e > t) val = -1e30f;
        v[n * 2 + e] = val; mx = fmaxf(mx, val);
      }
      mx = fmaxf(mx, __shfl_xor_sync(0xffffffffu, mx, 1)); mx = fmaxf(mx, __shfl_xor_sync(0xffffffffu, mx, 2));
      float z = 0.f;
      for (int i = 0; i < 10; i++) { v[i] = __expf(v[i] - mx); z += v[i]; }
      z += __shfl_xor_sync(0xffffffffu, z, 1); z += __shfl_xor_sync(0xffffffffu, z, 2);
      float iz = 1.f / z;
      sP[h][m][lane][hf] = pack_bf16(v[0] * iz, v[1] * iz);
      sP[h][m][lane][2 + hf] = pack_bf16(v[2] * iz, v[3] * iz);
      sP[h][m][lane][4 + hf] = pack_bf16(v[4] * iz, v[5] * iz);
      sP[h][m][lane][6 + hf] = pack_bf16(v[6] * iz, v[7] * iz);
      sP[h][m][lane][8 + hf] = pack_bf16(v[8] * iz, v[9] * iz);
    }
  }
  __syncthreads();
  if (w < 14) {
    float o[2][4][4] = {};
    for (int h = 0; h < NH; h++) {
      for (int n = 0; n < 4; n++) {
        int nt = w * 4 + n;
        uint4 v = g_VF[((seg * NH + h) * 56 + nt) * 32 + lane];
        uint32_t u = g_UF[((seg * NH + h) * 56 + nt) * 32 + lane];
        for (int m = 0; m < 2; m++) {
          const uint32_t* p = sP[h][m][lane];
          mma1688(o[m][n], p[0], p[1], u);
          mma16816(o[m][n], p[2], p[3], p[4], p[5], v.x, v.y);
          mma16816(o[m][n], p[6], p[7], p[8], p[9], v.z, v.w);
        }
      }
    }
    for (int m = 0; m < 2; m++) for (int n = 0; n < 4; n++) for (int i = 0; i < 4; i++) {
      int r = m * 16 + (i >> 1) * 8 + g, c = (w * 4 + n) * 8 + tq * 2 + (i & 1);
      int t = seg * 32 + r;
      float a = 0.f;
      for (int k = 0; k < DM; k++) a += g_oa[t * DM + k] * b2f(wo[k * DM + c]);
      float gt = sG[r];
      out[t * DM + c] = __float2bfloat16(gt * a + (1.f - gt) * o[m][n][i]);
    }
  }
}

__device__ __forceinline__ uint32_t smem_u32(const void* p) { return (uint32_t)__cvta_generic_to_shared(p); }
__device__ __forceinline__ uint32_t mapa(uint32_t a, uint32_t r) { uint32_t o; asm volatile("mapa.shared::cluster.u32 %0, %1, %2;" : "=r"(o) : "r"(a), "r"(r)); return o; }
__device__ __forceinline__ bool try_wait(uint32_t bar, uint32_t parity) {
  uint32_t ok; asm volatile("{\n.reg .pred p;\nmbarrier.try_wait.parity.shared::cta.b64 p, [%1], %2;\nselp.u32 %0, 1, 0, p;\n}" : "=r"(ok) : "r"(bar), "r"(parity) : "memory"); return ok; }
__device__ __forceinline__ void wait_bar(uint32_t bar, uint32_t parity) {
  int n = 0; while (!try_wait(bar, parity)) { if (++n > SPIN_LIMIT) { g_err = 1; break; } } }
__device__ __forceinline__ void arm_bar(uint32_t bar, uint32_t bytes) { asm volatile("mbarrier.arrive.expect_tx.shared::cta.b64 _, [%0], %1;" :: "r"(bar), "r"(bytes) : "memory"); }
__device__ __forceinline__ float4 ld_relaxed4(const void* p) { float4 v; asm volatile("ld.relaxed.gpu.global.v4.f32 {%0,%1,%2,%3}, [%4];" : "=f"(v.x), "=f"(v.y), "=f"(v.z), "=f"(v.w) : "l"(p) : "memory"); return v; }
__device__ __forceinline__ void red4(void* p, float a, float b, float c, float d) { asm volatile("red.relaxed.gpu.global.add.v4.f32 [%0], {%1,%2,%3,%4};" :: "l"(p), "f"(a), "f"(b), "f"(c), "f"(d) : "memory"); }
__device__ __forceinline__ void st_async2(uint32_t dst, float a, float b, uint32_t bar) { asm volatile("st.async.shared::cluster.mbarrier::complete_tx::bytes.v2.f32 [%0], {%1,%2}, [%3];" :: "r"(dst), "f"(a), "f"(b), "r"(bar) : "memory"); }
__device__ __forceinline__ void bulk_g2s(uint32_t dst, const void* src, uint32_t bytes, uint32_t bar) {
  asm volatile("cp.async.bulk.shared::cluster.global.mbarrier::complete_tx::bytes [%0], [%1], %2, [%3];" :: "r"(dst), "l"(src), "r"(bytes), "r"(bar) : "memory"); }
__device__ __forceinline__ unsigned clk() { unsigned c; asm volatile("mov.u32 %0, %%clock;" : "=r"(c) :: "memory"); return c; }
__device__ __forceinline__ float ex2(float x) { float y; asm("ex2.approx.ftz.f32 %0, %1;" : "=f"(y) : "f"(x)); return y; }

#define NST 4
struct RSmem {
  uint2 kf[NST][7][4][32];
  uint4 vf[NST][14][32];
  uint2 memF[28][32];
  float2 sx[4][4][32];
  float2 sm[4][32];
  float2 sred[4][32];
  uint32_t uF[8][32];
  float2 uP[6][4][32];
  uint32_t smax[4];
  unsigned long long bar_ld[NST], bar_sx, bar_sm;
  unsigned ts[64 * 16];
};
#define POLL_DELAY 300
#define STAMP(i)
__device__ __forceinline__ void wait_bar1(uint32_t bar, uint32_t parity) {
#pragma unroll 1
  for (int n = 0; n < SPIN_LIMIT; n++) if (try_wait(bar, parity)) return;
  g_err = 1;
}
__device__ __forceinline__ uint4 ld_relaxed_u4(const void* p) { uint4 v; asm volatile("ld.relaxed.gpu.global.v4.u32 {%0,%1,%2,%3}, [%4];" : "=r"(v.x), "=r"(v.y), "=r"(v.z), "=r"(v.w) : "l"(p) : "memory"); return v; }
__device__ __forceinline__ void red_h8(void* p, uint32_t a, uint32_t b, uint32_t c, uint32_t d) { asm volatile("red.relaxed.gpu.global.add.noftz.v4.f16x2 [%0], {%1,%2,%3,%4};" :: "l"(p), "r"(a), "r"(b), "r"(c), "r"(d) : "memory"); }
__device__ __forceinline__ uint32_t pack_f16(float lo, float hi) { uint32_t r; asm("cvt.rn.f16x2.f32 %0, %1, %2;" : "=r"(r) : "f"(hi), "f"(lo)); return r; }
__device__ __forceinline__ uint32_t h2_to_bf2(uint32_t v) {
  float lo, hi; asm("{.reg .f16 l, h; mov.b32 {l, h}, %2; cvt.f32.f16 %0, l; cvt.f32.f16 %1, h;}" : "=f"(lo), "=f"(hi) : "r"(v)); return pack_bf16(lo, hi); }
__device__ __forceinline__ uint2 lds64(uint32_t a) { uint2 v; asm volatile("ld.shared.v2.u32 {%0,%1}, [%2];" : "=r"(v.x), "=r"(v.y) : "r"(a) : "memory"); return v; }
__device__ __forceinline__ float2 lds64f(uint32_t a) { float2 v; asm volatile("ld.shared.v2.f32 {%0,%1}, [%2];" : "=f"(v.x), "=f"(v.y) : "r"(a) : "memory"); return v; }
__device__ __forceinline__ uint4 lds128(uint32_t a) { uint4 v; asm volatile("ld.shared.v4.u32 {%0,%1,%2,%3}, [%4];" : "=r"(v.x), "=r"(v.y), "=r"(v.z), "=r"(v.w) : "r"(a) : "memory"); return v; }
__device__ __forceinline__ uint32_t lds32(uint32_t a) { uint32_t v; asm volatile("ld.shared.u32 %0, [%1];" : "=r"(v) : "r"(a) : "memory"); return v; }
__device__ __forceinline__ void sts64(uint32_t a, uint32_t x, uint32_t y) { asm volatile("st.shared.v2.u32 [%0], {%1,%2};" :: "r"(a), "r"(x), "r"(y) : "memory"); }
__device__ __forceinline__ void sts64f(uint32_t a, float x, float y) { asm volatile("st.shared.v2.f32 [%0], {%1,%2};" :: "r"(a), "f"(x), "f"(y) : "memory"); }
__device__ __forceinline__ void sts32(uint32_t a, uint32_t x) { asm volatile("st.shared.u32 [%0], %1;" :: "r"(a), "r"(x) : "memory"); }
__device__ __forceinline__ void mma_z(float* d, uint32_t a0, uint32_t a1, uint32_t a2, uint32_t a3, uint32_t b0, uint32_t b1) {
  asm volatile("mma.sync.aligned.m16n8k16.row.col.f32.bf16.bf16.f32 {%0,%1,%2,%3}, {%4,%5,%6,%7}, {%8,%9}, {%10,%10,%10,%10};"
    : "=f"(d[0]), "=f"(d[1]), "=f"(d[2]), "=f"(d[3]) : "r"(a0), "r"(a1), "r"(a2), "r"(a3), "r"(b0), "r"(b1), "f"(0.f));
}
#define OFF(f) ((uint32_t)offsetof(RSmem, f))

__device__ __forceinline__ void stage1(const uint4 (&W)[49], float (&acc)[7][4], uint32_t r0, uint32_t r1, uint32_t r2, uint32_t r3) {
  uint2 bq[2][4];
  bq[0][0] = lds64(r0); bq[0][1] = lds64(r1); bq[0][2] = lds64(r2); bq[0][3] = lds64(r3);
#pragma unroll
  for (int e = 0; e < 7; e++) {
    uint2* b = bq[e & 1];
    if (e < 6) { uint2* n = bq[(e + 1) & 1]; n[0] = lds64(r0 + (e + 1) * 1024); n[1] = lds64(r1 + (e + 1) * 1024); n[2] = lds64(r2 + (e + 1) * 1024); n[3] = lds64(r3 + (e + 1) * 1024); }
#pragma unroll
    for (int x = 0; x < 3; x++) {
      const uint4& w = W[28 + 3 * e + x];
      if (e == 0) mma_z(acc[4 + x], w.x, w.y, w.z, w.w, b[0].x, b[0].y); else mma16816(acc[4 + x], w.x, w.y, w.z, w.w, b[0].x, b[0].y);
    }
#pragma unroll
    for (int i = 0; i < 4; i++) {
      const uint4& w = W[4 * e + i];
      if (e == 0) mma_z(acc[i], w.x, w.y, w.z, w.w, b[i].x, b[i].y); else mma16816(acc[i], w.x, w.y, w.z, w.w, b[i].x, b[i].y);
    }
  }
}
__device__ __forceinline__ void poll_mem(const uint4* p, uint32_t a_pair, uint32_t a_single) {
  uint4 v0, v1;
  int n = 0; bool done;
#pragma unroll 1
  do {
    v0 = ld_relaxed_u4(p); v1 = ld_relaxed_u4(p + 32);
    done = __all_sync(0xffffffffu, ((v0.w & v1.w) >> 16) == 0x4C00u && ((v0.w | v1.w) >> 16) == 0x4C00u);
  } while (!done && ++n < SPIN_LIMIT);
  if (!done) g_err = 2;
  sts64(a_pair, h2_to_bf2(v0.x), h2_to_bf2(v0.y));
  sts64(a_pair + 256, h2_to_bf2(v0.z), h2_to_bf2(v1.x));
  sts64(a_pair + 512, h2_to_bf2(v1.y), h2_to_bf2(v1.z));
  sts32(a_single, h2_to_bf2(__byte_perm(v0.w, v1.w, 0x5410)));
}

__global__ void __cluster_dims__(4, 1, 1) __launch_bounds__(256, 1) r_kernel(const bf16* mem0, int poll_delay) {
  extern __shared__ __align__(128) unsigned char smem_raw[];
  RSmem& sm = *reinterpret_cast<RSmem*>(smem_raw);
  const int h = blockIdx.x >> 2, j = blockIdx.x & 3;
  const int w = threadIdx.x >> 5, lane = threadIdx.x & 31, q = w & 3;
  const bool isA = w < 4;
  const uint32_t sb = smem_u32(smem_raw);
  const uint32_t bar_ld = sb + OFF(bar_ld), bar_sx = sb + OFF(bar_sx), bar_sm = sb + OFF(bar_sm);
  if (threadIdx.x == 0) {
    for (int i = 0; i < NST; i++) asm volatile("mbarrier.init.shared::cta.b64 [%0], 1;" :: "r"(bar_ld + 8 * i));
    asm volatile("mbarrier.init.shared::cta.b64 [%0], 1;" :: "r"(bar_sx));
    asm volatile("mbarrier.init.shared::cta.b64 [%0], 1;" :: "r"(bar_sm));
    asm volatile("fence.mbarrier_init.release.cluster;" ::: "memory");
    arm_bar(bar_sx, 4096); arm_bar(bar_sm, 1024);
    for (int s = 0; s < NST - 1; s++) {
      arm_bar(bar_ld + 8 * s, 14336);
      bulk_g2s(smem_u32(sm.kf[s]), g_KF + ((s * NH + h) * 28 + 7 * j) * 128, 7168, bar_ld + 8 * s);
      bulk_g2s(smem_u32(sm.vf[s]), g_VF + ((s * NH + h) * 56 + 14 * j) * 32, 7168, bar_ld + 8 * s);
    }
  }
  uint4 W[49];
  {
    const uint4* wf = g_WF + (((isA ? 0 : 1) * NH + h) * 28) * 28 * 32 + lane;
#pragma unroll
    for (int i = 0; i < 28; i++) W[i] = wf[((7 * j + q) * 28 + ((i & ~3) | ((i + q) & 3))) * 32];
#pragma unroll
    for (int e = 0; e < 7; e++)
#pragma unroll
      for (int x = 0; x < 3; x++) W[28 + e * 3 + x] = wf[((7 * j + 4 + x) * 28 + 4 * e + q) * 32];
  }
  for (int i = threadIdx.x; i < 28 * 32; i += 256) {
    int ks = i >> 5, l = i & 31;
    const uint32_t* r = (const uint32_t*)(mem0 + (l >> 2) * DM + ks * 16 + (l & 3) * 2);
    sm.memF[ks][l] = make_uint2(r[0], r[4]);
  }
  asm volatile("barrier.cluster.arrive.release.aligned;\nbarrier.cluster.wait.acquire.aligned;" ::: "memory");

  const uint32_t l8 = sb + lane * 8;
  const uint32_t mf = l8 + OFF(memF);
  const uint32_t pa_pair = mf + ((w >> 1) * 7 + (w & 1) * 4) * 256, pa_single = mf + ((w >> 1) * 7 + 3) * 256 + (w & 1) * 4;
  const uint4* pollp = g_ACC16 + (16 + w * 2) * 32 + lane;
  const uint32_t r0 = mf + ((0 + q) & 3) * 256, r1 = mf + ((1 + q) & 3) * 256, r2 = mf + ((2 + q) & 3) * 256, r3 = mf + ((3 + q) & 3) * 256;
  const uint32_t mslice = mf + j * 7 * 256;
  const float LOG2E = 1.4426950408889634f;

  if (isA) {
    const uint32_t dst_sm = mapa(l8 + OFF(sm) + j * 256, q), dst_bar = mapa(bar_sm, q);
    const int nt0 = q < 2 ? q * 3 : 8 + (q - 2) * 3, nts = 6 + (q >> 1);
    float inv = 1.f;
    uint32_t sc_bf = 0x3f803f80u;
#pragma unroll 1
    for (int s = 0; s < NSEG; s++) {
      const int st = s & (NST - 1);
      STAMP(0);
      if (s > 0) { poll_mem(pollp, pa_pair, pa_single); pollp += 512; }
      STAMP(1);
      asm volatile("bar.sync 0, 256;" ::: "memory");
      STAMP(2);
      float acc[7][4];
      stage1(W, acc, r0, r1, r2, r3);
      asm volatile("bar.arrive 1, 256;" ::: "memory");
      uint2 a0 = lds64(mslice + q * 256), a1 = lds64(mslice + 1024), a2 = lds64(mslice + 1280), a3 = lds64(mslice + 1536);
      STAMP(3);
      uint32_t kb[4][2];
#pragma unroll
      for (int x = 0; x < 3; x++) { kb[1 + x][0] = movm(pack_bf16(acc[4 + x][0], acc[4 + x][1])); kb[1 + x][1] = movm(pack_bf16(acc[4 + x][2], acc[4 + x][3])); }
      float d1[4], d2[4], d3[4], d0[4];
      mma_z(d1, a1.x, 0u, a1.y, 0u, kb[1][0], kb[1][1]);
      mma_z(d2, a2.x, 0u, a2.y, 0u, kb[2][0], kb[2][1]);
      mma_z(d3, a3.x, 0u, a3.y, 0u, kb[3][0], kb[3][1]);
      kb[0][0] = movm(pack_bf16((acc[0][0] + acc[1][0]) + (acc[2][0] + acc[3][0]), (acc[0][1] + acc[1][1]) + (acc[2][1] + acc[3][1])));
      kb[0][1] = movm(pack_bf16((acc[0][2] + acc[1][2]) + (acc[2][2] + acc[3][2]), (acc[0][3] + acc[1][3]) + (acc[2][3] + acc[3][3])));
      mma_z(d0, a0.x, 0u, a0.y, 0u, kb[0][0], kb[0][1]);
      sts64f(l8 + OFF(sred) + q * 256, ((d1[0] + d2[0]) + d3[0]) + d0[0], ((d1[1] + d2[1]) + d3[1]) + d0[1]);
      asm volatile("bar.sync 2, 128;" ::: "memory");
      {
        float2 t0 = lds64f(l8 + OFF(sred)), t1 = lds64f(l8 + OFF(sred) + 256), t2 = lds64f(l8 + OFF(sred) + 512), t3 = lds64f(l8 + OFF(sred) + 768);
        st_async2(dst_sm, (t0.x + t1.x) + (t2.x + t3.x), (t0.y + t1.y) + (t2.y + t3.y), dst_bar);
      }
      STAMP(4);
      float o[4][4], oz[4];
      float mx;
      {
        const uint32_t vb = sb + OFF(vf) + st * 7168 + lane * 16;
        wait_bar1(bar_ld + 8 * st, (s / NST) & 1);
        wait_bar1(bar_sx, s & 1);
        float sx[8];
        const float c1 = LOG2E * inv;
#pragma unroll
        for (int kg = 0; kg < 4; kg++) {
          float2 p0 = lds64f(l8 + OFF(sx) + kg * 256), p1 = lds64f(l8 + OFF(sx) + 1024 + kg * 256), p2 = lds64f(l8 + OFF(sx) + 2048 + kg * 256), p3 = lds64f(l8 + OFF(sx) + 3072 + kg * 256);
          sx[2 * kg] = ((p0.x + p1.x) + (p2.x + p3.x)) * c1; sx[2 * kg + 1] = ((p0.y + p1.y) + (p2.y + p3.y)) * c1;
        }
        uint4 v0 = lds128(vb + nt0 * 512), v1 = lds128(vb + nt0 * 512 + 512), v2 = lds128(vb + nt0 * 512 + 1024), v3 = lds128(vb + nts * 512);
        mx = fmaxf(fmaxf(fmaxf(sx[0], sx[1]), fmaxf(sx[2], sx[3])), fmaxf(fmaxf(sx[4], sx[5]), fmaxf(sx[6], sx[7])));
        mx = fmaxf(mx, __shfl_xor_sync(0xffffffffu, mx, 1)); mx = fmaxf(mx, __shfl_xor_sync(0xffffffffu, mx, 2));
#pragma unroll
        for (int i = 0; i < 8; i++) sx[i] = ex2(sx[i] - mx);
        uint32_t p0 = pack_bf16(sx[0], sx[1]), p1 = pack_bf16(sx[2], sx[3]), p2 = pack_bf16(sx[4], sx[5]), p3 = pack_bf16(sx[6], sx[7]);
        mma_z(o[0], p0, 0u, p1, 0u, v0.x, v0.y); mma_z(o[1], p0, 0u, p1, 0u, v1.x, v1.y); mma_z(o[2], p0, 0u, p1, 0u, v2.x, v2.y); mma_z(o[3], p0, 0u, p1, 0u, v3.x, v3.y);
        mma_z(oz, p0, 0u, p1, 0u, 0x3f803f80u, 0x3f803f80u);
        mma16816(o[0], p2, 0u, p3, 0u, v0.z, v0.w); mma16816(o[1], p2, 0u, p3, 0u, v1.z, v1.w); mma16816(o[2], p2, 0u, p3, 0u, v2.z, v2.w); mma16816(o[3], p2, 0u, p3, 0u, v3.z, v3.w);
        mma16816(oz, p2, 0u, p3, 0u, 0x3f803f80u, 0x3f803f80u);
      }
      STAMP(5);
      asm volatile("bar.sync 3, 256;" ::: "memory");
      uint32_t u[4];
      u[3] = lds32(sb + OFF(uF) + nts * 128 + lane * 4);
      if (q < 2) {
#pragma unroll
        for (int n = 0; n < 3; n++) u[n] = lds32(sb + OFF(uF) + (nt0 + n) * 128 + lane * 4);
      } else {
#pragma unroll
        for (int n = 0; n < 3; n++) {
          const uint32_t pp = l8 + OFF(uP) + (nt0 - 8 + n) * 1024;
          float2 t0 = lds64f(pp), t1 = lds64f(pp + 256), t2 = lds64f(pp + 512), t3 = lds64f(pp + 768);
          u[n] = pack_bf16((t0.x + t1.x) + (t2.x + t3.x), (t0.y + t1.y) + (t2.y + t3.y));
        }
      }
      float nsc, ninv;
      {
        uint4 m4 = lds128(sb + OFF(smax));
        uint32_t mb = max(max(m4.x, m4.y), max(m4.z, m4.w));
        float mh = fmaxf(__uint_as_float(mb << 16) * inv, g_xmax[s]);
        float bound = mh * g_bmax;
        int e = (int)(__float_as_uint(bound) >> 23) - 127 + 10;
        int se = min(max(15 - e, -100), 100);
        nsc = __uint_as_float((uint32_t)(127 + se) << 23); ninv = __uint_as_float((uint32_t)(127 - se) << 23);
      }
      STAMP(6);
      wait_bar1(bar_sm, s & 1);
      STAMP(7);
      {
        float2 t0 = lds64f(l8 + OFF(sm)), t1 = lds64f(l8 + OFF(sm) + 256), t2 = lds64f(l8 + OFF(sm) + 512), t3 = lds64f(l8 + OFF(sm) + 768);
        const float c1 = LOG2E * inv;
        float s0 = ((t0.x + t1.x) + (t2.x + t3.x)) * inv * c1, s1 = ((t0.y + t1.y) + (t2.y + t3.y)) * inv * c1;
        float m = fmaxf(fmaxf(s0, s1), mx);
        m = fmaxf(m, __shfl_xor_sync(0xffffffffu, m, 1)); m = fmaxf(m, __shfl_xor_sync(0xffffffffu, m, 2));
        float e0 = ex2(s0 - m), e1 = ex2(s1 - m), al = ex2(mx - m);
        uint32_t pm = pack_bf16(e0 * inv, e1 * inv);
        oz[0] *= al; mma1688(oz, pm, 0u, sc_bf);
#pragma unroll
        for (int n = 0; n < 4; n++) { o[n][0] *= al; o[n][1] *= al; mma1688(o[n], pm, 0u, u[n]); }
        float iz; asm("rcp.approx.ftz.f32 %0, %1;" : "=f"(iz) : "f"(oz[0]));
        iz *= nsc;
        if (s < NSEG - 1)
          red_h8(g_ACC16 + ((s + 1) * 16 + j * 4 + q) * 32 + lane, pack_f16(o[0][0] * iz, o[0][1] * iz), pack_f16(o[1][0] * iz, o[1][1] * iz), pack_f16(o[2][0] * iz, o[2][1] * iz),
               pack_f16(((q & 1) ? o[3][1] : o[3][0]) * iz, 1.f));
      }
      unsigned tred = clk();
      asm volatile("bar.arrive 4, 256;" ::: "memory");
      STAMP(8);
      {
        const __nv_bfloat162 iv = __float2bfloat162_rn(inv);
        auto us = [&](uint32_t v) { __nv_bfloat162 t = __hmul2(*reinterpret_cast<__nv_bfloat162*>(&v), iv); return *reinterpret_cast<uint32_t*>(&t); };
        uint2* kmf = g_KMF + (((s * NH + h) * 4 + j) * 16 + q * 4) * 32 + lane;
#pragma unroll
        for (int a = 0; a < 4; a++) kmf[a * 32] = make_uint2(us(kb[a][0]), us(kb[a][1]));
        uint32_t* uf = g_UF + ((s * NH + h) * 56 + 14 * j) * 32 + lane;
#pragma unroll
        for (int n = 0; n < 3; n++) uf[(nt0 + n) * 32] = us(u[n]);
        if ((q & 1) == 0) uf[nts * 32] = us(u[3]);
      }
      inv = ninv; { uint32_t t = __float_as_uint(nsc) >> 16; sc_bf = t | (t << 16); }
      while (clk() - tred < (unsigned)poll_delay) {}
    }
  } else {
    const uint32_t dsx = l8 + OFF(sx) + j * 1024 + q * 256;
#pragma unroll 1
    for (int s = 0; s < NSEG; s++) {
      const int st = s & (NST - 1);
      if (s > 0) { poll_mem(pollp, pa_pair, pa_single); pollp += 512; }
      wait_bar1(bar_ld + 8 * st, (s / NST) & 1);
      uint2 kb[7];
#pragma unroll
      for (int i = 0; i < 7; i++) kb[i] = lds64(l8 + OFF(kf) + st * 7168 + i * 1024 + q * 256);
      asm volatile("bar.sync 0, 256;" ::: "memory");
      {
        float d[4][4];
#pragma unroll
        for (int i = 0; i < 7; i++) {
          uint2 a = lds64(mslice + i * 256);
          if (i < 4) mma_z(d[i], a.x, 0u, a.y, 0u, kb[i].x, kb[i].y); else mma16816(d[i - 4], a.x, 0u, a.y, 0u, kb[i].x, kb[i].y);
        }
        float s0 = (d[0][0] + d[1][0]) + (d[2][0] + d[3][0]), s1 = (d[0][1] + d[1][1]) + (d[2][1] + d[3][1]);
#pragma unroll
        for (int r = 0; r < 4; r++) st_async2(mapa(dsx, r), s0, s1, mapa(bar_sx, r));
      }
      STAMP(9);
      {
        uint32_t m = 0;
#pragma unroll
        for (int i = 0; i < 7; i++) {
          uint2 a = lds64(mf + (q * 7 + i) * 256);
          m = __vmaxu2(m, __vmaxu2(a.x & 0x7fff7fffu, a.y & 0x7fff7fffu));
        }
        m = max(m & 0xffffu, m >> 16);
        m = __reduce_max_sync(0xffffffffu, m);
        if (lane == 0) sts32(sb + OFF(smax) + q * 4, m);
      }
      asm volatile("bar.sync 1, 256;" ::: "memory");
      STAMP(10);
      float acc[7][4];
      stage1(W, acc, r0, r1, r2, r3);
#pragma unroll
      for (int x = 0; x < 3; x++) { sts64f(l8 + OFF(uP) + (2 * x) * 1024 + q * 256, acc[4 + x][0], acc[4 + x][1]); sts64f(l8 + OFF(uP) + (2 * x + 1) * 1024 + q * 256, acc[4 + x][2], acc[4 + x][3]); }
      sts32(sb + OFF(uF) + (2 * q) * 128 + lane * 4, pack_bf16((acc[0][0] + acc[1][0]) + (acc[2][0] + acc[3][0]), (acc[0][1] + acc[1][1]) + (acc[2][1] + acc[3][1])));
      sts32(sb + OFF(uF) + (2 * q + 1) * 128 + lane * 4, pack_bf16((acc[0][2] + acc[1][2]) + (acc[2][2] + acc[3][2]), (acc[0][3] + acc[1][3]) + (acc[2][3] + acc[3][3])));
      asm volatile("bar.arrive 3, 256;" ::: "memory");
      STAMP(11);
      if (threadIdx.x == 128 && s + NST - 1 < NSEG) {
        int s2 = s + NST - 1, st2 = s2 & (NST - 1);
        arm_bar(bar_ld + 8 * st2, 14336);
        bulk_g2s(smem_u32(sm.kf[st2]), g_KF + ((s2 * NH + h) * 28 + 7 * j) * 128, 7168, bar_ld + 8 * st2);
        bulk_g2s(smem_u32(sm.vf[st2]), g_VF + ((s2 * NH + h) * 56 + 14 * j) * 32, 7168, bar_ld + 8 * st2);
      }
      __syncwarp();
      asm volatile("bar.sync 4, 256;" ::: "memory");
      unsigned tred = clk();
      if (threadIdx.x == 160) { arm_bar(bar_sx, 4096); arm_bar(bar_sm, 1024); }
      __syncwarp();
      while (clk() - tred < (unsigned)poll_delay) {}
    }
  }
  asm volatile("barrier.cluster.arrive.release.aligned;\nbarrier.cluster.wait.acquire.aligned;" ::: "memory");
}

__global__ void n_stats(const bf16* x) {
  if (blockIdx.x < 64) {
    float m = 0.f;
    for (int i = threadIdx.x; i < 32 * DM; i += 256) m = fmaxf(m, fabsf(b2f(x[blockIdx.x * 32 * DM + i])));
    atomicMax((unsigned*)&g_xmax[blockIdx.x], __float_as_uint(m));
  } else {
    int r = (blockIdx.x - 64) * 256 + threadIdx.x;
    if (r < NH * DM) { float a = 0.f; for (int k = 0; k < DM; k++) { float v = wf_elem(1, r / DM, r % DM, k); a += v * v; } atomicMax((unsigned*)&g_bmax, __float_as_uint(sqrtf(a))); }
  }
}

int g_poll_delay = POLL_DELAY;
extern "C" void kernel_launch(void* const* d_in, const int* in_sizes, int n_in, void* d_out, int out_size) {
  const bf16* x = (const bf16*)d_in[0];
  const bf16* wqkv = (const bf16*)d_in[1];
  const bf16* wphi = (const bf16*)d_in[2];
  const bf16* wo_a = (const bf16*)d_in[3];
  const bf16* mem0 = (const bf16*)d_in[5];
  const bf16* Wq = (const bf16*)d_in[6];
  const bf16* Wk = (const bf16*)d_in[7];
  const bf16* Wv = (const bf16*)d_in[8];
  const bf16* Wo = (const bf16*)d_in[9];
  const bf16* gate_w = (const bf16*)d_in[11];
  bf16* out = (bf16*)d_out;
  cudaFuncSetAttribute(r_kernel, cudaFuncAttributeMaxDynamicSharedMemorySize, (int)sizeof(RSmem));
  n_zero<<<(NSEG * 40 * 32 + 255) / 256, 256>>>();
  n_prep<<<(2 * NH * 28 * 28 * 32 + 255) / 256, 256>>>(Wq, Wk, Wv, Wo);
  n_stats<<<64 + 28, 256>>>(x);
  n_xgemm<<<2 * NH * 28 * NSEG * 32 / 256, 256>>>(x);
  r_kernel<<<64, 256, sizeof(RSmem)>>>(mem0, g_poll_delay);
  n_qkv<<<(S_LEN * 1344 + 255) / 256, 256>>>(x, wqkv);
  n_phi<<<(S_LEN * 2 * NH + 255) / 256, 256>>>(wphi);
  n_kv<<<(32 * NH * 56 * 29 + 255) / 256, 256>>>();
  n_oa<<<(S_LEN * DM + 255) / 256, 256>>>();
  n_x3<<<NSEG, 512>>>(x, wo_a, gate_w, out);
}
```

```cpp
#include <cuda_runtime.h>
#include <cuda_bf16.h>
#include <stdint.h>
#include <stddef.h>

typedef __nv_bfloat16 bf16;
#define S_LEN 2048
#define DM 448
#define NH 16
#define NSEG 64
#define SPIN_LIMIT (1 << 22)

__device__ uint4 g_WF[2 * NH * 28 * 28 * 32];
__device__ uint2 g_KF[NSEG * NH * 28 * 4 * 32];
__device__ uint4 g_VF[NSEG * NH * 56 * 32];
__device__ uint2 g_KMF[NSEG * NH * 4 * 16 * 32];
__device__ uint32_t g_UF[NSEG * NH * 56 * 32];
__device__ uint4 g_ACC16[(NSEG + 2) * 16 * 32];
__device__ float g_xmax[NSEG];
__device__ float g_bmax;
__device__ float g_qkv[S_LEN * 1344];
__device__ float g_phiq[S_LEN * NH * 56];
__device__ float g_phik[S_LEN * NH * 56];
__device__ float g_kv[NH * 56 * 29];
__device__ float g_oa[S_LEN * DM];
__device__ int g_err;
__device__ unsigned g_ts[64 * 64 * 16];

__device__ __forceinline__ uint32_t pack_bf16(float lo, float hi) {
  uint32_t r; asm("cvt.rn.bf16x2.f32 %0, %1, %2;" : "=r"(r) : "f"(hi), "f"(lo)); return r;
}
__device__ __forceinline__ float bf_lo(uint32_t v) { return __uint_as_float(v << 16); }
__device__ __forceinline__ float bf_hi(uint32_t v) { return __uint_as_float(v & 0xffff0000u); }
__device__ __forceinline__ float b2f(bf16 v) { return __bfloat162float(v); }

__global__ void n_prep(const bf16* Wq, const bf16* Wk, const bf16* Wv, const bf16* Wo) {
  int idx = blockIdx.x * blockDim.x + threadIdx.x;
  if (idx >= 2 * NH * 28 * 28 * 32) return;
  int lane = idx & 31, r = idx >> 5;
  int ks = r % 28; r /= 28; int tile = r % 28; r /= 28; int h = r % NH; int mat = r / NH;
  int g = lane >> 2, tq = lane & 3;
  float v[8];
  for (int i = 0; i < 8; i++) {
    int row = tile * 16 + g + ((i >> 1) & 1) * 8;
    int col = ks * 16 + tq * 2 + (i & 1) + (i >> 2) * 8;
    float acc = 0.f;
    if (mat == 0) { for (int e = 0; e < 256; e++) acc += b2f(Wq[(row * NH + h) * 256 + e]) * b2f(Wk[(col * NH + h) * 256 + e]); acc *= 0.0625f; }
    else { for (int e = 0; e < 256; e++) acc += b2f(Wo[(h * 256 + e) * DM + row]) * b2f(Wv[(col * NH + h) * 256 + e]); }
    v[i] = acc;
  }
  g_WF[idx] = make_uint4(pack_bf16(v[0], v[1]), pack_bf16(v[2], v[3]), pack_bf16(v[4], v[5]), pack_bf16(v[6], v[7]));
}
__device__ __forceinline__ float wf_elem(int mat, int h, int row, int col) {
  int tile = row >> 4, ks = col >> 4, rr = row & 15, cc = col & 15;
  int lane = (rr & 7) * 4 + ((cc & 7) >> 1);
  int reg = (rr >> 3) + (cc >> 3) * 2;
  uint32_t w = ((const uint32_t*)g_WF)[((((mat * NH + h) * 28 + tile) * 28 + ks) * 32 + lane) * 4 + reg];
  return (cc & 1) ? bf_hi(w) : bf_lo(w);
}
__device__ __forceinline__ void mma16816(float* d, uint32_t a0, uint32_t a1, uint32_t a2, uint32_t a3, uint32_t b0, uint32_t b1) {
  asm volatile("mma.sync.aligned.m16n8k16.row.col.f32.bf16.bf16.f32 {%0,%1,%2,%3}, {%4,%5,%6,%7}, {%8,%9}, {%0,%1,%2,%3};"
    : "+f"(d[0]), "+f"(d[1]), "+f"(d[2]), "+f"(d[3]) : "r"(a0), "r"(a1), "r"(a2), "r"(a3), "r"(b0), "r"(b1));
}
__device__ __forceinline__ void mma1688(float* d, uint32_t a0, uint32_t a1, uint32_t b0) {
  asm volatile("mma.sync.aligned.m16n8k8.row.col.f32.bf16.bf16.f32 {%0,%1,%2,%3}, {%4,%5}, {%6}, {%0,%1,%2,%3};"
    : "+f"(d[0]), "+f"(d[1]), "+f"(d[2]), "+f"(d[3]) : "r"(a0), "r"(a1), "r"(b0));
}
__device__ __forceinline__ uint32_t movm(uint32_t a) { uint32_t d; asm volatile("movmatrix.sync.aligned.m8n8.trans.b16 %0, %1;" : "=r"(d) : "r"(a)); return d; }

__global__ void n_xgemm(const bf16* x) {
  int wid = (blockIdx.x * blockDim.x + threadIdx.x) >> 5, lane = threadIdx.x & 31;
  int seg = wid % NSEG; int r = wid / NSEG;
  int tile = r % 28; r /= 28; int h = r % NH; int mat = r / NH;
  if (mat >= 2) return;
  int g = lane >> 2, tq = lane & 3;
  float d[4][4] = {};
  const uint4* wf = g_WF + (((mat * NH + h) * 28 + tile) * 28) * 32 + lane;
  for (int ks = 0; ks < 28; ks++) {
    uint4 a = wf[ks * 32];
    for (int kg = 0; kg < 4; kg++) {
      const uint32_t* xr = (const uint32_t*)(x + (seg * 32 + kg * 8 + g) * DM + ks * 16 + tq * 2);
      mma16816(d[kg], a.x, a.y, a.z, a.w, xr[0], xr[4]);
    }
  }
  if (mat == 0) {
    for (int kg = 0; kg < 4; kg++) {
      uint32_t b0 = movm(pack_bf16(d[kg][0], d[kg][1])), b1 = movm(pack_bf16(d[kg][2], d[kg][3]));
      g_KF[(((seg * NH + h) * 28 + tile) * 4 + kg) * 32 + lane] = make_uint2(b0, b1);
    }
  } else {
    g_VF[((seg * NH + h) * 56 + tile * 2) * 32 + lane] = make_uint4(pack_bf16(d[0][0], d[0][1]), pack_bf16(d[1][0], d[1][1]), pack_bf16(d[2][0], d[2][1]), pack_bf16(d[3][0], d[3][1]));
    g_VF[((seg * NH + h) * 56 + tile * 2 + 1) * 32 + lane] = make_uint4(pack_bf16(d[0][2], d[0][3]), pack_bf16(d[1][2], d[1][3]), pack_bf16(d[2][2], d[2][3]), pack_bf16(d[3][2], d[3][3]));
  }
}
__global__ void n_zero() {
  int i = blockIdx.x * blockDim.x + threadIdx.x;
  if (i < (NSEG + 2) * 16 * 32) g_ACC16[i] = make_uint4(0, 0, 0, 0);
  if (i < NSEG) g_xmax[i] = 0.f;
  if (i == 0) g_bmax = 0.f;
  if (i < NH * 56 * 29) g_kv[i] = 0.f;
}
__global__ void n_qkv(const bf16* x, const bf16* w) {
  int i = blockIdx.x * blockDim.x + threadIdx.x;
  if (i >= S_LEN * 1344) return;
  int n = i % 1344, t = i / 1344;
  float acc = 0.f;
  for (int k = 0; k < DM; k++) acc += b2f(x[t * DM + k]) * b2f(w[k * 1344 + n]);
  g_qkv[i] = acc;
}
__global__ void n_phi(const bf16* wphi) {
  int i = blockIdx.x * blockDim.x + threadIdx.x;
  if (i >= S_LEN * 2 * NH) return;
  int h = i % NH, which = (i / NH) % 2, t = i / (2 * NH);
  float p[28]; float mx = -1e30f, mn = 1e30f;
  for (int f = 0; f < 28; f++) {
    float acc = 0.f;
    for (int d = 0; d < 28; d++) acc += g_qkv[t * 1344 + which * 448 + h * 28 + d] * b2f(wphi[(h * 28 + d) * 28 + f]);
    p[f] = acc; mx = fmaxf(mx, acc); mn = fminf(mn, acc);
  }
  float s1 = 0.f, s2 = 0.f;
  for (int f = 0; f < 28; f++) { s1 += __expf(p[f] - mx); s2 += __expf(mn - p[f]); }
  float* o = (which ? g_phik : g_phiq) + (t * NH + h) * 56;
  for (int f = 0; f < 28; f++) { o[f] = __expf(p[f] - mx) / s1; o[28 + f] = __expf(mn - p[f]) / s2; }
}
__global__ void n_kv() {
  int i = blockIdx.x * blockDim.x + threadIdx.x;
  if (i >= 32 * NH * 56 * 29) return;
  int d = i % 29, f = (i / 29) % 56, h = (i / (29 * 56)) % NH, ch = i / (29 * 56 * NH);
  float acc = 0.f;
  for (int t = ch * 64; t < ch * 64 + 64; t++) acc += g_phik[(t * NH + h) * 56 + f] * (d < 28 ? g_qkv[t * 1344 + 896 + h * 28 + d] : 1.f);
  atomicAdd(&g_kv[(h * 56 + f) * 29 + d], acc);
}
__global__ void n_oa() {
  int i = blockIdx.x * blockDim.x + threadIdx.x;
  if (i >= S_LEN * DM) return;
  int c = i % DM, t = i / DM, h = c / 28, d = c % 28;
  float num = 0.f, den = 0.f;
  for (int f = 0; f < 56; f++) { float p = g_phiq[(t * NH + h) * 56 + f]; num += p * g_kv[(h * 56 + f) * 29 + d]; den += p * g_kv[(h * 56 + f) * 29 + 28]; }
  g_oa[i] = num / (den + 1e-6f);
}

__global__ void __launch_bounds__(512) n_x3(const bf16* x, const bf16* wo, const bf16* gate_w, bf16* out) {
  __shared__ uint32_t sP[NH][2][32][10];
  __shared__ float sG[32];
  int seg = blockIdx.x, w = threadIdx.x >> 5, lane = threadIdx.x & 31, g = lane >> 2, tq = lane & 3;
  for (int r = w; r < 32; r += 16) {
    float acc = 0.f;
    for (int k = lane; k < DM; k += 32) acc += b2f(x[(seg * 32 + r) * DM + k]) * b2f(gate_w[k]);
    for (int o = 16; o; o >>= 1) acc += __shfl_xor_sync(0xffffffffu, acc, o);
    if (lane == 0) sG[r] = 1.f / (1.f + __expf(-acc));
  }
  {
    int h = w;
    float s[2][5][4] = {};
    for (int ct = 0; ct < 28; ct++) {
      uint32_t a[2][4];
      for (int m = 0; m < 2; m++) {
        const uint32_t* r0 = (const uint32_t*)(x + (seg * 32 + m * 16 + g) * DM + ct * 16 + tq * 2);
        const uint32_t* r1 = (const uint32_t*)(x + (seg * 32 + m * 16 + g + 8) * DM + ct * 16 + tq * 2);
        a[m][0] = r0[0]; a[m][1] = r1[0]; a[m][2] = r0[4]; a[m][3] = r1[4];
      }
      for (int kg = 0; kg < 4; kg++) {
        uint2 b = g_KF[(((seg * NH + h) * 28 + ct) * 4 + kg) * 32 + lane];
        for (int m = 0; m < 2; m++) mma16816(s[m][1 + kg], a[m][0], a[m][1], a[m][2], a[m][3], b.x, b.y);
      }
      int j = ct / 7, i = ct % 7;
      if (i < 4) {
        uint2 b = g_KMF[(((seg * NH + h) * 4 + j) * 16 + i * 4) * 32 + lane];
        for (int m = 0; m < 2; m++) mma16816(s[m][0], a[m][0], a[m][1], a[m][2], a[m][3], b.x, b.y);
      } else {
        for (int q = 0; q < 4; q++) {
          uint2 b = g_KMF[(((seg * NH + h) * 4 + j) * 16 + q * 4 + (i - 3)) * 32 + lane];
          for (int m = 0; m < 2; m++) mma16816(s[m][0], a[m][0], a[m][1], a[m][2], a[m][3], b.x, b.y);
        }
      }
    }
    for (int m = 0; m < 2; m++) for (int hf = 0; hf < 2; hf++) {
      int t = m * 16 + hf * 8 + g;
      float v[10]; float mx = -1e30f;
      for (int n = 0; n < 5; n++) for (int e = 0; e < 2; e++) {
        float val = s[m][n][hf * 2 + e];
        if (n > 0 && (n - 1) * 8 + tq * 2 + e > t) val = -1e30f;
        v[n * 2 + e] = val; mx = fmaxf(mx, val);
      }
      mx = fmaxf(mx, __shfl_xor_sync(0xffffffffu, mx, 1)); mx = fmaxf(mx, __shfl_xor_sync(0xffffffffu, mx, 2));
      float z = 0.f;
      for (int i = 0; i < 10; i++) { v[i] = __expf(v[i] - mx); z += v[i]; }
      z += __shfl_xor_sync(0xffffffffu, z, 1); z += __shfl_xor_sync(0xffffffffu, z, 2);
      float iz = 1.f / z;
      sP[h][m][lane][hf] = pack_bf16(v[0] * iz, v[1] * iz);
      sP[h][m][lane][2 + hf] = pack_bf16(v[2] * iz, v[3] * iz);
      sP[h][m][lane][4 + hf] = pack_bf16(v[4] * iz, v[5] * iz);
      sP[h][m][lane][6 + hf] = pack_bf16(v[6] * iz, v[7] * iz);
      sP[h][m][lane][8 + hf] = pack_bf16(v[8] * iz, v[9] * iz);
    }
  }
  __syncthreads();
  if (w < 14) {
    float o[2][4][4] = {};
    for (int h = 0; h < NH; h++) {
      for (int n = 0; n < 4; n++) {
        int nt = w * 4 + n;
        uint4 v = g_VF[((seg * NH + h) * 56 + nt) * 32 + lane];
        uint32_t u = g_UF[((seg * NH + h) * 56 + nt) * 32 + lane];
        for (int m = 0; m < 2; m++) {
          const uint32_t* p = sP[h][m][lane];
          mma1688(o[m][n], p[0], p[1], u);
          mma16816(o[m][n], p[2], p[3], p[4], p[5], v.x, v.y);
          mma16816(o[m][n], p[6], p[7], p[8], p[9], v.z, v.w);
        }
      }
    }
    for (int m = 0; m < 2; m++) for (int n = 0; n < 4; n++) for (int i = 0; i < 4; i++) {
      int r = m * 16 + (i >> 1) * 8 + g, c = (w * 4 + n) * 8 + tq * 2 + (i & 1);
      int t = seg * 32 + r;
      float a = 0.f;
      for (int k = 0; k < DM; k++) a += g_oa[t * DM + k] * b2f(wo[k * DM + c]);
      float gt = sG[r];
      out[t * DM + c] = __float2bfloat16(gt * a + (1.f - gt) * o[m][n][i]);
    }
  }
}

__device__ __forceinline__ uint32_t smem_u32(const void* p) { return (uint32_t)__cvta_generic_to_shared(p); }
__device__ __forceinline__ uint32_t mapa(uint32_t a, uint32_t r) { uint32_t o; asm volatile("mapa.shared::cluster.u32 %0, %1, %2;" : "=r"(o) : "r"(a), "r"(r)); return o; }
__device__ __forceinline__ bool try_wait(uint32_t bar, uint32_t parity) {
  uint32_t ok; asm volatile("{\n.reg .pred p;\nmbarrier.try_wait.parity.shared::cta.b64 p, [%1], %2;\nselp.u32 %0, 1, 0, p;\n}" : "=r"(ok) : "r"(bar), "r"(parity) : "memory"); return ok; }
__device__ __forceinline__ void wait_bar(uint32_t bar, uint32_t parity) {
  int n = 0; while (!try_wait(bar, parity)) { if (++n > SPIN_LIMIT) { g_err = 1; break; } } }
__device__ __forceinline__ void arm_bar(uint32_t bar, uint32_t bytes) { asm volatile("mbarrier.arrive.expect_tx.shared::cta.b64 _, [%0], %1;" :: "r"(bar), "r"(bytes) : "memory"); }
__device__ __forceinline__ float4 ld_relaxed4(const void* p) { float4 v; asm volatile("ld.relaxed.gpu.global.v4.f32 {%0,%1,%2,%3}, [%4];" : "=f"(v.x), "=f"(v.y), "=f"(v.z), "=f"(v.w) : "l"(p) : "memory"); return v; }
__device__ __forceinline__ void red4(void* p, float a, float b, float c, float d) { asm volatile("red.relaxed.gpu.global.add.v4.f32 [%0], {%1,%2,%3,%4};" :: "l"(p), "f"(a), "f"(b), "f"(c), "f"(d) : "memory"); }
__device__ __forceinline__ void st_async2(uint32_t dst, float a, float b, uint32_t bar) { asm volatile("st.async.shared::cluster.mbarrier::complete_tx::bytes.v2.f32 [%0], {%1,%2}, [%3];" :: "r"(dst), "f"(a), "f"(b), "r"(bar) : "memory"); }
__device__ __forceinline__ void bulk_g2s(uint32_t dst, const void* src, uint32_t bytes, uint32_t bar) {
  asm volatile("cp.async.bulk.shared::cluster.global.mbarrier::complete_tx::bytes [%0], [%1], %2, [%3];" :: "r"(dst), "l"(src), "r"(bytes), "r"(bar) : "memory"); }
__device__ __forceinline__ unsigned clk() { unsigned c; asm volatile("mov.u32 %0, %%clock;" : "=r"(c) :: "memory"); return c; }
__device__ __forceinline__ float ex2(float x) { float y; asm("ex2.approx.ftz.f32 %0, %1;" : "=f"(y) : "f"(x)); return y; }

#define NST 4
struct RSmem {
  uint2 kf[NST][7][4][32];
  uint4 vf[NST][14][32];
  uint4 wS[8][7][32];
  uint4 memF[14][32];
  float2 sx[4][4][32];
  float2 sm[4][32];
  float2 sred[4][32];
  uint32_t uF[8][32];
  float2 uP[6][4][32];
  uint32_t smax[4];
  float xmax[NSEG];
  float sinv[2];
  unsigned long long bar_ld[NST], bar_sx, bar_sm;
  unsigned ts[64 * 16];
};
#define POLL_DELAY 300
#define STAMP(i)
__device__ __noinline__ void wait_slow(uint32_t bar, uint32_t parity) {
#pragma unroll 1
  for (int n = 0; n < SPIN_LIMIT; n++) if (try_wait(bar, parity)) return;
  g_err = 1;
}
__device__ __forceinline__ void wait_bar1(uint32_t bar, uint32_t parity) { if (!try_wait(bar, parity)) wait_slow(bar, parity); }
__device__ __forceinline__ uint4 ld_relaxed_u4(const void* p) { uint4 v; asm volatile("ld.relaxed.gpu.global.v4.u32 {%0,%1,%2,%3}, [%4];" : "=r"(v.x), "=r"(v.y), "=r"(v.z), "=r"(v.w) : "l"(p) : "memory"); return v; }
__device__ __forceinline__ void red_h8(void* p, uint32_t a, uint32_t b, uint32_t c, uint32_t d) { asm volatile("red.relaxed.gpu.global.add.noftz.v4.f16x2 [%0], {%1,%2,%3,%4};" :: "l"(p), "r"(a), "r"(b), "r"(c), "r"(d) : "memory"); }
__device__ __forceinline__ uint32_t pack_f16(float lo, float hi) { uint32_t r; asm("cvt.rn.f16x2.f32 %0, %1, %2;" : "=r"(r) : "f"(hi), "f"(lo)); return r; }
__device__ __forceinline__ uint32_t h2_to_bf2(uint32_t v) {
  float lo, hi; asm("{.reg .f16 l, h; mov.b32 {l, h}, %2; cvt.f32.f16 %0, l; cvt.f32.f16 %1, h;}" : "=f"(lo), "=f"(hi) : "r"(v)); return pack_bf16(lo, hi); }
__device__ __forceinline__ uint2 lds64(uint32_t a) { uint2 v; asm volatile("ld.shared.v2.u32 {%0,%1}, [%2];" : "=r"(v.x), "=r"(v.y) : "r"(a) : "memory"); return v; }
__device__ __forceinline__ float2 lds64f(uint32_t a) { float2 v; asm volatile("ld.shared.v2.f32 {%0,%1}, [%2];" : "=f"(v.x), "=f"(v.y) : "r"(a) : "memory"); return v; }
__device__ __forceinline__ uint4 lds128(uint32_t a) { uint4 v; asm volatile("ld.shared.v4.u32 {%0,%1,%2,%3}, [%4];" : "=r"(v.x), "=r"(v.y), "=r"(v.z), "=r"(v.w) : "r"(a) : "memory"); return v; }
__device__ __forceinline__ uint32_t lds32(uint32_t a) { uint32_t v; asm volatile("ld.shared.u32 %0, [%1];" : "=r"(v) : "r"(a) : "memory"); return v; }
__device__ __forceinline__ void sts64(uint32_t a, uint32_t x, uint32_t y) { asm volatile("st.shared.v2.u32 [%0], {%1,%2};" :: "r"(a), "r"(x), "r"(y) : "memory"); }
__device__ __forceinline__ void sts64f(uint32_t a, float x, float y) { asm volatile("st.shared.v2.f32 [%0], {%1,%2};" :: "r"(a), "f"(x), "f"(y) : "memory"); }
__device__ __forceinline__ void sts32(uint32_t a, uint32_t x) { asm volatile("st.shared.u32 [%0], %1;" :: "r"(a), "r"(x) : "memory"); }
__device__ __forceinline__ void mma_z(float* d, uint32_t a0, uint32_t a1, uint32_t a2, uint32_t a3, uint32_t b0, uint32_t b1) {
  asm volatile("mma.sync.aligned.m16n8k16.row.col.f32.bf16.bf16.f32 {%0,%1,%2,%3}, {%4,%5,%6,%7}, {%8,%9}, {%10,%10,%10,%10};"
    : "=f"(d[0]), "=f"(d[1]), "=f"(d[2]), "=f"(d[3]) : "r"(a0), "r"(a1), "r"(a2), "r"(a3), "r"(b0), "r"(b1), "f"(0.f));
}
__device__ __forceinline__ void mma8_z(float* d, uint32_t a0, uint32_t a1, uint32_t b0) {
  asm volatile("mma.sync.aligned.m16n8k8.row.col.f32.bf16.bf16.f32 {%0,%1,%2,%3}, {%4,%5}, {%6}, {%7,%7,%7,%7};"
    : "=f"(d[0]), "=f"(d[1]), "=f"(d[2]), "=f"(d[3]) : "r"(a0), "r"(a1), "r"(b0), "f"(0.f));
}
#define OFF(f) ((uint32_t)offsetof(RSmem, f))
#define BAR_SYNC(id, n) asm volatile("bar.sync %0, %1;" :: "n"(id), "n"(n) : "memory")
#define BAR_ARRIVE(id, n) asm volatile("bar.arrive %0, %1;" :: "n"(id), "n"(n) : "memory")

__device__ __forceinline__ void stage1(const uint4 (&W)[42], float (&acc)[6][4], uint32_t mf16, uint32_t mfx, uint32_t ws, uint4 w3) {
  uint4 p0 = lds128(mf16), p1 = lds128(mf16 + 512); uint2 xb = lds64(mfx);
#pragma unroll
  for (int e = 0; e < 7; e++) {
    uint4 n0, n1, nw; uint2 nx;
    const uint4 *w = &W[e * 6];
#define MM(A, WW, B0, B1, first) do { if (first) mma_z(A, WW.x, WW.y, WW.z, WW.w, B0, B1); else mma16816(A, WW.x, WW.y, WW.z, WW.w, B0, B1); } while (0)
    MM(acc[(4 * e + 0) % 3], w[0], p0.x, p0.y, e == 0);
    if (e < 6) nx = lds64(mfx + (e + 1) * 1024);
    MM(acc[3], w[3], xb.x, xb.y, e == 0);
    MM(acc[(4 * e + 1) % 3], w[1], p0.z, p0.w, e == 0);
    if (e < 6) n0 = lds128(mf16 + (e + 1) * 1024);
    MM(acc[4], w[4], xb.x, xb.y, e == 0);
    MM(acc[(4 * e + 2) % 3], w[2], p1.x, p1.y, e == 0);
    MM(acc[5], w[5], xb.x, xb.y, e == 0);
    MM(acc[(4 * e + 3) % 3], w3, p1.z, p1.w, false);
    if (e < 6) { n1 = lds128(mf16 + (e + 1) * 1024 + 512); nw = lds128(ws + (e + 1) * 512); p0 = n0; p1 = n1; xb = nx; w3 = nw; }
  }
}
__device__ __noinline__ void poll_slow(const uint4* p, uint4& v0, uint4& v1) {
#pragma unroll 1
  for (int n = 0; n < SPIN_LIMIT; n++) {
    v0 = ld_relaxed_u4(p); v1 = ld_relaxed_u4(p + 64);
    if (__all_sync(0xffffffffu, __byte_perm(v0.w, v1.w, 0x7632) == 0x4C004C00u)) return;
  }
  g_err = 2;
}
__device__ __forceinline__ void poll_mem(const uint4* p, uint32_t a0, uint32_t a1, uint32_t a2, uint32_t as) {
  uint4 v0 = ld_relaxed_u4(p), v1 = ld_relaxed_u4(p + 64);
  if (!__all_sync(0xffffffffu, __byte_perm(v0.w, v1.w, 0x7632) == 0x4C004C00u)) {
#pragma unroll 1
    for (int n = 0; n < SPIN_LIMIT; n++) {
      v0 = ld_relaxed_u4(p); v1 = ld_relaxed_u4(p + 64);
      if (__all_sync(0xffffffffu, __byte_perm(v0.w, v1.w, 0x7632) == 0x4C004C00u)) break;
    }
  }
  sts64(a0, h2_to_bf2(v0.x), h2_to_bf2(v0.y));
  sts64(a1, h2_to_bf2(v0.z), h2_to_bf2(v1.x));
  sts64(a2, h2_to_bf2(v1.y), h2_to_bf2(v1.z));
  sts32(as, h2_to_bf2(__byte_perm(v0.w, v1.w, 0x5410)));
}
__device__ __forceinline__ uint32_t ks_addr(uint32_t mf16, int ks) { return mf16 + (ks >> 1) * 512 + (ks & 1) * 8; }
__device__ __forceinline__ uint4* acc_ptr(int step, int vec, int lane) { return g_ACC16 + (((step >> 1) * 16 + vec) * 2 + (step & 1)) * 32 + lane; }

__global__ void __cluster_dims__(4, 1, 1) __launch_bounds__(384, 1) r_kernel(const bf16* mem0, int poll_delay) {
  extern __shared__ __align__(128) unsigned char smem_raw[];
  RSmem& sm = *reinterpret_cast<RSmem*>(smem_raw);
  const int h = blockIdx.x >> 2, j = blockIdx.x & 3;
  const int w = threadIdx.x >> 5, lane = threadIdx.x & 31, q = w & 3, role = w >> 2;
  const uint32_t sb = smem_u32(smem_raw);
  const uint32_t bar_ld = sb + OFF(bar_ld), bar_sx = sb + OFF(bar_sx), bar_sm = sb + OFF(bar_sm);
  if (threadIdx.x == 0) {
    for (int i = 0; i < NST; i++) asm volatile("mbarrier.init.shared::cta.b64 [%0], 1;" :: "r"(bar_ld + 8 * i));
    asm volatile("mbarrier.init.shared::cta.b64 [%0], 1;" :: "r"(bar_sx));
    asm volatile("mbarrier.init.shared::cta.b64 [%0], 1;" :: "r"(bar_sm));
    asm volatile("fence.mbarrier_init.release.cluster;" ::: "memory");
    arm_bar(bar_sx, 4096); arm_bar(bar_sm, 1024);
    for (int s = 0; s < NST - 1; s++) {
      arm_bar(bar_ld + 8 * s, 14336);
      bulk_g2s(smem_u32(sm.kf[s]), g_KF + ((s * NH + h) * 28 + 7 * j) * 128, 7168, bar_ld + 8 * s);
      bulk_g2s(smem_u32(sm.vf[s]), g_VF + ((s * NH + h) * 56 + 14 * j) * 32, 7168, bar_ld + 8 * s);
    }
    sm.sinv[0] = 1.f;
  }
  for (int i = threadIdx.x; i < 28 * 32; i += 384) {
    int ks = i >> 5, l = i & 31;
    const uint32_t* r = (const uint32_t*)(mem0 + (l >> 2) * DM + ks * 16 + (l & 3) * 2);
    ((uint2*)&sm.memF[ks >> 1][l])[ks & 1] = make_uint2(r[0], r[4]);
  }
  if (threadIdx.x < NSEG) sm.xmax[threadIdx.x] = g_xmax[threadIdx.x];
  if (role < 2) {
    const uint4* wf = g_WF + ((role * NH + h) * 28 + 7 * j + q) * 28 * 32 + lane;
#pragma unroll
    for (int e = 0; e < 7; e++) sm.wS[w][e][lane] = wf[(4 * e + 3) * 32];
  }
  asm volatile("barrier.cluster.arrive.release.aligned;\nbarrier.cluster.wait.acquire.aligned;" ::: "memory");

  const uint32_t l8 = sb + lane * 8, l16 = sb + lane * 16;
  const uint32_t mf16 = l16 + OFF(memF);
  const float LOG2E = 1.4426950408889634f;

  if (role < 2) {
    asm volatile("setmaxnreg.inc.sync.aligned.u32 216;");
    uint4 W[42];
    {
      const uint4* wf = g_WF + ((role * NH + h) * 28 + 7 * j) * 28 * 32 + lane;
#pragma unroll
      for (int e = 0; e < 7; e++) {
#pragma unroll
        for (int i = 0; i < 3; i++) W[e * 6 + i] = wf[(q * 28 + 4 * e + i) * 32];
#pragma unroll
        for (int x = 0; x < 3; x++) W[e * 6 + 3 + x] = wf[((4 + x) * 28 + 4 * e + q) * 32];
      }
    }
    const uint32_t mfx = mf16 + (q >> 1) * 512 + (q & 1) * 8;
    const uint32_t ws = l16 + OFF(wS) + w * 7 * 512;
    if (role == 0) {
      const uint32_t dst_sm = mapa(l8 + OFF(sm) + j * 256, q), dst_bar = mapa(bar_sm, q);
      const uint32_t am = ks_addr(mf16, 7 * j + q), ae0 = ks_addr(mf16, 7 * j + 4), ae1 = ks_addr(mf16, 7 * j + 5);
      uint2* kmf = g_KMF + ((h * 4 + j) * 16 + q * 4) * 32 + lane;
#pragma unroll 1
      for (int s = 0; s < NSEG; s++) {
        uint4 w3 = lds128(ws);
        BAR_SYNC(0, 384);
        STAMP(2);
        float acc[6][4];
        stage1(W, acc, mf16, mfx, ws, w3);
        BAR_ARRIVE(1, 256);
        uint2 a1 = lds64(ae0), a2 = lds64(ae1), a3 = lds64(ae0 + 512), a0 = lds64(am);
        STAMP(3);
        uint32_t kb[4][2];
#pragma unroll
        for (int x = 0; x < 3; x++) { kb[1 + x][0] = movm(pack_bf16(acc[3 + x][0], acc[3 + x][1])); kb[1 + x][1] = movm(pack_bf16(acc[3 + x][2], acc[3 + x][3])); }
        float dl[4], dh[4], el[4], eh[4];
        mma8_z(dl, a1.x, a1.y, kb[1][0]); mma8_z(dh, a1.x, a1.y, kb[1][1]);
        mma8_z(el, a2.x, a2.y, kb[2][0]); mma8_z(eh, a2.x, a2.y, kb[2][1]);
        kb[0][0] = movm(pack_bf16((acc[1][0] + acc[2][0]) + acc[0][0], (acc[1][1] + acc[2][1]) + acc[0][1]));
        kb[0][1] = movm(pack_bf16((acc[1][2] + acc[2][2]) + acc[0][2], (acc[1][3] + acc[2][3]) + acc[0][3]));
        mma1688(dl, a3.x, a3.y, kb[3][0]); mma1688(dh, a3.x, a3.y, kb[3][1]);
        mma1688(el, a0.x, a0.y, kb[0][0]); mma1688(eh, a0.x, a0.y, kb[0][1]);
        sts64f(l8 + OFF(sred) + q * 256, (dl[0] + dh[2]) + (el[0] + eh[2]), (dl[1] + dh[3]) + (el[1] + eh[3]));
        BAR_SYNC(2, 128);
        {
          float2 t0 = lds64f(l8 + OFF(sred)), t1 = lds64f(l8 + OFF(sred) + 256), t2 = lds64f(l8 + OFF(sred) + 512), t3 = lds64f(l8 + OFF(sred) + 768);
          st_async2(dst_sm, (t0.x + t1.x) + (t2.x + t3.x), (t0.y + t1.y) + (t2.y + t3.y), dst_bar);
        }
        STAMP(4);
        const __nv_bfloat162 iv = __float2bfloat162_rn(__uint_as_float(lds32(sb + OFF(sinv) + (s & 1) * 4)));
        auto us = [&](uint32_t v) { __nv_bfloat162 t = __hmul2(*reinterpret_cast<__nv_bfloat162*>(&v), iv); return *reinterpret_cast<uint32_t*>(&t); };
        BAR_SYNC(4, 384);
#pragma unroll
        for (int a = 0; a < 4; a++) kmf[a * 32] = make_uint2(us(kb[a][0]), us(kb[a][1]));
        kmf += NH * 4 * 16 * 32;
      }
    } else {
      const int pj = q >> 1, ph = q & 1;
      const uint32_t pa0 = ks_addr(mf16, pj * 7 + ph * 4), pa1 = ks_addr(mf16, pj * 7 + ph * 4 + 1), pas = ks_addr(mf16, pj * 7 + 3) + ph * 4;
#pragma unroll 1
      for (int s = 0; s < NSEG; s++) {
        if (s > 0) poll_mem(acc_ptr(s, q * 2, lane), pa0, pa1, pa0 + 512, pas);
        BAR_SYNC(0, 384);
        {
          uint4 a = lds128(mf16 + q * 512), b = lds128(mf16 + q * 512 + 2048), c = lds128(mf16 + q * 512 + 4096), d = lds128(mf16 + (q & 1) * 512 + 6144);
          const uint32_t M = 0x7fff7fffu;
          uint32_t m = __vmaxu2(__vmaxu2(__vmaxu2(a.x & M, a.y & M), __vmaxu2(a.z & M, a.w & M)), __vmaxu2(__vmaxu2(b.x & M, b.y & M), __vmaxu2(b.z & M, b.w & M)));
          m = __vmaxu2(m, __vmaxu2(__vmaxu2(__vmaxu2(c.x & M, c.y & M), __vmaxu2(c.z & M, c.w & M)), __vmaxu2(__vmaxu2(d.x & M, d.y & M), __vmaxu2(d.z & M, d.w & M))));
          m = max(m & 0xffffu, m >> 16);
          m = __reduce_max_sync(0xffffffffu, m);
          if (lane == 0) sts32(sb + OFF(smax) + q * 4, m);
        }
        uint4 w3 = lds128(ws);
        BAR_SYNC(1, 256);
        STAMP(10);
        float acc[6][4];
        stage1(W, acc, mf16, mfx, ws, w3);
#pragma unroll
        for (int x = 0; x < 3; x++) { sts64f(l8 + OFF(uP) + (2 * x) * 1024 + q * 256, acc[3 + x][0], acc[3 + x][1]); sts64f(l8 + OFF(uP) + (2 * x + 1) * 1024 + q * 256, acc[3 + x][2], acc[3 + x][3]); }
        sts32(sb + OFF(uF) + (2 * q) * 128 + lane * 4, pack_bf16((acc[1][0] + acc[2][0]) + acc[0][0], (acc[1][1] + acc[2][1]) + acc[0][1]));
        sts32(sb + OFF(uF) + (2 * q + 1) * 128 + lane * 4, pack_bf16((acc[1][2] + acc[2][2]) + acc[0][2], (acc[1][3] + acc[2][3]) + acc[0][3]));
        BAR_ARRIVE(3, 256);
        STAMP(11);
        if (threadIdx.x == 128 && s + NST - 1 < NSEG) {
          int s2 = s + NST - 1, st2 = s2 & (NST - 1);
          arm_bar(bar_ld + 8 * st2, 14336);
          bulk_g2s(smem_u32(sm.kf[st2]), g_KF + ((s2 * NH + h) * 28 + 7 * j) * 128, 7168, bar_ld + 8 * st2);
          bulk_g2s(smem_u32(sm.vf[st2]), g_VF + ((s2 * NH + h) * 56 + 14 * j) * 32, 7168, bar_ld + 8 * st2);
        }
        __syncwarp();
        BAR_SYNC(4, 384);
        unsigned tred = clk();
        if (threadIdx.x == 160) { arm_bar(bar_sx, 4096); arm_bar(bar_sm, 1024); }
        __syncwarp();
        while (clk() - tred < (unsigned)poll_delay) {}
      }
    }
  } else {
    asm volatile("setmaxnreg.dec.sync.aligned.u32 72;");
    const int pj = 2 + (q >> 1), ph = q & 1;
    const uint32_t pa0 = ks_addr(mf16, pj * 7 + ph * 4), pa1 = ks_addr(mf16, pj * 7 + ph * 4 + 1), pas = ks_addr(mf16, pj * 7 + 3) + ph * 4;
    const uint32_t dsx = l8 + OFF(sx) + j * 1024 + q * 256;
    const uint32_t ms0 = ks_addr(mf16, 7 * j), ms1 = ks_addr(mf16, 7 * j + 1);
    const int nt0 = q < 2 ? q * 3 : 8 + (q - 2) * 3, nts = 6 + (q >> 1);
    const float bmax = g_bmax;
    float inv = 1.f;
    uint32_t sc_bf = 0x3f803f80u;
    uint32_t* uf = g_UF + (h * 56 + 14 * j) * 32 + lane;
#pragma unroll 1
    for (int s = 0; s < NSEG; s++) {
      const int st = s & (NST - 1);
      wait_bar1(bar_ld + 8 * st, (s / NST) & 1);
      uint2 kb[7];
#pragma unroll
      for (int i = 0; i < 7; i++) kb[i] = lds64(l8 + OFF(kf) + st * 7168 + i * 1024 + q * 256);
      STAMP(0);
      if (s > 0) poll_mem(acc_ptr(s, 8 + q * 2, lane), pa0, pa1, pa0 + 512, pas);
      STAMP(1);
      BAR_SYNC(0, 384);
      {
        float dl[2][4], dh[2][4];
#pragma unroll
        for (int i = 0; i < 7; i++) {
          uint2 a = lds64(((i & 1) ? ms1 : ms0) + (i >> 1) * 512);
          if (i < 2) { mma8_z(dl[i], a.x, a.y, kb[i].x); mma8_z(dh[i], a.x, a.y, kb[i].y); }
          else { mma1688(dl[i & 1], a.x, a.y, kb[i].x); mma1688(dh[i & 1], a.x, a.y, kb[i].y); }
        }
        float s0 = (dl[0][0] + dh[0][2]) + (dl[1][0] + dh[1][2]), s1 = (dl[0][1] + dh[0][3]) + (dl[1][1] + dh[1][3]);
#pragma unroll
        for (int r = 0; r < 4; r++) st_async2(mapa(dsx, r), s0, s1, mapa(bar_sx, r));
      }
      STAMP(9);
      float o[4][4], oz[4];
      float mx;
      const float c1 = LOG2E * inv;
      {
        const uint32_t vb = l16 + OFF(vf) + st * 7168;
        uint4 v0 = lds128(vb + nt0 * 512), v1 = lds128(vb + nt0 * 512 + 512), v2 = lds128(vb + nt0 * 512 + 1024), v3 = lds128(vb + nts * 512);
        wait_bar1(bar_sx, s & 1);
        float sx[8];
#pragma unroll
        for (int kg = 0; kg < 4; kg++) {
          float2 p0 = lds64f(l8 + OFF(sx) + kg * 256), p1 = lds64f(l8 + OFF(sx) + 1024 + kg * 256), p2 = lds64f(l8 + OFF(sx) + 2048 + kg * 256), p3 = lds64f(l8 + OFF(sx) + 3072 + kg * 256);
          sx[2 * kg] = ((p0.x + p1.x) + (p2.x + p3.x)) * c1; sx[2 * kg + 1] = ((p0.y + p1.y) + (p2.y + p3.y)) * c1;
        }
        mx = fmaxf(fmaxf(fmaxf(sx[0], sx[1]), fmaxf(sx[2], sx[3])), fmaxf(fmaxf(sx[4], sx[5]), fmaxf(sx[6], sx[7])));
        mx = fmaxf(mx, __shfl_xor_sync(0xffffffffu, mx, 1)); mx = fmaxf(mx, __shfl_xor_sync(0xffffffffu, mx, 2));
#pragma unroll
        for (int i = 0; i < 8; i++) sx[i] = ex2(sx[i] - mx);
        uint32_t p0 = pack_bf16(sx[0], sx[1]), p1 = pack_bf16(sx[2], sx[3]), p2 = pack_bf16(sx[4], sx[5]), p3 = pack_bf16(sx[6], sx[7]);
        mma_z(o[0], p0, 0u, p1, 0u, v0.x, v0.y); mma_z(o[1], p0, 0u, p1, 0u, v1.x, v1.y); mma_z(o[2], p0, 0u, p1, 0u, v2.x, v2.y); mma_z(o[3], p0, 0u, p1, 0u, v3.x, v3.y);
        mma_z(oz, p0, 0u, p1, 0u, 0x3f803f80u, 0x3f803f80u);
        mma16816(o[0], p2, 0u, p3, 0u, v0.z, v0.w); mma16816(o[1], p2, 0u, p3, 0u, v1.z, v1.w); mma16816(o[2], p2, 0u, p3, 0u, v2.z, v2.w); mma16816(o[3], p2, 0u, p3, 0u, v3.z, v3.w);
        mma16816(oz, p2, 0u, p3, 0u, 0x3f803f80u, 0x3f803f80u);
      }
      uint4* redp = acc_ptr(s + 1, j * 4 + q, lane);
      STAMP(5);
      BAR_SYNC(3, 256);
      uint32_t u[4];
      u[3] = lds32(sb + OFF(uF) + nts * 128 + lane * 4);
      if (q < 2) {
#pragma unroll
        for (int n = 0; n < 3; n++) u[n] = lds32(sb + OFF(uF) + (nt0 + n) * 128 + lane * 4);
      } else {
#pragma unroll
        for (int n = 0; n < 3; n++) {
          const uint32_t pp = l8 + OFF(uP) + (nt0 - 8 + n) * 1024;
          float2 t0 = lds64f(pp), t1 = lds64f(pp + 256), t2 = lds64f(pp + 512), t3 = lds64f(pp + 768);
          u[n] = pack_bf16((t0.x + t1.x) + (t2.x + t3.x), (t0.y + t1.y) + (t2.y + t3.y));
        }
      }
      float nsc, ninv;
      {
        uint4 m4 = lds128(sb + OFF(smax));
        uint32_t mb = max(max(m4.x, m4.y), max(m4.z, m4.w));
        float mh = fmaxf(__uint_as_float(mb << 16) * inv, __uint_as_float(lds32(sb + OFF(xmax) + s * 4)));
        float bound = mh * bmax;
        int e = (int)(__float_as_uint(bound) >> 23) - 127 + 10;
        int se = min(max(15 - e, -100), 100);
        nsc = __uint_as_float((uint32_t)(127 + se) << 23); ninv = __uint_as_float((uint32_t)(127 - se) << 23);
      }
      STAMP(6);
      wait_bar1(bar_sm, s & 1);
      STAMP(7);
      {
        float2 t0 = lds64f(l8 + OFF(sm)), t1 = lds64f(l8 + OFF(sm) + 256), t2 = lds64f(l8 + OFF(sm) + 512), t3 = lds64f(l8 + OFF(sm) + 768);
        float s0 = ((t0.x + t1.x) + (t2.x + t3.x)) * inv * c1, s1 = ((t0.y + t1.y) + (t2.y + t3.y)) * inv * c1;
        float m = fmaxf(fmaxf(s0, s1), mx);
        m = fmaxf(m, __shfl_xor_sync(0xffffffffu, m, 1)); m = fmaxf(m, __shfl_xor_sync(0xffffffffu, m, 2));
        float e0 = ex2(s0 - m), e1 = ex2(s1 - m), al = ex2(mx - m);
        uint32_t pm = pack_bf16(e0 * inv, e1 * inv);
        oz[0] *= al; mma1688(oz, pm, 0u, sc_bf);
#pragma unroll
        for (int n = 0; n < 4; n++) { o[n][0] *= al; o[n][1] *= al; mma1688(o[n], pm, 0u, u[n]); }
        float iz; asm("rcp.approx.ftz.f32 %0, %1;" : "=f"(iz) : "f"(oz[0]));
        iz *= nsc;
        red_h8(redp, pack_f16(o[0][0] * iz, o[0][1] * iz), pack_f16(o[1][0] * iz, o[1][1] * iz), pack_f16(o[2][0] * iz, o[2][1] * iz),
               pack_f16(((q & 1) ? o[3][1] : o[3][0]) * iz, 1.f));
      }
      unsigned tred = clk();
      BAR_ARRIVE(4, 384);
      STAMP(8);
      {
        const __nv_bfloat162 iv = __float2bfloat162_rn(inv);
        auto us = [&](uint32_t v) { __nv_bfloat162 t = __hmul2(*reinterpret_cast<__nv_bfloat162*>(&v), iv); return *reinterpret_cast<uint32_t*>(&t); };
#pragma unroll
        for (int n = 0; n < 3; n++) uf[(nt0 + n) * 32] = us(u[n]);
        if ((q & 1) == 0) uf[nts * 32] = us(u[3]);
        uf += NH * 56 * 32;
      }
      if (threadIdx.x == 256) sts32(sb + OFF(sinv) + ((s + 1) & 1) * 4, __float_as_uint(ninv));
      inv = ninv; { uint32_t t = __float_as_uint(nsc) >> 16; sc_bf = t | (t << 16); }
      while (clk() - tred < (unsigned)(poll_delay - 80)) {}
    }
  }
  asm volatile("barrier.cluster.arrive.release.aligned;\nbarrier.cluster.wait.acquire.aligned;" ::: "memory");
}

__global__ void n_stats(const bf16* x) {
  if (blockIdx.x < 64) {
    float m = 0.f;
    for (int i = threadIdx.x; i < 32 * DM; i += 256) m = fmaxf(m, fabsf(b2f(x[blockIdx.x * 32 * DM + i])));
    atomicMax((unsigned*)&g_xmax[blockIdx.x], __float_as_uint(m));
  } else {
    int r = (blockIdx.x - 64) * 256 + threadIdx.x;
    if (r < NH * DM) { float a = 0.f; for (int k = 0; k < DM; k++) { float v = wf_elem(1, r / DM, r % DM, k); a += v * v; } atomicMax((unsigned*)&g_bmax, __float_as_uint(sqrtf(a))); }
  }
}

int g_poll_delay = POLL_DELAY;
extern "C" void kernel_launch(void* const* d_in, const int* in_sizes, int n_in, void* d_out, int out_size) {
  const bf16* x = (const bf16*)d_in[0];
  const bf16* wqkv = (const bf16*)d_in[1];
  const bf16* wphi = (const bf16*)d_in[2];
  const bf16* wo_a = (const bf16*)d_in[3];
  const bf16* mem0 = (const bf16*)d_in[5];
  const bf16* Wq = (const bf16*)d_in[6];
  const bf16* Wk = (const bf16*)d_in[7];
  const bf16* Wv = (const bf16*)d_in[8];
  const bf16* Wo = (const bf16*)d_in[9];
  const bf16* gate_w = (const bf16*)d_in[11];
  bf16* out = (bf16*)d_out;
  cudaFuncSetAttribute(r_kernel, cudaFuncAttributeMaxDynamicSharedMemorySize, (int)sizeof(RSmem));
  n_zero<<<(NSEG * 40 * 32 + 255) / 256, 256>>>();
  n_prep<<<(2 * NH * 28 * 28 * 32 + 255) / 256, 256>>>(Wq, Wk, Wv, Wo);
  n_stats<<<64 + 28, 256>>>(x);
  n_xgemm<<<2 * NH * 28 * NSEG * 32 / 256, 256>>>(x);
  r_kernel<<<64, 384, sizeof(RSmem)>>>(mem0, g_poll_delay);
  n_qkv<<<(S_LEN * 1344 + 255) / 256, 256>>>(x, wqkv);
  n_phi<<<(S_LEN * 2 * NH + 255) / 256, 256>>>(wphi);
  n_kv<<<(32 * NH * 56 * 29 + 255) / 256, 256>>>();
  n_oa<<<(S_LEN * DM + 255) / 256, 256>>>();
  n_x3<<<NSEG, 512>>>(x, wo_a, gate_w, out);
}
```

```cpp
#include <cuda_runtime.h>
#include <cuda_bf16.h>
#include <stdint.h>
#include <stddef.h>

typedef __nv_bfloat16 bf16;
#define S_LEN 2048
#define DM 448
#define NH 16
#define NSEG 64
#define SPIN_LIMIT (1 << 22)

__device__ uint4 g_WF[2 * NH * 28 * 28 * 32];
__device__ uint4 g_KF[NSEG * NH * 4 * 4 * 4 * 32];
__device__ uint4 g_VF[NSEG * NH * 56 * 32];
__device__ uint2 g_KMF[NSEG * NH * 4 * 28 * 32];
__device__ uint32_t g_UF[NSEG * NH * 56 * 32];
__device__ uint4 g_ACC16[(NSEG + 2) * 16 * 32];
__device__ float g_xmax[NSEG];
__device__ float g_bmax;
__device__ float g_qkv[S_LEN * 1344];
__device__ float g_phiq[S_LEN * NH * 56];
__device__ float g_phik[S_LEN * NH * 56];
__device__ float g_kv[NH * 56 * 29];
__device__ float g_oa[S_LEN * DM];
__device__ int g_err;
__device__ unsigned g_ts[64 * 64 * 16];

__device__ __forceinline__ uint32_t pack_bf16(float lo, float hi) {
  uint32_t r; asm("cvt.rn.bf16x2.f32 %0, %1, %2;" : "=r"(r) : "f"(hi), "f"(lo)); return r;
}
__device__ __forceinline__ float bf_lo(uint32_t v) { return __uint_as_float(v << 16); }
__device__ __forceinline__ float bf_hi(uint32_t v) { return __uint_as_float(v & 0xffff0000u); }
__device__ __forceinline__ float b2f(bf16 v) { return __bfloat162float(v); }

__global__ void n_prep(const bf16* Wq, const bf16* Wk, const bf16* Wv, const bf16* Wo) {
  int idx = blockIdx.x * blockDim.x + threadIdx.x;
  if (idx >= 2 * NH * 28 * 28 * 32) return;
  int lane = idx & 31, r = idx >> 5;
  int ks = r % 28; r /= 28; int tile = r % 28; r /= 28; int h = r % NH; int mat = r / NH;
  int g = lane >> 2, tq = lane & 3;
  float v[8];
  for (int i = 0; i < 8; i++) {
    int row = tile * 16 + g + ((i >> 1) & 1) * 8;
    int col = ks * 16 + tq * 2 + (i & 1) + (i >> 2) * 8;
    float acc = 0.f;
    if (mat == 0) { for (int e = 0; e < 256; e++) acc += b2f(Wq[(row * NH + h) * 256 + e]) * b2f(Wk[(col * NH + h) * 256 + e]); acc *= 0.0625f; }
    else { for (int e = 0; e < 256; e++) acc += b2f(Wo[(h * 256 + e) * DM + row]) * b2f(Wv[(col * NH + h) * 256 + e]); }
    v[i] = acc;
  }
  g_WF[idx] = make_uint4(pack_bf16(v[0], v[1]), pack_bf16(v[2], v[3]), pack_bf16(v[4], v[5]), pack_bf16(v[6], v[7]));
}
__device__ __forceinline__ float wf_elem(int mat, int h, int row, int col) {
  int tile = row >> 4, ks = col >> 4, rr = row & 15, cc = col & 15;
  int lane = (rr & 7) * 4 + ((cc & 7) >> 1);
  int reg = (rr >> 3) + (cc >> 3) * 2;
  uint32_t w = ((const uint32_t*)g_WF)[((((mat * NH + h) * 28 + tile) * 28 + ks) * 32 + lane) * 4 + reg];
  return (cc & 1) ? bf_hi(w) : bf_lo(w);
}
__device__ __forceinline__ void mma16816(float* d, uint32_t a0, uint32_t a1, uint32_t a2, uint32_t a3, uint32_t b0, uint32_t b1) {
  asm volatile("mma.sync.aligned.m16n8k16.row.col.f32.bf16.bf16.f32 {%0,%1,%2,%3}, {%4,%5,%6,%7}, {%8,%9}, {%0,%1,%2,%3};"
    : "+f"(d[0]), "+f"(d[1]), "+f"(d[2]), "+f"(d[3]) : "r"(a0), "r"(a1), "r"(a2), "r"(a3), "r"(b0), "r"(b1));
}
__device__ __forceinline__ void mma1688(float* d, uint32_t a0, uint32_t a1, uint32_t b0) {
  asm volatile("mma.sync.aligned.m16n8k8.row.col.f32.bf16.bf16.f32 {%0,%1,%2,%3}, {%4,%5}, {%6}, {%0,%1,%2,%3};"
    : "+f"(d[0]), "+f"(d[1]), "+f"(d[2]), "+f"(d[3]) : "r"(a0), "r"(a1), "r"(b0));
}
__device__ __forceinline__ uint32_t movm(uint32_t a) { uint32_t d; asm volatile("movmatrix.sync.aligned.m8n8.trans.b16 %0, %1;" : "=r"(d) : "r"(a)); return d; }

__global__ void n_xgemm(const bf16* x) {
  int wid = (blockIdx.x * blockDim.x + threadIdx.x) >> 5, lane = threadIdx.x & 31;
  int seg = wid % NSEG; int r = wid / NSEG;
  int tile = r % 28; r /= 28; int h = r % NH; int mat = r / NH;
  if (mat >= 2) return;
  int g = lane >> 2, tq = lane & 3;
  float d[4][4] = {};
  const uint4* wf = g_WF + (((mat * NH + h) * 28 + tile) * 28) * 32 + lane;
  for (int ks = 0; ks < 28; ks++) {
    uint4 a = wf[ks * 32];
    for (int kg = 0; kg < 4; kg++) {
      const uint32_t* xr = (const uint32_t*)(x + (seg * 32 + kg * 8 + g) * DM + ks * 16 + tq * 2);
      mma16816(d[kg], a.x, a.y, a.z, a.w, xr[0], xr[4]);
    }
  }
  if (mat == 0) {
    for (int kg = 0; kg < 4; kg++) {
      uint32_t b0 = movm(pack_bf16(d[kg][0], d[kg][1])), b1 = movm(pack_bf16(d[kg][2], d[kg][3]));
      int jj = tile / 7, i = tile % 7;
      uint32_t* dst = (uint32_t*)&g_KF[((((seg * NH + h) * 4 + jj) * 4 + (i >> 1)) * 4 + kg) * 32 + lane];
      if (i == 6) { dst[0] = b0; dst[1] = b1; } else { dst[i & 1] = b0; dst[2 + (i & 1)] = b1; }
    }
  } else {
    g_VF[((seg * NH + h) * 56 + tile * 2) * 32 + lane] = make_uint4(pack_bf16(d[0][0], d[0][1]), pack_bf16(d[1][0], d[1][1]), pack_bf16(d[2][0], d[2][1]), pack_bf16(d[3][0], d[3][1]));
    g_VF[((seg * NH + h) * 56 + tile * 2 + 1) * 32 + lane] = make_uint4(pack_bf16(d[0][2], d[0][3]), pack_bf16(d[1][2], d[1][3]), pack_bf16(d[2][2], d[2][3]), pack_bf16(d[3][2], d[3][3]));
  }
}
__global__ void n_zero() {
  int i = blockIdx.x * blockDim.x + threadIdx.x;
  if (i < (NSEG + 2) * 16 * 32) g_ACC16[i] = make_uint4(0, 0, 0, 0);
  if (i < NSEG) g_xmax[i] = 0.f;
  if (i == 0) g_bmax = 0.f;
  if (i < NH * 56 * 29) g_kv[i] = 0.f;
}
__global__ void n_qkv(const bf16* x, const bf16* w) {
  int i = blockIdx.x * blockDim.x + threadIdx.x;
  if (i >= S_LEN * 1344) return;
  int n = i % 1344, t = i / 1344;
  float acc = 0.f;
  for (int k = 0; k < DM; k++) acc += b2f(x[t * DM + k]) * b2f(w[k * 1344 + n]);
  g_qkv[i] = acc;
}
__global__ void n_phi(const bf16* wphi) {
  int i = blockIdx.x * blockDim.x + threadIdx.x;
  if (i >= S_LEN * 2 * NH) return;
  int h = i % NH, which = (i / NH) % 2, t = i / (2 * NH);
  float p[28]; float mx = -1e30f, mn = 1e30f;
  for (int f = 0; f < 28; f++) {
    float acc = 0.f;
    for (int d = 0; d < 28; d++) acc += g_qkv[t * 1344 + which * 448 + h * 28 + d] * b2f(wphi[(h * 28 + d) * 28 + f]);
    p[f] = acc; mx = fmaxf(mx, acc); mn = fminf(mn, acc);
  }
  float s1 = 0.f, s2 = 0.f;
  for (int f = 0; f < 28; f++) { s1 += __expf(p[f] - mx); s2 += __expf(mn - p[f]); }
  float* o = (which ? g_phik : g_phiq) + (t * NH + h) * 56;
  for (int f = 0; f < 28; f++) { o[f] = __expf(p[f] - mx) / s1; o[28 + f] = __expf(mn - p[f]) / s2; }
}
__global__ void n_kv() {
  int i = blockIdx.x * blockDim.x + threadIdx.x;
  if (i >= 32 * NH * 56 * 29) return;
  int d = i % 29, f = (i / 29) % 56, h = (i / (29 * 56)) % NH, ch = i / (29 * 56 * NH);
  float acc = 0.f;
  for (int t = ch * 64; t < ch * 64 + 64; t++) acc += g_phik[(t * NH + h) * 56 + f] * (d < 28 ? g_qkv[t * 1344 + 896 + h * 28 + d] : 1.f);
  atomicAdd(&g_kv[(h * 56 + f) * 29 + d], acc);
}
__global__ void n_oa() {
  int i = blockIdx.x * blockDim.x + threadIdx.x;
  if (i >= S_LEN * DM) return;
  int c = i % DM, t = i / DM, h = c / 28, d = c % 28;
  float num = 0.f, den = 0.f;
  for (int f = 0; f < 56; f++) { float p = g_phiq[(t * NH + h) * 56 + f]; num += p * g_kv[(h * 56 + f) * 29 + d]; den += p * g_kv[(h * 56 + f) * 29 + 28]; }
  g_oa[i] = num / (den + 1e-6f);
}

__global__ void __launch_bounds__(512) n_x3(const bf16* x, const bf16* wo, const bf16* gate_w, bf16* out) {
  __shared__ uint32_t sP[NH][2][32][10];
  __shared__ float sG[32];
  int seg = blockIdx.x, w = threadIdx.x >> 5, lane = threadIdx.x & 31, g = lane >> 2, tq = lane & 3;
  for (int r = w; r < 32; r += 16) {
    float acc = 0.f;
    for (int k = lane; k < DM; k += 32) acc += b2f(x[(seg * 32 + r) * DM + k]) * b2f(gate_w[k]);
    for (int o = 16; o; o >>= 1) acc += __shfl_xor_sync(0xffffffffu, acc, o);
    if (lane == 0) sG[r] = 1.f / (1.f + __expf(-acc));
  }
  {
    int h = w;
    float s[2][5][4] = {};
    for (int ct = 0; ct < 28; ct++) {
      uint32_t a[2][4];
      for (int m = 0; m < 2; m++) {
        const uint32_t* r0 = (const uint32_t*)(x + (seg * 32 + m * 16 + g) * DM + ct * 16 + tq * 2);
        const uint32_t* r1 = (const uint32_t*)(x + (seg * 32 + m * 16 + g + 8) * DM + ct * 16 + tq * 2);
        a[m][0] = r0[0]; a[m][1] = r1[0]; a[m][2] = r0[4]; a[m][3] = r1[4];
      }
      int j = ct / 7, i = ct % 7;
      for (int kg = 0; kg < 4; kg++) {
        const uint32_t* src = (const uint32_t*)&g_KF[((((seg * NH + h) * 4 + j) * 4 + (i >> 1)) * 4 + kg) * 32 + lane];
        uint2 b = i == 6 ? make_uint2(src[0], src[1]) : make_uint2(src[i & 1], src[2 + (i & 1)]);
        for (int m = 0; m < 2; m++) mma16816(s[m][1 + kg], a[m][0], a[m][1], a[m][2], a[m][3], b.x, b.y);
      }
      for (int q = 0; q < 4; q++) {
        uint2 b = g_KMF[((((seg * NH + h) * 4 + j) * 4 + q) * 7 + i) * 32 + lane];
        for (int m = 0; m < 2; m++) mma16816(s[m][0], a[m][0], a[m][1], a[m][2], a[m][3], b.x, b.y);
      }
    }
    for (int m = 0; m < 2; m++) for (int hf = 0; hf < 2; hf++) {
      int t = m * 16 + hf * 8 + g;
      float v[10]; float mx = -1e30f;
      for (int n = 0; n < 5; n++) for (int e = 0; e < 2; e++) {
        float val = s[m][n][hf * 2 + e];
        if (n > 0 && (n - 1) * 8 + tq * 2 + e > t) val = -1e30f;
        v[n * 2 + e] = val; mx = fmaxf(mx, val);
      }
      mx = fmaxf(mx, __shfl_xor_sync(0xffffffffu, mx, 1)); mx = fmaxf(mx, __shfl_xor_sync(0xffffffffu, mx, 2));
      float z = 0.f;
      for (int i = 0; i < 10; i++) { v[i] = __expf(v[i] - mx); z += v[i]; }
      z += __shfl_xor_sync(0xffffffffu, z, 1); z += __shfl_xor_sync(0xffffffffu, z, 2);
      float iz = 1.f / z;
      sP[h][m][lane][hf] = pack_bf16(v[0] * iz, v[1] * iz);
      sP[h][m][lane][2 + hf] = pack_bf16(v[2] * iz, v[3] * iz);
      sP[h][m][lane][4 + hf] = pack_bf16(v[4] * iz, v[5] * iz);
      sP[h][m][lane][6 + hf] = pack_bf16(v[6] * iz, v[7] * iz);
      sP[h][m][lane][8 + hf] = pack_bf16(v[8] * iz, v[9] * iz);
    }
  }
  __syncthreads();
  if (w < 14) {
    float o[2][4][4] = {};
    for (int h = 0; h < NH; h++) {
      for (int n = 0; n < 4; n++) {
        int nt = w * 4 + n;
        uint4 v = g_VF[((seg * NH + h) * 56 + nt) * 32 + lane];
        uint32_t u = g_UF[((seg * NH + h) * 56 + nt) * 32 + lane];
        for (int m = 0; m < 2; m++) {
          const uint32_t* p = sP[h][m][lane];
          mma1688(o[m][n], p[0], p[1], u);
          mma16816(o[m][n], p[2], p[3], p[4], p[5], v.x, v.y);
          mma16816(o[m][n], p[6], p[7], p[8], p[9], v.z, v.w);
        }
      }
    }
    for (int m = 0; m < 2; m++) for (int n = 0; n < 4; n++) for (int i = 0; i < 4; i++) {
      int r = m * 16 + (i >> 1) * 8 + g, c = (w * 4 + n) * 8 + tq * 2 + (i & 1);
      int t = seg * 32 + r;
      float a = 0.f;
      for (int k = 0; k < DM; k++) a += g_oa[t * DM + k] * b2f(wo[k * DM + c]);
      float gt = sG[r];
      out[t * DM + c] = __float2bfloat16(gt * a + (1.f - gt) * o[m][n][i]);
    }
  }
}

__device__ __forceinline__ uint32_t smem_u32(const void* p) { return (uint32_t)__cvta_generic_to_shared(p); }
__device__ __forceinline__ uint32_t mapa(uint32_t a, uint32_t r) { uint32_t o; asm volatile("mapa.shared::cluster.u32 %0, %1, %2;" : "=r"(o) : "r"(a), "r"(r)); return o; }
__device__ __forceinline__ bool try_wait(uint32_t bar, uint32_t parity) {
  uint32_t ok; asm volatile("{\n.reg .pred p;\nmbarrier.try_wait.parity.shared::cta.b64 p, [%1], %2;\nselp.u32 %0, 1, 0, p;\n}" : "=r"(ok) : "r"(bar), "r"(parity) : "memory"); return ok; }
__device__ __forceinline__ void wait_bar(uint32_t bar, uint32_t parity) {
  int n = 0; while (!try_wait(bar, parity)) { if (++n > SPIN_LIMIT) { g_err = 1; break; } } }
__device__ __forceinline__ void arm_bar(uint32_t bar, uint32_t bytes) { asm volatile("mbarrier.arrive.expect_tx.shared::cta.b64 _, [%0], %1;" :: "r"(bar), "r"(bytes) : "memory"); }
__device__ __forceinline__ float4 ld_relaxed4(const void* p) { float4 v; asm volatile("ld.relaxed.gpu.global.v4.f32 {%0,%1,%2,%3}, [%4];" : "=f"(v.x), "=f"(v.y), "=f"(v.z), "=f"(v.w) : "l"(p) : "memory"); return v; }
__device__ __forceinline__ void red4(void* p, float a, float b, float c, float d) { asm volatile("red.relaxed.gpu.global.add.v4.f32 [%0], {%1,%2,%3,%4};" :: "l"(p), "f"(a), "f"(b), "f"(c), "f"(d) : "memory"); }
__device__ __forceinline__ void st_async2(uint32_t dst, float a, float b, uint32_t bar) { asm volatile("st.async.shared::cluster.mbarrier::complete_tx::bytes.v2.f32 [%0], {%1,%2}, [%3];" :: "r"(dst), "f"(a), "f"(b), "r"(bar) : "memory"); }
__device__ __forceinline__ void bulk_g2s(uint32_t dst, const void* src, uint32_t bytes, uint32_t bar) {
  asm volatile("cp.async.bulk.shared::cluster.global.mbarrier::complete_tx::bytes [%0], [%1], %2, [%3];" :: "r"(dst), "l"(src), "r"(bytes), "r"(bar) : "memory"); }
__device__ __forceinline__ unsigned clk() { unsigned c; asm volatile("mov.u32 %0, %%clock;" : "=r"(c) :: "memory"); return c; }
__device__ __forceinline__ float ex2(float x) { float y; asm("ex2.approx.ftz.f32 %0, %1;" : "=f"(y) : "f"(x)); return y; }

#define NST 4
struct RSmem {
  uint4 kf[NST][4][4][32];
  uint4 vf[NST][14][32];
  uint4 wS[8][7][32];
  uint4 memF[4][4][32];
  float2 sx[4][4][32];
  float2 sm[4][32];
  float2 sred[4][32];
  uint4 uQ[14][32];
  uint32_t smax[4];
  float xmax[NSEG];
  float sinv[2];
  unsigned long long bar_ld[NST], bar_sx, bar_sm;
  unsigned ts[64 * 16];
};
#define POLL_DELAY 300
#define STAMP(i)
__device__ __noinline__ void wait_slow(uint32_t bar, uint32_t parity) {
#pragma unroll 1
  for (int n = 0; n < SPIN_LIMIT; n++) if (try_wait(bar, parity)) return;
  g_err = 1;
}
__device__ __forceinline__ void wait_bar1(uint32_t bar, uint32_t parity) { if (!try_wait(bar, parity)) wait_slow(bar, parity); }
__device__ __forceinline__ uint4 ld_relaxed_u4(const void* p) { uint4 v; asm volatile("ld.relaxed.gpu.global.v4.u32 {%0,%1,%2,%3}, [%4];" : "=r"(v.x), "=r"(v.y), "=r"(v.z), "=r"(v.w) : "l"(p) : "memory"); return v; }
__device__ __forceinline__ void red_h8(void* p, uint32_t a, uint32_t b, uint32_t c, uint32_t d) { asm volatile("red.relaxed.gpu.global.add.noftz.v4.f16x2 [%0], {%1,%2,%3,%4};" :: "l"(p), "r"(a), "r"(b), "r"(c), "r"(d) : "memory"); }
__device__ __forceinline__ uint32_t pack_f16(float lo, float hi) { uint32_t r; asm("cvt.rn.f16x2.f32 %0, %1, %2;" : "=r"(r) : "f"(hi), "f"(lo)); return r; }
__device__ __forceinline__ uint32_t h2_to_bf2(uint32_t v) {
  float lo, hi; asm("{.reg .f16 l, h; mov.b32 {l, h}, %2; cvt.f32.f16 %0, l; cvt.f32.f16 %1, h;}" : "=f"(lo), "=f"(hi) : "r"(v)); return pack_bf16(lo, hi); }
__device__ __forceinline__ uint2 lds64(uint32_t a) { uint2 v; asm volatile("ld.shared.v2.u32 {%0,%1}, [%2];" : "=r"(v.x), "=r"(v.y) : "r"(a) : "memory"); return v; }
__device__ __forceinline__ float2 lds64f(uint32_t a) { float2 v; asm volatile("ld.shared.v2.f32 {%0,%1}, [%2];" : "=f"(v.x), "=f"(v.y) : "r"(a) : "memory"); return v; }
__device__ __forceinline__ uint4 lds128(uint32_t a) { uint4 v; asm volatile("ld.shared.v4.u32 {%0,%1,%2,%3}, [%4];" : "=r"(v.x), "=r"(v.y), "=r"(v.z), "=r"(v.w) : "r"(a) : "memory"); return v; }
__device__ __forceinline__ uint32_t lds32(uint32_t a) { uint32_t v; asm volatile("ld.shared.u32 %0, [%1];" : "=r"(v) : "r"(a) : "memory"); return v; }
__device__ __forceinline__ void sts64(uint32_t a, uint32_t x, uint32_t y) { asm volatile("st.shared.v2.u32 [%0], {%1,%2};" :: "r"(a), "r"(x), "r"(y) : "memory"); }
__device__ __forceinline__ void sts64f(uint32_t a, float x, float y) { asm volatile("st.shared.v2.f32 [%0], {%1,%2};" :: "r"(a), "f"(x), "f"(y) : "memory"); }
__device__ __forceinline__ void sts32(uint32_t a, uint32_t x) { asm volatile("st.shared.u32 [%0], %1;" :: "r"(a), "r"(x) : "memory"); }
__device__ __forceinline__ void mma_z(float* d, uint32_t a0, uint32_t a1, uint32_t a2, uint32_t a3, uint32_t b0, uint32_t b1) {
  asm volatile("mma.sync.aligned.m16n8k16.row.col.f32.bf16.bf16.f32 {%0,%1,%2,%3}, {%4,%5,%6,%7}, {%8,%9}, {%10,%10,%10,%10};"
    : "=f"(d[0]), "=f"(d[1]), "=f"(d[2]), "=f"(d[3]) : "r"(a0), "r"(a1), "r"(a2), "r"(a3), "r"(b0), "r"(b1), "f"(0.f));
}
__device__ __forceinline__ void mma8_z(float* d, uint32_t a0, uint32_t a1, uint32_t b0) {
  asm volatile("mma.sync.aligned.m16n8k8.row.col.f32.bf16.bf16.f32 {%0,%1,%2,%3}, {%4,%5}, {%6}, {%7,%7,%7,%7};"
    : "=f"(d[0]), "=f"(d[1]), "=f"(d[2]), "=f"(d[3]) : "r"(a0), "r"(a1), "r"(b0), "f"(0.f));
}
#define OFF(f) ((uint32_t)offsetof(RSmem, f))
#define BAR_SYNC(id, n) asm volatile("bar.sync %0, %1;" :: "n"(id), "n"(n) : "memory")
#define BAR_ARRIVE(id, n) asm volatile("bar.arrive %0, %1;" :: "n"(id), "n"(n) : "memory")

__device__ __forceinline__ void sts128(uint32_t a, uint32_t x, uint32_t y, uint32_t z, uint32_t w) { asm volatile("st.shared.v4.u32 [%0], {%1,%2,%3,%4};" :: "r"(a), "r"(x), "r"(y), "r"(z), "r"(w) : "memory"); }
template <int K>
__device__ __forceinline__ void kstep(const uint4 (&W)[42], float (&acc)[7][4], uint32_t b0, uint32_t b1, uint4& w6, uint32_t ws) {
#pragma unroll
  for (int t = 0; t < 6; t++) {
    const uint4& w = W[K * 6 + t];
    if (K == 0) mma_z(acc[t], w.x, w.y, w.z, w.w, b0, b1); else mma16816(acc[t], w.x, w.y, w.z, w.w, b0, b1);
  }
  if (K == 0) mma_z(acc[6], w6.x, w6.y, w6.z, w6.w, b0, b1); else mma16816(acc[6], w6.x, w6.y, w6.z, w6.w, b0, b1);
  if (K < 6) w6 = lds128(ws + (K + 1) * 512);
}
__device__ __forceinline__ uint4* acc_ptr(int step, int vec, int lane) { return g_ACC16 + (((step >> 1) * 16 + vec) * 2 + (step & 1)) * 32 + lane; }

__global__ void __cluster_dims__(4, 1, 1) __launch_bounds__(384, 1) r_kernel(const bf16* mem0, int poll_delay) {
  extern __shared__ __align__(128) unsigned char smem_raw[];
  RSmem& sm = *reinterpret_cast<RSmem*>(smem_raw);
  const int h = blockIdx.x >> 2, j = blockIdx.x & 3;
  const int w = threadIdx.x >> 5, lane = threadIdx.x & 31, q = w & 3, role = w >> 2;
  const uint32_t sb = smem_u32(smem_raw);
  const uint32_t bar_ld = sb + OFF(bar_ld), bar_sx = sb + OFF(bar_sx), bar_sm = sb + OFF(bar_sm);
  if (threadIdx.x == 0) {
    for (int i = 0; i < NST; i++) asm volatile("mbarrier.init.shared::cta.b64 [%0], 1;" :: "r"(bar_ld + 8 * i));
    asm volatile("mbarrier.init.shared::cta.b64 [%0], 1;" :: "r"(bar_sx));
    asm volatile("mbarrier.init.shared::cta.b64 [%0], 1;" :: "r"(bar_sm));
    asm volatile("fence.mbarrier_init.release.cluster;" ::: "memory");
    arm_bar(bar_sx, 4096); arm_bar(bar_sm, 1024);
    for (int s = 0; s < NST - 1; s++) {
      arm_bar(bar_ld + 8 * s, 15360);
      bulk_g2s(smem_u32(sm.kf[s]), g_KF + ((s * NH + h) * 4 + j) * 512, 8192, bar_ld + 8 * s);
      bulk_g2s(smem_u32(sm.vf[s]), g_VF + ((s * NH + h) * 56 + 14 * j) * 32, 7168, bar_ld + 8 * s);
    }
    sm.sinv[0] = 1.f;
  }
  if (threadIdx.x < NSEG) sm.xmax[threadIdx.x] = g_xmax[threadIdx.x];
  if (role < 2) {
    const uint4* wf = g_WF + (((role * NH + h) * 28 + 7 * j + 6) * 28 + 7 * q) * 32 + lane;
#pragma unroll
    for (int e = 0; e < 7; e++) sm.wS[w][e][lane] = wf[e * 32];
  }
  asm volatile("barrier.cluster.arrive.release.aligned;\nbarrier.cluster.wait.acquire.aligned;" ::: "memory");

  const uint32_t l8 = sb + lane * 8, l16 = sb + lane * 16;
  const float LOG2E = 1.4426950408889634f;

  if (role == 0) {
    asm volatile("setmaxnreg.inc.sync.aligned.u32 232;");
    uint4 W[42];
    {
      const uint4* wf = g_WF + ((h * 28 + 7 * j) * 28 + 7 * q) * 32 + lane;
#pragma unroll
      for (int k = 0; k < 7; k++)
#pragma unroll
        for (int t = 0; t < 6; t++) W[k * 6 + t] = wf[(t * 28 + k) * 32];
    }
    const uint32_t ws = l16 + OFF(wS) + w * 7 * 512;
    const uint32_t mq = l16 + OFF(memF) + q * 2048, mj = l16 + OFF(memF) + j * 2048;
    const uint32_t dst_sm = mapa(l8 + OFF(sm) + j * 256, q), dst_bar = mapa(bar_sm, q);
    uint2* kmf = g_KMF + (((h * 4 + j) * 4 + q) * 7) * 32 + lane;
#pragma unroll 1
    for (int s = 0; s < NSEG; s++) {
      uint4 w6 = lds128(ws);
      float acc[7][4];
      uint32_t b[14];
      if (s > 0) {
        const uint4* p = acc_ptr(s, q * 4, lane);
        STAMP(0);
        uint4 v0 = ld_relaxed_u4(p), v1 = ld_relaxed_u4(p + 64), v2 = ld_relaxed_u4(p + 128), v3 = ld_relaxed_u4(p + 192);
        if (!__all_sync(0xffffffffu, __byte_perm(v0.w, v1.w, 0x7632) == 0x4C004C00u && __byte_perm(v2.w, v3.w, 0x7632) == 0x4C004C00u)) {
#pragma unroll 1
          for (int n = 0; n < SPIN_LIMIT; n++) {
            v0 = ld_relaxed_u4(p); v1 = ld_relaxed_u4(p + 64); v2 = ld_relaxed_u4(p + 128); v3 = ld_relaxed_u4(p + 192);
            if (__all_sync(0xffffffffu, __byte_perm(v0.w, v1.w, 0x7632) == 0x4C004C00u && __byte_perm(v2.w, v3.w, 0x7632) == 0x4C004C00u)) break;
          }
        }
        STAMP(1);
        b[0] = h2_to_bf2(v0.x); b[1] = h2_to_bf2(v0.y); b[2] = h2_to_bf2(v0.z); b[3] = h2_to_bf2(v1.x); b[4] = h2_to_bf2(v1.y); b[5] = h2_to_bf2(v1.z);
        b[6] = h2_to_bf2(__byte_perm(v0.w, v1.w, 0x5410)); b[7] = h2_to_bf2(__byte_perm(v2.w, v3.w, 0x5410));
        b[8] = h2_to_bf2(v2.x); b[9] = h2_to_bf2(v2.y); b[10] = h2_to_bf2(v2.z); b[11] = h2_to_bf2(v3.x); b[12] = h2_to_bf2(v3.y); b[13] = h2_to_bf2(v3.z);
      } else {
        const uint32_t* r = (const uint32_t*)(mem0 + (lane >> 2) * DM + q * 112 + (lane & 3) * 2);
#pragma unroll
        for (int i = 0; i < 14; i++) b[i] = r[i * 4];
      }
      kstep<0>(W, acc, b[0], b[1], w6, ws);
      sts128(mq, b[0], b[1], b[2], b[3]); sts128(mq + 512, b[4], b[5], b[6], b[7]); sts128(mq + 1024, b[8], b[9], b[10], b[11]); sts64(mq + 1536, b[12], b[13]);
      BAR_ARRIVE(0, 384);
      uint4 p1 = lds128(mq + 512);
      kstep<1>(W, acc, b[2], b[3], w6, ws);
      kstep<2>(W, acc, p1.x, p1.y, w6, ws);
      uint4 p2 = lds128(mq + 1024);
      kstep<3>(W, acc, p1.z, p1.w, w6, ws);
      kstep<4>(W, acc, p2.x, p2.y, w6, ws);
      uint2 p3 = lds64(mq + 1536);
      kstep<5>(W, acc, p2.z, p2.w, w6, ws);
      kstep<6>(W, acc, p3.x, p3.y, w6, ws);
      BAR_SYNC(1, 256);
      uint4 a0 = lds128(mj), a1 = lds128(mj + 512), a2 = lds128(mj + 1024); uint2 a3 = lds64(mj + 1536);
      STAMP(3);
      uint32_t kl[7], kh[7];
#pragma unroll
      for (int t = 0; t < 7; t++) { kl[t] = movm(pack_bf16(acc[t][0], acc[t][1])); kh[t] = movm(pack_bf16(acc[t][2], acc[t][3])); }
      float dl[4], dh[4], el[4], eh[4];
      mma_z(dl, a0.x, a0.y, a0.z, a0.w, kl[0], kl[1]); mma_z(dh, a0.x, a0.y, a0.z, a0.w, kh[0], kh[1]);
      mma_z(el, a1.x, a1.y, a1.z, a1.w, kl[2], kl[3]); mma_z(eh, a1.x, a1.y, a1.z, a1.w, kh[2], kh[3]);
      mma16816(dl, a2.x, a2.y, a2.z, a2.w, kl[4], kl[5]); mma16816(dh, a2.x, a2.y, a2.z, a2.w, kh[4], kh[5]);
      mma1688(el, a3.x, a3.y, kl[6]); mma1688(eh, a3.x, a3.y, kh[6]);
      sts64f(l8 + OFF(sred) + q * 256, (dl[0] + dh[2]) + (el[0] + eh[2]), (dl[1] + dh[3]) + (el[1] + eh[3]));
      BAR_SYNC(2, 128);
      {
        float2 t0 = lds64f(l8 + OFF(sred)), t1 = lds64f(l8 + OFF(sred) + 256), t2 = lds64f(l8 + OFF(sred) + 512), t3 = lds64f(l8 + OFF(sred) + 768);
        st_async2(dst_sm, (t0.x + t1.x) + (t2.x + t3.x), (t0.y + t1.y) + (t2.y + t3.y), dst_bar);
      }
      STAMP(4);
      {
        const __nv_bfloat162 iv = __float2bfloat162_rn(__uint_as_float(lds32(sb + OFF(sinv) + (s & 1) * 4)));
        auto us = [&](uint32_t v) { __nv_bfloat162 t = __hmul2(*reinterpret_cast<__nv_bfloat162*>(&v), iv); return *reinterpret_cast<uint32_t*>(&t); };
#pragma unroll
        for (int t = 0; t < 7; t++) kmf[t * 32] = make_uint2(us(kl[t]), us(kh[t]));
        kmf += NH * 4 * 28 * 32;
      }
      BAR_SYNC(4, 256);
      unsigned tred = clk();
      if (threadIdx.x == 0) { arm_bar(bar_sx, 4096); arm_bar(bar_sm, 1024); }
      __syncwarp();
      while (clk() - tred < (unsigned)poll_delay) {}
    }
  } else if (role == 1) {
    asm volatile("setmaxnreg.inc.sync.aligned.u32 216;");
    uint4 W[42];
    {
      const uint4* wf = g_WF + (((NH + h) * 28 + 7 * j) * 28 + 7 * q) * 32 + lane;
#pragma unroll
      for (int k = 0; k < 7; k++)
#pragma unroll
        for (int t = 0; t < 6; t++) W[k * 6 + t] = wf[(t * 28 + k) * 32];
    }
    const uint32_t ws = l16 + OFF(wS) + w * 7 * 512;
    const uint32_t mq = l16 + OFF(memF) + q * 2048;
    const uint32_t uq = l16 + OFF(uQ) + q * 4;
#pragma unroll 1
    for (int s = 0; s < NSEG; s++) {
      BAR_SYNC(0, 384);
      uint4 p0 = lds128(mq);
      {
        uint4 p1 = lds128(mq + 512), p2 = lds128(mq + 1024); uint2 p3 = lds64(mq + 1536);
        const uint32_t M = 0x7fff7fffu;
        uint32_t m = __vmaxu2(__vmaxu2(__vmaxu2(p0.x & M, p0.y & M), __vmaxu2(p0.z & M, p0.w & M)), __vmaxu2(__vmaxu2(p1.x & M, p1.y & M), __vmaxu2(p1.z & M, p1.w & M)));
        m = __vmaxu2(m, __vmaxu2(__vmaxu2(__vmaxu2(p2.x & M, p2.y & M), __vmaxu2(p2.z & M, p2.w & M)), __vmaxu2(p3.x & M, p3.y & M)));
        m = max(m & 0xffffu, m >> 16);
        m = __reduce_max_sync(0xffffffffu, m);
        if (lane == 0) sts32(sb + OFF(smax) + q * 4, m);
      }
      uint4 w6 = lds128(ws);
      BAR_SYNC(1, 256);
      p0 = lds128(mq);
      STAMP(10);
      float acc[7][4];
      kstep<0>(W, acc, p0.x, p0.y, w6, ws);
      uint4 p1 = lds128(mq + 512);
      kstep<1>(W, acc, p0.z, p0.w, w6, ws);
      kstep<2>(W, acc, p1.x, p1.y, w6, ws);
      p0 = lds128(mq + 1024);
      kstep<3>(W, acc, p1.z, p1.w, w6, ws);
      kstep<4>(W, acc, p0.x, p0.y, w6, ws);
      uint2 p3 = lds64(mq + 1536);
      kstep<5>(W, acc, p0.z, p0.w, w6, ws);
      kstep<6>(W, acc, p3.x, p3.y, w6, ws);
#pragma unroll
      for (int t = 0; t < 7; t++) { sts32(uq + (2 * t) * 512, pack_bf16(acc[t][0], acc[t][1])); sts32(uq + (2 * t + 1) * 512, pack_bf16(acc[t][2], acc[t][3])); }
      BAR_ARRIVE(3, 256);
      STAMP(11);
      if (threadIdx.x == 128 && s + NST - 1 < NSEG) {
        int s2 = s + NST - 1, st2 = s2 & (NST - 1);
        arm_bar(bar_ld + 8 * st2, 15360);
        bulk_g2s(smem_u32(sm.kf[st2]), g_KF + ((s2 * NH + h) * 4 + j) * 512, 8192, bar_ld + 8 * st2);
        bulk_g2s(smem_u32(sm.vf[st2]), g_VF + ((s2 * NH + h) * 56 + 14 * j) * 32, 7168, bar_ld + 8 * st2);
      }
      __syncwarp();
    }
  } else {
    asm volatile("setmaxnreg.dec.sync.aligned.u32 56;");
    const uint32_t dsx = l8 + OFF(sx) + j * 1024 + q * 256;
    const uint32_t mj = l16 + OFF(memF) + j * 2048;
    const int nt0 = q < 2 ? q * 3 : 8 + (q - 2) * 3, nts = 6 + (q >> 1);
    const float bmax = g_bmax;
    float inv = 1.f;
    uint32_t sc_bf = 0x3f803f80u;
    uint32_t* uf = g_UF + (h * 56 + 14 * j) * 32 + lane;
#pragma unroll 1
    for (int s = 0; s < NSEG; s++) {
      const int st = s & (NST - 1);
      wait_bar1(bar_ld + 8 * st, (s / NST) & 1);
      {
        const uint32_t kb = l16 + OFF(kf) + st * 8192 + q * 512;
        uint4 k0 = lds128(kb), k1 = lds128(kb + 2048), k2 = lds128(kb + 4096); uint2 k3 = lds64(kb + 6144);
        BAR_SYNC(0, 384);
        STAMP(2);
        uint4 a0 = lds128(mj), a1 = lds128(mj + 512), a2 = lds128(mj + 1024); uint2 a3 = lds64(mj + 1536);
        float dl[4], dh[4], el[4], eh[4];
        mma_z(dl, a0.x, a0.y, a0.z, a0.w, k0.x, k0.y); mma_z(dh, a0.x, a0.y, a0.z, a0.w, k0.z, k0.w);
        mma_z(el, a1.x, a1.y, a1.z, a1.w, k1.x, k1.y); mma_z(eh, a1.x, a1.y, a1.z, a1.w, k1.z, k1.w);
        mma16816(dl, a2.x, a2.y, a2.z, a2.w, k2.x, k2.y); mma16816(dh, a2.x, a2.y, a2.z, a2.w, k2.z, k2.w);
        mma1688(el, a3.x, a3.y, k3.x); mma1688(eh, a3.x, a3.y, k3.y);
        float s0 = (dl[0] + dh[2]) + (el[0] + eh[2]), s1 = (dl[1] + dh[3]) + (el[1] + eh[3]);
#pragma unroll
        for (int r = 0; r < 4; r++) st_async2(mapa(dsx, r), s0, s1, mapa(bar_sx, r));
      }
      STAMP(9);
      float o[4][4], oz[4];
      float mx;
      const float c1 = LOG2E * inv;
      {
        const uint32_t vb = l16 + OFF(vf) + st * 7168;
        wait_bar1(bar_sx, s & 1);
        float sx[8];
#pragma unroll
        for (int kg = 0; kg < 4; kg++) {
          float2 p0 = lds64f(l8 + OFF(sx) + kg * 256), p1 = lds64f(l8 + OFF(sx) + 1024 + kg * 256), p2 = lds64f(l8 + OFF(sx) + 2048 + kg * 256), p3 = lds64f(l8 + OFF(sx) + 3072 + kg * 256);
          sx[2 * kg] = ((p0.x + p1.x) + (p2.x + p3.x)) * c1; sx[2 * kg + 1] = ((p0.y + p1.y) + (p2.y + p3.y)) * c1;
        }
        uint4 v0 = lds128(vb + nt0 * 512), v1 = lds128(vb + nt0 * 512 + 512), v2 = lds128(vb + nt0 * 512 + 1024), v3 = lds128(vb + nts * 512);
        mx = fmaxf(fmaxf(fmaxf(sx[0], sx[1]), fmaxf(sx[2], sx[3])), fmaxf(fmaxf(sx[4], sx[5]), fmaxf(sx[6], sx[7])));
        mx = fmaxf(mx, __shfl_xor_sync(0xffffffffu, mx, 1)); mx = fmaxf(mx, __shfl_xor_sync(0xffffffffu, mx, 2));
#pragma unroll
        for (int i = 0; i < 8; i++) sx[i] = ex2(sx[i] - mx);
        uint32_t p0 = pack_bf16(sx[0], sx[1]), p1 = pack_bf16(sx[2], sx[3]), p2 = pack_bf16(sx[4], sx[5]), p3 = pack_bf16(sx[6], sx[7]);
        mma_z(o[0], p0, 0u, p1, 0u, v0.x, v0.y); mma_z(o[1], p0, 0u, p1, 0u, v1.x, v1.y); mma_z(o[2], p0, 0u, p1, 0u, v2.x, v2.y); mma_z(o[3], p0, 0u, p1, 0u, v3.x, v3.y);
        mma_z(oz, p0, 0u, p1, 0u, 0x3f803f80u, 0x3f803f80u);
        mma16816(o[0], p2, 0u, p3, 0u, v0.z, v0.w); mma16816(o[1], p2, 0u, p3, 0u, v1.z, v1.w); mma16816(o[2], p2, 0u, p3, 0u, v2.z, v2.w); mma16816(o[3], p2, 0u, p3, 0u, v3.z, v3.w);
        mma16816(oz, p2, 0u, p3, 0u, 0x3f803f80u, 0x3f803f80u);
      }
      float ox[8] = {o[0][0], o[0][1], o[1][0], o[1][1], o[2][0], o[2][1], (q & 1) ? o[3][1] : o[3][0], oz[0]};
      uint4* redp = acc_ptr(s + 1, j * 4 + q, lane);
      STAMP(5);
      BAR_SYNC(3, 256);
      uint4 u0 = lds128(l16 + OFF(uQ) + nt0 * 512), u1 = lds128(l16 + OFF(uQ) + nt0 * 512 + 512), u2 = lds128(l16 + OFF(uQ) + nt0 * 512 + 1024), u3 = lds128(l16 + OFF(uQ) + nts * 512);
      float nsc, ninv;
      {
        uint4 m4 = lds128(sb + OFF(smax));
        uint32_t mb = max(max(m4.x, m4.y), max(m4.z, m4.w));
        float mh = fmaxf(__uint_as_float(mb << 16) * inv, __uint_as_float(lds32(sb + OFF(xmax) + s * 4)));
        float bound = mh * bmax;
        int e = (int)(__float_as_uint(bound) >> 23) - 127 + 10;
        int se = min(max(15 - e, -100), 100);
        nsc = __uint_as_float((uint32_t)(127 + se) << 23); ninv = __uint_as_float((uint32_t)(127 - se) << 23);
      }
      STAMP(6);
      wait_bar1(bar_sm, s & 1);
      STAMP(7);
      {
        float2 t0 = lds64f(l8 + OFF(sm)), t1 = lds64f(l8 + OFF(sm) + 256), t2 = lds64f(l8 + OFF(sm) + 512), t3 = lds64f(l8 + OFF(sm) + 768);
        float s0 = ((t0.x + t1.x) + (t2.x + t3.x)) * inv * c1, s1 = ((t0.y + t1.y) + (t2.y + t3.y)) * inv * c1;
        float m = fmaxf(fmaxf(s0, s1), mx);
        m = fmaxf(m, __shfl_xor_sync(0xffffffffu, m, 1)); m = fmaxf(m, __shfl_xor_sync(0xffffffffu, m, 2));
        float e0 = ex2(s0 - m), e1 = ex2(s1 - m), al = ex2(mx - m);
        uint32_t pm = pack_bf16(e0 * inv, e1 * inv);
        float z[4], y0[4], y1[4], y2[4], y3[4];
        mma8_z(z, pm, pm, sc_bf);
        mma_z(y0, pm, pm, pm, pm, u0.x, u0.y); mma_z(y1, pm, pm, pm, pm, u1.x, u1.y); mma_z(y2, pm, pm, pm, pm, u2.x, u2.y); mma_z(y3, pm, pm, pm, pm, u3.x, u3.y);
        mma16816(y0, pm, pm, pm, pm, u0.z, u0.w); mma16816(y1, pm, pm, pm, pm, u1.z, u1.w); mma16816(y2, pm, pm, pm, pm, u2.z, u2.w); mma16816(y3, pm, pm, pm, pm, u3.z, u3.w);
        float iz; asm("rcp.approx.ftz.f32 %0, %1;" : "=f"(iz) : "f"(fmaf(ox[7], al, z[0])));
        iz *= nsc;
        const float ia = iz * al;
        red_h8(redp, pack_f16(fmaf(y0[0], iz, ox[0] * ia), fmaf(y0[1], iz, ox[1] * ia)), pack_f16(fmaf(y1[0], iz, ox[2] * ia), fmaf(y1[1], iz, ox[3] * ia)),
               pack_f16(fmaf(y2[0], iz, ox[4] * ia), fmaf(y2[1], iz, ox[5] * ia)), pack_f16(fmaf((q & 1) ? y3[1] : y3[0], iz, ox[6] * ia), 1.f));
      }
      if (threadIdx.x == 256) sts32(sb + OFF(sinv) + ((s + 1) & 1) * 4, __float_as_uint(ninv));
      BAR_ARRIVE(4, 256);
      STAMP(8);
      {
        auto us = [&](uint4 v) { return pack_bf16(((bf_lo(v.x) + bf_lo(v.y)) + (bf_lo(v.z) + bf_lo(v.w))) * inv, ((bf_hi(v.x) + bf_hi(v.y)) + (bf_hi(v.z) + bf_hi(v.w))) * inv); };
        uf[(nt0 + 0) * 32] = us(u0); uf[(nt0 + 1) * 32] = us(u1); uf[(nt0 + 2) * 32] = us(u2);
        if ((q & 1) == 0) uf[nts * 32] = us(u3);
        uf += NH * 56 * 32;
      }
      inv = ninv; { uint32_t t = __float_as_uint(nsc) >> 16; sc_bf = t | (t << 16); }
    }
  }
  asm volatile("barrier.cluster.arrive.release.aligned;\nbarrier.cluster.wait.acquire.aligned;" ::: "memory");
}

__global__ void n_stats(const bf16* x) {
  if (blockIdx.x < 64) {
    float m = 0.f;
    for (int i = threadIdx.x; i < 32 * DM; i += 256) m = fmaxf(m, fabsf(b2f(x[blockIdx.x * 32 * DM + i])));
    atomicMax((unsigned*)&g_xmax[blockIdx.x], __float_as_uint(m));
  } else {
    int r = (blockIdx.x - 64) * 256 + threadIdx.x;
    if (r < NH * DM) { float a = 0.f; for (int k = 0; k < DM; k++) { float v = wf_elem(1, r / DM, r % DM, k); a += v * v; } atomicMax((unsigned*)&g_bmax, __float_as_uint(sqrtf(a))); }
  }
}

int g_poll_delay = POLL_DELAY;
extern "C" void kernel_launch(void* const* d_in, const int* in_sizes, int n_in, void* d_out, int out_size) {
  const bf16* x = (const bf16*)d_in[0];
  const bf16* wqkv = (const bf16*)d_in[1];
  const bf16* wphi = (const bf16*)d_in[2];
  const bf16* wo_a = (const bf16*)d_in[3];
  const bf16* mem0 = (const bf16*)d_in[5];
  const bf16* Wq = (const bf16*)d_in[6];
  const bf16* Wk = (const bf16*)d_in[7];
  const bf16* Wv = (const bf16*)d_in[8];
  const bf16* Wo = (const bf16*)d_in[9];
  const bf16* gate_w = (const bf16*)d_in[11];
  bf16* out = (bf16*)d_out;
  cudaFuncSetAttribute(r_kernel, cudaFuncAttributeMaxDynamicSharedMemorySize, (int)sizeof(RSmem));
  n_zero<<<(NSEG * 40 * 32 + 255) / 256, 256>>>();
  n_prep<<<(2 * NH * 28 * 28 * 32 + 255) / 256, 256>>>(Wq, Wk, Wv, Wo);
  n_stats<<<64 + 28, 256>>>(x);
  n_xgemm<<<2 * NH * 28 * NSEG * 32 / 256, 256>>>(x);
  r_kernel<<<64, 384, sizeof(RSmem)>>>(mem0, g_poll_delay);
  n_qkv<<<(S_LEN * 1344 + 255) / 256, 256>>>(x, wqkv);
  n_phi<<<(S_LEN * 2 * NH + 255) / 256, 256>>>(wphi);
  n_kv<<<(32 * NH * 56 * 29 + 255) / 256, 256>>>();
  n_oa<<<(S_LEN * DM + 255) / 256, 256>>>();
  n_x3<<<NSEG, 512>>>(x, wo_a, gate_w, out);
}
```

```cpp
#include <cuda_runtime.h>
#include <cuda_bf16.h>
#include <stdint.h>
#include <stddef.h>

typedef __nv_bfloat16 bf16;
#define S_LEN 2048
#define DM 448
#define NH 16
#define NSEG 64
#define SPIN_LIMIT (1 << 22)

__device__ uint4 g_WF[2 * NH * 28 * 28 * 32];
__device__ uint4 g_KF[NSEG * NH * 4 * 4 * 4 * 32];
__device__ uint4 g_VF[NSEG * NH * 56 * 32];
__device__ uint2 g_KMF[NSEG * NH * 4 * 28 * 32];
__device__ uint32_t g_UF[NSEG * NH * 56 * 32];
__device__ uint4 g_ACC16[(NSEG + 2) * 16 * 32];
__device__ float g_xmax[NSEG];
__device__ float g_bmax;
__device__ float g_inv0;
__device__ float g_qkv[S_LEN * 1344];
__device__ float g_phiq[S_LEN * NH * 56];
__device__ float g_phik[S_LEN * NH * 56];
__device__ float g_kv[NH * 56 * 29];
__device__ float g_oa[S_LEN * DM];
__device__ int g_err;
__device__ unsigned g_ts[64 * 64 * 16];

__device__ __forceinline__ uint32_t pack_bf16(float lo, float hi) {
  uint32_t r; asm("cvt.rn.bf16x2.f32 %0, %1, %2;" : "=r"(r) : "f"(hi), "f"(lo)); return r;
}
__device__ __forceinline__ float bf_lo(uint32_t v) { return __uint_as_float(v << 16); }
__device__ __forceinline__ float bf_hi(uint32_t v) { return __uint_as_float(v & 0xffff0000u); }
__device__ __forceinline__ float b2f(bf16 v) { return __bfloat162float(v); }

__global__ void n_prep(const bf16* Wq, const bf16* Wk, const bf16* Wv, const bf16* Wo) {
  int idx = blockIdx.x * blockDim.x + threadIdx.x;
  if (idx >= 2 * NH * 28 * 28 * 32) return;
  int lane = idx & 31, r = idx >> 5;
  int ks = r % 28; r /= 28; int tile = r % 28; r /= 28; int h = r % NH; int mat = r / NH;
  int g = lane >> 2, tq = lane & 3;
  float v[8];
  for (int i = 0; i < 8; i++) {
    int row = tile * 16 + g + ((i >> 1) & 1) * 8;
    int col = ks * 16 + tq * 2 + (i & 1) + (i >> 2) * 8;
    float acc = 0.f;
    if (mat == 0) { for (int e = 0; e < 256; e++) acc += b2f(Wq[(row * NH + h) * 256 + e]) * b2f(Wk[(col * NH + h) * 256 + e]); acc *= 0.0625f; }
    else { for (int e = 0; e < 256; e++) acc += b2f(Wo[(h * 256 + e) * DM + row]) * b2f(Wv[(col * NH + h) * 256 + e]); }
    v[i] = acc;
  }
  g_WF[idx] = make_uint4(pack_bf16(v[0], v[1]), pack_bf16(v[2], v[3]), pack_bf16(v[4], v[5]), pack_bf16(v[6], v[7]));
}
__device__ __forceinline__ float wf_elem(int mat, int h, int row, int col) {
  int tile = row >> 4, ks = col >> 4, rr = row & 15, cc = col & 15;
  int lane = (rr & 7) * 4 + ((cc & 7) >> 1);
  int reg = (rr >> 3) + (cc >> 3) * 2;
  uint32_t w = ((const uint32_t*)g_WF)[((((mat * NH + h) * 28 + tile) * 28 + ks) * 32 + lane) * 4 + reg];
  return (cc & 1) ? bf_hi(w) : bf_lo(w);
}
__device__ __forceinline__ void mma16816(float* d, uint32_t a0, uint32_t a1, uint32_t a2, uint32_t a3, uint32_t b0, uint32_t b1) {
  asm volatile("mma.sync.aligned.m16n8k16.row.col.f32.bf16.bf16.f32 {%0,%1,%2,%3}, {%4,%5,%6,%7}, {%8,%9}, {%0,%1,%2,%3};"
    : "+f"(d[0]), "+f"(d[1]), "+f"(d[2]), "+f"(d[3]) : "r"(a0), "r"(a1), "r"(a2), "r"(a3), "r"(b0), "r"(b1));
}
__device__ __forceinline__ void mma1688(float* d, uint32_t a0, uint32_t a1, uint32_t b0) {
  asm volatile("mma.sync.aligned.m16n8k8.row.col.f32.bf16.bf16.f32 {%0,%1,%2,%3}, {%4,%5}, {%6}, {%0,%1,%2,%3};"
    : "+f"(d[0]), "+f"(d[1]), "+f"(d[2]), "+f"(d[3]) : "r"(a0), "r"(a1), "r"(b0));
}
__device__ __forceinline__ uint32_t movm(uint32_t a) { uint32_t d; asm volatile("movmatrix.sync.aligned.m8n8.trans.b16 %0, %1;" : "=r"(d) : "r"(a)); return d; }

__global__ void n_xgemm(const bf16* x) {
  int wid = (blockIdx.x * blockDim.x + threadIdx.x) >> 5, lane = threadIdx.x & 31;
  int seg = wid % NSEG; int r = wid / NSEG;
  int tile = r % 28; r /= 28; int h = r % NH; int mat = r / NH;
  if (mat >= 2) return;
  int g = lane >> 2, tq = lane & 3;
  float d[4][4] = {};
  const uint4* wf = g_WF + (((mat * NH + h) * 28 + tile) * 28) * 32 + lane;
  for (int ks = 0; ks < 28; ks++) {
    uint4 a = wf[ks * 32];
    for (int kg = 0; kg < 4; kg++) {
      const uint32_t* xr = (const uint32_t*)(x + (seg * 32 + kg * 8 + g) * DM + ks * 16 + tq * 2);
      mma16816(d[kg], a.x, a.y, a.z, a.w, xr[0], xr[4]);
    }
  }
  if (mat == 0) {
    for (int kg = 0; kg < 4; kg++) {
      uint32_t b0 = movm(pack_bf16(d[kg][0], d[kg][1])), b1 = movm(pack_bf16(d[kg][2], d[kg][3]));
      int jj = tile / 7, i = tile % 7;
      uint32_t* dst = (uint32_t*)&g_KF[((((seg * NH + h) * 4 + jj) * 4 + (i >> 1)) * 4 + kg) * 32 + lane];
      if (i == 6) { dst[0] = b0; dst[1] = b1; } else { dst[i & 1] = b0; dst[2 + (i & 1)] = b1; }
    }
  } else {
    g_VF[((seg * NH + h) * 56 + tile * 2) * 32 + lane] = make_uint4(pack_bf16(d[0][0], d[0][1]), pack_bf16(d[1][0], d[1][1]), pack_bf16(d[2][0], d[2][1]), pack_bf16(d[3][0], d[3][1]));
    g_VF[((seg * NH + h) * 56 + tile * 2 + 1) * 32 + lane] = make_uint4(pack_bf16(d[0][2], d[0][3]), pack_bf16(d[1][2], d[1][3]), pack_bf16(d[2][2], d[2][3]), pack_bf16(d[3][2], d[3][3]));
  }
}
__global__ void n_zero() {
  int i = blockIdx.x * blockDim.x + threadIdx.x;
  if (i < (NSEG + 2) * 16 * 32) g_ACC16[i] = make_uint4(0, 0, 0, 0);
  if (i < NSEG) g_xmax[i] = 0.f;
  if (i == 0) g_bmax = 0.f;
  if (i < NH * 56 * 29) g_kv[i] = 0.f;
}
__global__ void n_qkv(const bf16* x, const bf16* w) {
  int i = blockIdx.x * blockDim.x + threadIdx.x;
  if (i >= S_LEN * 1344) return;
  int n = i % 1344, t = i / 1344;
  float acc = 0.f;
  for (int k = 0; k < DM; k++) acc += b2f(x[t * DM + k]) * b2f(w[k * 1344 + n]);
  g_qkv[i] = acc;
}
__global__ void n_phi(const bf16* wphi) {
  int i = blockIdx.x * blockDim.x + threadIdx.x;
  if (i >= S_LEN * 2 * NH) return;
  int h = i % NH, which = (i / NH) % 2, t = i / (2 * NH);
  float p[28]; float mx = -1e30f, mn = 1e30f;
  for (int f = 0; f < 28; f++) {
    float acc = 0.f;
    for (int d = 0; d < 28; d++) acc += g_qkv[t * 1344 + which * 448 + h * 28 + d] * b2f(wphi[(h * 28 + d) * 28 + f]);
    p[f] = acc; mx = fmaxf(mx, acc); mn = fminf(mn, acc);
  }
  float s1 = 0.f, s2 = 0.f;
  for (int f = 0; f < 28; f++) { s1 += __expf(p[f] - mx); s2 += __expf(mn - p[f]); }
  float* o = (which ? g_phik : g_phiq) + (t * NH + h) * 56;
  for (int f = 0; f < 28; f++) { o[f] = __expf(p[f] - mx) / s1; o[28 + f] = __expf(mn - p[f]) / s2; }
}
__global__ void n_kv() {
  int i = blockIdx.x * blockDim.x + threadIdx.x;
  if (i >= 32 * NH * 56 * 29) return;
  int d = i % 29, f = (i / 29) % 56, h = (i / (29 * 56)) % NH, ch = i / (29 * 56 * NH);
  float acc = 0.f;
  for (int t = ch * 64; t < ch * 64 + 64; t++) acc += g_phik[(t * NH + h) * 56 + f] * (d < 28 ? g_qkv[t * 1344 + 896 + h * 28 + d] : 1.f);
  atomicAdd(&g_kv[(h * 56 + f) * 29 + d], acc);
}
__global__ void n_oa() {
  int i = blockIdx.x * blockDim.x + threadIdx.x;
  if (i >= S_LEN * DM) return;
  int c = i % DM, t = i / DM, h = c / 28, d = c % 28;
  float num = 0.f, den = 0.f;
  for (int f = 0; f < 56; f++) { float p = g_phiq[(t * NH + h) * 56 + f]; num += p * g_kv[(h * 56 + f) * 29 + d]; den += p * g_kv[(h * 56 + f) * 29 + 28]; }
  g_oa[i] = num / (den + 1e-6f);
}

__global__ void __launch_bounds__(512) n_x3(const bf16* x, const bf16* wo, const bf16* gate_w, bf16* out) {
  __shared__ uint32_t sP[NH][2][32][10];
  __shared__ float sG[32];
  int seg = blockIdx.x, w = threadIdx.x >> 5, lane = threadIdx.x & 31, g = lane >> 2, tq = lane & 3;
  for (int r = w; r < 32; r += 16) {
    float acc = 0.f;
    for (int k = lane; k < DM; k += 32) acc += b2f(x[(seg * 32 + r) * DM + k]) * b2f(gate_w[k]);
    for (int o = 16; o; o >>= 1) acc += __shfl_xor_sync(0xffffffffu, acc, o);
    if (lane == 0) sG[r] = 1.f / (1.f + __expf(-acc));
  }
  {
    int h = w;
    float s[2][5][4] = {};
    for (int ct = 0; ct < 28; ct++) {
      uint32_t a[2][4];
      for (int m = 0; m < 2; m++) {
        const uint32_t* r0 = (const uint32_t*)(x + (seg * 32 + m * 16 + g) * DM + ct * 16 + tq * 2);
        const uint32_t* r1 = (const uint32_t*)(x + (seg * 32 + m * 16 + g + 8) * DM + ct * 16 + tq * 2);
        a[m][0] = r0[0]; a[m][1] = r1[0]; a[m][2] = r0[4]; a[m][3] = r1[4];
      }
      int j = ct / 7, i = ct % 7;
      for (int kg = 0; kg < 4; kg++) {
        const uint32_t* src = (const uint32_t*)&g_KF[((((seg * NH + h) * 4 + j) * 4 + (i >> 1)) * 4 + kg) * 32 + lane];
        uint2 b = i == 6 ? make_uint2(src[0], src[1]) : make_uint2(src[i & 1], src[2 + (i & 1)]);
        for (int m = 0; m < 2; m++) mma16816(s[m][1 + kg], a[m][0], a[m][1], a[m][2], a[m][3], b.x, b.y);
      }
      for (int q = 0; q < 4; q++) {
        uint2 b = g_KMF[((((seg * NH + h) * 4 + j) * 4 + q) * 7 + i) * 32 + lane];
        for (int m = 0; m < 2; m++) mma16816(s[m][0], a[m][0], a[m][1], a[m][2], a[m][3], b.x, b.y);
      }
    }
    for (int m = 0; m < 2; m++) for (int hf = 0; hf < 2; hf++) {
      int t = m * 16 + hf * 8 + g;
      float v[10]; float mx = -1e30f;
      for (int n = 0; n < 5; n++) for (int e = 0; e < 2; e++) {
        float val = s[m][n][hf * 2 + e];
        if (n > 0 && (n - 1) * 8 + tq * 2 + e > t) val = -1e30f;
        v[n * 2 + e] = val; mx = fmaxf(mx, val);
      }
      mx = fmaxf(mx, __shfl_xor_sync(0xffffffffu, mx, 1)); mx = fmaxf(mx, __shfl_xor_sync(0xffffffffu, mx, 2));
      float z = 0.f;
      for (int i = 0; i < 10; i++) { v[i] = __expf(v[i] - mx); z += v[i]; }
      z += __shfl_xor_sync(0xffffffffu, z, 1); z += __shfl_xor_sync(0xffffffffu, z, 2);
      float iz = 1.f / z;
      sP[h][m][lane][hf] = pack_bf16(v[0] * iz, v[1] * iz);
      sP[h][m][lane][2 + hf] = pack_bf16(v[2] * iz, v[3] * iz);
      sP[h][m][lane][4 + hf] = pack_bf16(v[4] * iz, v[5] * iz);
      sP[h][m][lane][6 + hf] = pack_bf16(v[6] * iz, v[7] * iz);
      sP[h][m][lane][8 + hf] = pack_bf16(v[8] * iz, v[9] * iz);
    }
  }
  __syncthreads();
  if (w < 14) {
    float o[2][4][4] = {};
    for (int h = 0; h < NH; h++) {
      for (int n = 0; n < 4; n++) {
        int nt = w * 4 + n;
        uint4 v = g_VF[((seg * NH + h) * 56 + nt) * 32 + lane];
        uint32_t u = g_UF[((seg * NH + h) * 56 + nt) * 32 + lane];
        for (int m = 0; m < 2; m++) {
          const uint32_t* p = sP[h][m][lane];
          mma1688(o[m][n], p[0], p[1], u);
          mma16816(o[m][n], p[2], p[3], p[4], p[5], v.x, v.y);
          mma16816(o[m][n], p[6], p[7], p[8], p[9], v.z, v.w);
        }
      }
    }
    for (int m = 0; m < 2; m++) for (int n = 0; n < 4; n++) for (int i = 0; i < 4; i++) {
      int r = m * 16 + (i >> 1) * 8 + g, c = (w * 4 + n) * 8 + tq * 2 + (i & 1);
      int t = seg * 32 + r;
      float a = 0.f;
      for (int k = 0; k < DM; k++) a += g_oa[t * DM + k] * b2f(wo[k * DM + c]);
      float gt = sG[r];
      out[t * DM + c] = __float2bfloat16(gt * a + (1.f - gt) * o[m][n][i]);
    }
  }
}

__device__ __forceinline__ uint32_t smem_u32(const void* p) { return (uint32_t)__cvta_generic_to_shared(p); }
__device__ __forceinline__ uint32_t mapa(uint32_t a, uint32_t r) { uint32_t o; asm volatile("mapa.shared::cluster.u32 %0, %1, %2;" : "=r"(o) : "r"(a), "r"(r)); return o; }
__device__ __forceinline__ bool try_wait(uint32_t bar, uint32_t parity) {
  uint32_t ok; asm volatile("{\n.reg .pred p;\nmbarrier.try_wait.parity.shared::cta.b64 p, [%1], %2;\nselp.u32 %0, 1, 0, p;\n}" : "=r"(ok) : "r"(bar), "r"(parity) : "memory"); return ok; }
__device__ __forceinline__ void wait_bar(uint32_t bar, uint32_t parity) {
  int n = 0; while (!try_wait(bar, parity)) { if (++n > SPIN_LIMIT) { g_err = 1; break; } } }
__device__ __forceinline__ void arm_bar(uint32_t bar, uint32_t bytes) { asm volatile("mbarrier.arrive.expect_tx.shared::cta.b64 _, [%0], %1;" :: "r"(bar), "r"(bytes) : "memory"); }
__device__ __forceinline__ float4 ld_relaxed4(const void* p) { float4 v; asm volatile("ld.relaxed.gpu.global.v4.f32 {%0,%1,%2,%3}, [%4];" : "=f"(v.x), "=f"(v.y), "=f"(v.z), "=f"(v.w) : "l"(p) : "memory"); return v; }
__device__ __forceinline__ void red4(void* p, float a, float b, float c, float d) { asm volatile("red.relaxed.gpu.global.add.v4.f32 [%0], {%1,%2,%3,%4};" :: "l"(p), "f"(a), "f"(b), "f"(c), "f"(d) : "memory"); }
__device__ __forceinline__ void st_async2(uint32_t dst, float a, float b, uint32_t bar) { asm volatile("st.async.shared::cluster.mbarrier::complete_tx::bytes.v2.f32 [%0], {%1,%2}, [%3];" :: "r"(dst), "f"(a), "f"(b), "r"(bar) : "memory"); }
__device__ __forceinline__ void bulk_g2s(uint32_t dst, const void* src, uint32_t bytes, uint32_t bar) {
  asm volatile("cp.async.bulk.shared::cluster.global.mbarrier::complete_tx::bytes [%0], [%1], %2, [%3];" :: "r"(dst), "l"(src), "r"(bytes), "r"(bar) : "memory"); }
__device__ __forceinline__ unsigned clk() { unsigned c; asm volatile("mov.u32 %0, %%clock;" : "=r"(c) :: "memory"); return c; }
__device__ __forceinline__ float ex2(float x) { float y; asm("ex2.approx.ftz.f32 %0, %1;" : "=f"(y) : "f"(x)); return y; }

#define NST 4
struct RSmem {
  uint4 kf[NST][4][4][32];
  uint4 vf[NST][14][32];
  uint4 wS[8][7][32];
  uint4 memF[4][4][32];
  float4 sx[4][2][32];
  float2 sm[4][32];
  float2 sred[4][32];
  uint4 uQ[4][4][32];
  uint32_t smax[4];
  float xmax[NSEG];
  float sinv[4];
  unsigned long long bar_ld[NST], bar_sx, bar_sm;
  unsigned ts[64 * 16];
};
#define POLL_DELAY 300
#define STAMP(i)
__device__ __forceinline__ void wait_slow(uint32_t bar, uint32_t parity) {
#pragma unroll 1
  for (int n = 0; n < SPIN_LIMIT; n++) if (try_wait(bar, parity)) return;
  g_err = 1;
}
__device__ __forceinline__ void wait_bar1(uint32_t bar, uint32_t parity) { if (!try_wait(bar, parity)) wait_slow(bar, parity); }
__device__ __forceinline__ uint4 ld_relaxed_u4(const void* p) { uint4 v; asm volatile("ld.relaxed.gpu.global.v4.u32 {%0,%1,%2,%3}, [%4];" : "=r"(v.x), "=r"(v.y), "=r"(v.z), "=r"(v.w) : "l"(p) : "memory"); return v; }
__device__ __forceinline__ void red_h8(void* p, uint32_t a, uint32_t b, uint32_t c, uint32_t d) { asm volatile("red.relaxed.gpu.global.add.noftz.v4.f16x2 [%0], {%1,%2,%3,%4};" :: "l"(p), "r"(a), "r"(b), "r"(c), "r"(d) : "memory"); }
__device__ __forceinline__ uint32_t pack_f16(float lo, float hi) { uint32_t r; asm("cvt.rn.f16x2.f32 %0, %1, %2;" : "=r"(r) : "f"(hi), "f"(lo)); return r; }
__device__ __forceinline__ uint32_t h2_to_bf2(uint32_t v) {
  float lo, hi; asm("{.reg .f16 l, h; mov.b32 {l, h}, %2; cvt.f32.f16 %0, l; cvt.f32.f16 %1, h;}" : "=f"(lo), "=f"(hi) : "r"(v)); return pack_bf16(lo, hi); }
__device__ __forceinline__ uint2 lds64(uint32_t a) { uint2 v; asm volatile("ld.shared.v2.u32 {%0,%1}, [%2];" : "=r"(v.x), "=r"(v.y) : "r"(a) : "memory"); return v; }
__device__ __forceinline__ float2 lds64f(uint32_t a) { float2 v; asm volatile("ld.shared.v2.f32 {%0,%1}, [%2];" : "=f"(v.x), "=f"(v.y) : "r"(a) : "memory"); return v; }
__device__ __forceinline__ uint4 lds128(uint32_t a) { uint4 v; asm volatile("ld.shared.v4.u32 {%0,%1,%2,%3}, [%4];" : "=r"(v.x), "=r"(v.y), "=r"(v.z), "=r"(v.w) : "r"(a) : "memory"); return v; }
__device__ __forceinline__ uint32_t lds32(uint32_t a) { uint32_t v; asm volatile("ld.shared.u32 %0, [%1];" : "=r"(v) : "r"(a) : "memory"); return v; }
__device__ __forceinline__ void sts64(uint32_t a, uint32_t x, uint32_t y) { asm volatile("st.shared.v2.u32 [%0], {%1,%2};" :: "r"(a), "r"(x), "r"(y) : "memory"); }
__device__ __forceinline__ void sts64f(uint32_t a, float x, float y) { asm volatile("st.shared.v2.f32 [%0], {%1,%2};" :: "r"(a), "f"(x), "f"(y) : "memory"); }
__device__ __forceinline__ void sts32(uint32_t a, uint32_t x) { asm volatile("st.shared.u32 [%0], %1;" :: "r"(a), "r"(x) : "memory"); }
__device__ __forceinline__ void mma_z(float* d, uint32_t a0, uint32_t a1, uint32_t a2, uint32_t a3, uint32_t b0, uint32_t b1) {
  asm volatile("mma.sync.aligned.m16n8k16.row.col.f32.bf16.bf16.f32 {%0,%1,%2,%3}, {%4,%5,%6,%7}, {%8,%9}, {%10,%10,%10,%10};"
    : "=f"(d[0]), "=f"(d[1]), "=f"(d[2]), "=f"(d[3]) : "r"(a0), "r"(a1), "r"(a2), "r"(a3), "r"(b0), "r"(b1), "f"(0.f));
}
__device__ __forceinline__ void mma8_z(float* d, uint32_t a0, uint32_t a1, uint32_t b0) {
  asm volatile("mma.sync.aligned.m16n8k8.row.col.f32.bf16.bf16.f32 {%0,%1,%2,%3}, {%4,%5}, {%6}, {%7,%7,%7,%7};"
    : "=f"(d[0]), "=f"(d[1]), "=f"(d[2]), "=f"(d[3]) : "r"(a0), "r"(a1), "r"(b0), "f"(0.f));
}
#define OFF(f) ((uint32_t)offsetof(RSmem, f))
#define BAR_SYNC(id, n) asm volatile("bar.sync %0, %1;" :: "n"(id), "n"(n) : "memory")
#define BAR_ARRIVE(id, n) asm volatile("bar.arrive %0, %1;" :: "n"(id), "n"(n) : "memory")

__device__ __forceinline__ void sts128(uint32_t a, uint32_t x, uint32_t y, uint32_t z, uint32_t w) { asm volatile("st.shared.v4.u32 [%0], {%1,%2,%3,%4};" :: "r"(a), "r"(x), "r"(y), "r"(z), "r"(w) : "memory"); }
template <int K>
__device__ __forceinline__ void kstep(const uint4 (&W)[42], float (&acc)[7][4], uint32_t b0, uint32_t b1, uint4& w6, uint32_t ws) {
#pragma unroll
  for (int t = 0; t < 6; t++) {
    const uint4& w = W[K * 6 + t];
    if (K == 0) mma_z(acc[t], w.x, w.y, w.z, w.w, b0, b1); else mma16816(acc[t], w.x, w.y, w.z, w.w, b0, b1);
  }
  if (K == 0) mma_z(acc[6], w6.x, w6.y, w6.z, w6.w, b0, b1); else mma16816(acc[6], w6.x, w6.y, w6.z, w6.w, b0, b1);
  if (K < 6) w6 = lds128(ws + (K + 1) * 512);
}
__device__ __forceinline__ uint4* acc_ptr(int step, int vec, int lane) { return g_ACC16 + (((step >> 1) * 16 + vec) * 2 + (step & 1)) * 32 + lane; }

__device__ __forceinline__ bool elect1() { uint32_t p; asm volatile("{.reg .pred p; elect.sync _|p, 0xffffffff; selp.u32 %0, 1, 0, p;}" : "=r"(p)); return p; }
__device__ __forceinline__ float4 lds128f(uint32_t a) { float4 v; asm volatile("ld.shared.v4.f32 {%0,%1,%2,%3}, [%4];" : "=f"(v.x), "=f"(v.y), "=f"(v.z), "=f"(v.w) : "r"(a) : "memory"); return v; }
__device__ __forceinline__ uint32_t amax2(uint32_t m, uint32_t x, uint32_t y) { return __vmaxu2(m, __vmaxu2(x & 0x7fff7fffu, y & 0x7fff7fffu)); }

__global__ void __cluster_dims__(4, 1, 1) __launch_bounds__(384, 1) r_kernel(const bf16* mem0, int poll_delay) {
  extern __shared__ __align__(128) unsigned char smem_raw[];
  RSmem& sm = *reinterpret_cast<RSmem*>(smem_raw);
  const int h = blockIdx.x >> 2, j = blockIdx.x & 3;
  const int w = __shfl_sync(0xffffffffu, threadIdx.x >> 5, 0), lane = __shfl_sync(0xffffffffu, threadIdx.x & 31, threadIdx.x & 31), q = w & 3, role = w >> 2;
  const uint32_t sb = smem_u32(smem_raw);
  const uint32_t bar_ld = sb + OFF(bar_ld), bar_sx = sb + OFF(bar_sx), bar_sm = sb + OFF(bar_sm);
  if (threadIdx.x == 0) {
    for (int i = 0; i < NST; i++) asm volatile("mbarrier.init.shared::cta.b64 [%0], 1;" :: "r"(bar_ld + 8 * i));
    asm volatile("mbarrier.init.shared::cta.b64 [%0], 1;" :: "r"(bar_sx));
    asm volatile("mbarrier.init.shared::cta.b64 [%0], 1;" :: "r"(bar_sm));
    asm volatile("fence.mbarrier_init.release.cluster;" ::: "memory");
    arm_bar(bar_sx, 4096); arm_bar(bar_sm, 1024);
    for (int s = 0; s < NST - 1; s++) {
      arm_bar(bar_ld + 8 * s, 15360);
      bulk_g2s(smem_u32(sm.kf[s]), g_KF + ((s * NH + h) * 4 + j) * 512, 8192, bar_ld + 8 * s);
      bulk_g2s(smem_u32(sm.vf[s]), g_VF + ((s * NH + h) * 56 + 14 * j) * 32, 7168, bar_ld + 8 * s);
    }
    sm.sinv[0] = g_inv0;
  }
  if (threadIdx.x < NSEG) sm.xmax[threadIdx.x] = g_xmax[threadIdx.x];
  if (role < 2) {
    const uint4* wf = g_WF + (((role * NH + h) * 28 + 7 * j + 6) * 28 + 7 * q) * 32 + lane;
#pragma unroll
    for (int e = 0; e < 7; e++) sm.wS[w][e][lane] = wf[e * 32];
  }
  asm volatile("barrier.cluster.arrive.release.aligned;\nbarrier.cluster.wait.acquire.aligned;" ::: "memory");

  const uint32_t l8 = sb + lane * 8, l16 = sb + lane * 16;
  const float LOG2E = 1.4426950408889634f;

  if (role == 0) {
    asm volatile("setmaxnreg.inc.sync.aligned.u32 224;");
    uint4 W[42];
    {
      const uint4* wf = g_WF + ((h * 28 + 7 * j) * 28 + 7 * q) * 32 + lane;
#pragma unroll
      for (int k = 0; k < 7; k++)
#pragma unroll
        for (int t = 0; t < 6; t++) W[k * 6 + t] = wf[(t * 28 + k) * 32];
    }
    const uint32_t ws = l16 + OFF(wS) + w * 7 * 512;
    const uint32_t mq = l16 + OFF(memF) + q * 2048, mj = l16 + OFF(memF) + j * 2048;
    const uint32_t dst_sm = mapa(l8 + OFF(sm) + j * 256, q), dst_bar = mapa(bar_sm, q);
#pragma unroll 1
    for (int s = 0; s < NSEG; s++) {
      uint4 w6 = lds128(ws);
      float acc[7][4];
      const uint4* p = acc_ptr(s, q * 4, lane);
      STAMP(0);
      uint4 v0 = ld_relaxed_u4(p), v1 = ld_relaxed_u4(p + 64), v2 = ld_relaxed_u4(p + 128), v3 = ld_relaxed_u4(p + 192);
      if (!__all_sync(0xffffffffu, __byte_perm(v0.w, v1.w, 0x7632) == 0x4C004C00u && __byte_perm(v2.w, v3.w, 0x7632) == 0x4C004C00u)) {
#pragma unroll 1
        for (int n = 0; n < SPIN_LIMIT; n++) {
          v0 = ld_relaxed_u4(p); v1 = ld_relaxed_u4(p + 64); v2 = ld_relaxed_u4(p + 128); v3 = ld_relaxed_u4(p + 192);
          if (__all_sync(0xffffffffu, __byte_perm(v0.w, v1.w, 0x7632) == 0x4C004C00u && __byte_perm(v2.w, v3.w, 0x7632) == 0x4C004C00u)) break;
        }
      }
      STAMP(1);
      const uint32_t b0 = h2_to_bf2(v0.x), b1 = h2_to_bf2(v0.y);
      kstep<0>(W, acc, b0, b1, w6, ws);
      const uint32_t b2 = h2_to_bf2(v0.z), b3 = h2_to_bf2(v1.x);
      sts128(mq, b0, b1, b2, b3);
      sts128(mq + 512, h2_to_bf2(v1.y), h2_to_bf2(v1.z), h2_to_bf2(__byte_perm(v0.w, v1.w, 0x5410)), h2_to_bf2(__byte_perm(v2.w, v3.w, 0x5410)));
      sts128(mq + 1024, h2_to_bf2(v2.x), h2_to_bf2(v2.y), h2_to_bf2(v2.z), h2_to_bf2(v3.x));
      sts64(mq + 1536, h2_to_bf2(v3.y), h2_to_bf2(v3.z));
      BAR_ARRIVE(0, 256);
      uint4 p1 = lds128(mq + 512);
      kstep<1>(W, acc, b2, b3, w6, ws);
      kstep<2>(W, acc, p1.x, p1.y, w6, ws);
      uint4 p2 = lds128(mq + 1024);
      kstep<3>(W, acc, p1.z, p1.w, w6, ws);
      kstep<4>(W, acc, p2.x, p2.y, w6, ws);
      uint2 p3 = lds64(mq + 1536);
      kstep<5>(W, acc, p2.z, p2.w, w6, ws);
      kstep<6>(W, acc, p3.x, p3.y, w6, ws);
      BAR_SYNC(1, 256);
      uint4 a0 = lds128(mj), a1 = lds128(mj + 512), a2 = lds128(mj + 1024); uint2 a3 = lds64(mj + 1536);
      STAMP(3);
      uint32_t kl[7], kh[7];
#pragma unroll
      for (int t = 0; t < 7; t++) { kl[t] = movm(pack_bf16(acc[t][0], acc[t][1])); kh[t] = movm(pack_bf16(acc[t][2], acc[t][3])); }
      float dl[4], dh[4], el[4], eh[4];
      mma_z(dl, a0.x, a0.y, a0.z, a0.w, kl[0], kl[1]); mma_z(dh, a0.x, a0.y, a0.z, a0.w, kh[0], kh[1]);
      mma_z(el, a1.x, a1.y, a1.z, a1.w, kl[2], kl[3]); mma_z(eh, a1.x, a1.y, a1.z, a1.w, kh[2], kh[3]);
      mma16816(dl, a2.x, a2.y, a2.z, a2.w, kl[4], kl[5]); mma16816(dh, a2.x, a2.y, a2.z, a2.w, kh[4], kh[5]);
      mma1688(el, a3.x, a3.y, kl[6]); mma1688(eh, a3.x, a3.y, kh[6]);
      sts64f(l8 + OFF(sred) + q * 256, (dl[0] + dh[2]) + (el[0] + eh[2]), (dl[1] + dh[3]) + (el[1] + eh[3]));
      BAR_SYNC(2, 128);
      {
        float2 t0 = lds64f(l8 + OFF(sred)), t1 = lds64f(l8 + OFF(sred) + 256), t2 = lds64f(l8 + OFF(sred) + 512), t3 = lds64f(l8 + OFF(sred) + 768);
        st_async2(dst_sm, (t0.x + t1.x) + (t2.x + t3.x), (t0.y + t1.y) + (t2.y + t3.y), dst_bar);
      }
      STAMP(4);
      {
        const __nv_bfloat162 iv = __float2bfloat162_rn(__uint_as_float(lds32(sb + OFF(sinv) + (s & 1) * 4)));
        auto us = [&](uint32_t v) { __nv_bfloat162 t = __hmul2(*reinterpret_cast<__nv_bfloat162*>(&v), iv); return *reinterpret_cast<uint32_t*>(&t); };
        uint2* kmf = g_KMF + ((((s * NH + h) * 4 + j) * 4 + q) * 7) * 32 + lane;
#pragma unroll
        for (int t = 0; t < 7; t++) kmf[t * 32] = make_uint2(us(kl[t]), us(kh[t]));
      }
      BAR_SYNC(4, 256);
      unsigned tred = clk();
      if (q == 0) { if (elect1()) { arm_bar(bar_sx, 4096); arm_bar(bar_sm, 1024); } __syncwarp(); }
      while (clk() - tred < (unsigned)poll_delay) {}
    }
  } else if (role == 1) {
    asm volatile("setmaxnreg.inc.sync.aligned.u32 208;");
    uint4 W[42];
    {
      const uint4* wf = g_WF + (((NH + h) * 28 + 7 * j) * 28 + 7 * q) * 32 + lane;
#pragma unroll
      for (int k = 0; k < 7; k++)
#pragma unroll
        for (int t = 0; t < 6; t++) W[k * 6 + t] = wf[(t * 28 + k) * 32];
    }
    const uint32_t ws = l16 + OFF(wS) + w * 7 * 512;
    const uint32_t mq = l16 + OFF(memF) + q * 2048, mj = l16 + OFF(memF) + j * 2048;
    const uint32_t uq = l16 + OFF(uQ) + q * 512;
    const uint32_t dsx = l16 + OFF(sx) + j * 1024 + (q >> 1) * 512 + (q & 1) * 8;
#pragma unroll 1
    for (int s = 0; s < NSEG; s++) {
      const int st = s & (NST - 1);
      wait_bar1(bar_ld + 8 * st, (s / NST) & 1);
      {
        const uint32_t kb = l16 + OFF(kf) + st * 8192 + q * 512;
        uint4 k0 = lds128(kb), k1 = lds128(kb + 2048), k2 = lds128(kb + 4096); uint2 k3 = lds64(kb + 6144);
        BAR_SYNC(0, 256);
        STAMP(2);
        uint4 a0 = lds128(mj), a1 = lds128(mj + 512);
        float dl[4], dh[4];
        mma_z(dl, a0.x, a0.y, a0.z, a0.w, k0.x, k0.y); mma_z(dh, a0.x, a0.y, a0.z, a0.w, k0.z, k0.w);
        uint4 a2 = lds128(mj + 1024); uint2 a3 = lds64(mj + 1536);
        mma16816(dl, a1.x, a1.y, a1.z, a1.w, k1.x, k1.y); mma16816(dh, a1.x, a1.y, a1.z, a1.w, k1.z, k1.w);
        mma16816(dl, a2.x, a2.y, a2.z, a2.w, k2.x, k2.y); mma16816(dh, a2.x, a2.y, a2.z, a2.w, k2.z, k2.w);
        mma1688(dl, a3.x, a3.y, k3.x); mma1688(dh, a3.x, a3.y, k3.y);
        float s0 = dl[0] + dh[2], s1 = dl[1] + dh[3];
#pragma unroll
        for (int r = 0; r < 4; r++) st_async2(mapa(dsx, r), s0, s1, mapa(bar_sx, r));
      }
      STAMP(9);
      uint4 w6 = lds128(ws);
      BAR_SYNC(1, 256);
      uint4 p0 = lds128(mq);
      STAMP(10);
      float acc[7][4];
      uint32_t m = 0;
      kstep<0>(W, acc, p0.x, p0.y, w6, ws);
      uint2 pn = lds64(mq + 512);
      m = amax2(amax2(m, p0.x, p0.y), p0.z, p0.w);
      kstep<1>(W, acc, p0.z, p0.w, w6, ws);
      uint2 pm_ = lds64(mq + 520);
      kstep<2>(W, acc, pn.x, pn.y, w6, ws); m = amax2(m, pn.x, pn.y);
      pn = lds64(mq + 1024);
      kstep<3>(W, acc, pm_.x, pm_.y, w6, ws); m = amax2(m, pm_.x, pm_.y);
      pm_ = lds64(mq + 1032);
      kstep<4>(W, acc, pn.x, pn.y, w6, ws); m = amax2(m, pn.x, pn.y);
      pn = lds64(mq + 1536);
      kstep<5>(W, acc, pm_.x, pm_.y, w6, ws); m = amax2(m, pm_.x, pm_.y);
      m = amax2(m, pn.x, pn.y);
      m = max(m & 0xffffu, m >> 16);
      m = __reduce_max_sync(0xffffffffu, m);
      sts32(sb + OFF(smax) + q * 4, m);
      kstep<6>(W, acc, pn.x, pn.y, w6, ws);
#define UP(nt) pack_bf16(acc[(nt) >> 1][((nt) & 1) * 2], acc[(nt) >> 1][((nt) & 1) * 2 + 1])
      { uint32_t u6 = UP(6), u7 = UP(7);
        sts128(uq, UP(0), UP(1), UP(2), u6); sts128(uq + 2048, UP(3), UP(4), UP(5), u6);
        sts128(uq + 4096, UP(8), UP(9), UP(10), u7); sts128(uq + 6144, UP(11), UP(12), UP(13), u7); }
      BAR_ARRIVE(3, 256);
      STAMP(11);
      if (q == 0 && s + NST - 1 < NSEG) {
        if (elect1()) {
          int s2 = s + NST - 1, st2 = s2 & (NST - 1);
          arm_bar(bar_ld + 8 * st2, 15360);
          bulk_g2s(sb + OFF(kf) + st2 * 8192, g_KF + ((s2 * NH + h) * 4 + j) * 512, 8192, bar_ld + 8 * st2);
          bulk_g2s(sb + OFF(vf) + st2 * 7168, g_VF + ((s2 * NH + h) * 56 + 14 * j) * 32, 7168, bar_ld + 8 * st2);
        }
        __syncwarp();
      }
    }
  } else {
    asm volatile("setmaxnreg.dec.sync.aligned.u32 72;");
    const int nt0 = q < 2 ? q * 3 : 8 + (q - 2) * 3, nts = 6 + (q >> 1);
    const float bmax = g_bmax;
    float inv = g_inv0;
    uint32_t sc_bf; { uint32_t t = (0x7f000000u - __float_as_uint(inv)) >> 16; sc_bf = t | (t << 16); }
#pragma unroll 1
    for (int s = 0; s < NSEG; s++) {
      const int st = s & (NST - 1);
      float ox[8];
      float mx;
      const float c1 = LOG2E * inv;
      {
        const uint32_t vb = l16 + OFF(vf) + st * 7168;
        wait_bar1(bar_ld + 8 * st, (s / NST) & 1);
        uint4 v0 = lds128(vb + nt0 * 512), v1 = lds128(vb + nt0 * 512 + 512), v2 = lds128(vb + nt0 * 512 + 1024), v3 = lds128(vb + nts * 512);
        wait_bar1(bar_sx, s & 1);
        float sx[8];
        {
          const uint32_t sxa = l16 + OFF(sx);
          float4 x0 = lds128f(sxa), x1 = lds128f(sxa + 1024), x2 = lds128f(sxa + 2048), x3 = lds128f(sxa + 3072);
          float4 y0 = lds128f(sxa + 512), y1 = lds128f(sxa + 1536), y2 = lds128f(sxa + 2560), y3 = lds128f(sxa + 3584);
          sx[0] = (x0.x + x1.x) + (x2.x + x3.x); sx[1] = (x0.y + x1.y) + (x2.y + x3.y); sx[2] = (x0.z + x1.z) + (x2.z + x3.z); sx[3] = (x0.w + x1.w) + (x2.w + x3.w);
          sx[4] = (y0.x + y1.x) + (y2.x + y3.x); sx[5] = (y0.y + y1.y) + (y2.y + y3.y); sx[6] = (y0.z + y1.z) + (y2.z + y3.z); sx[7] = (y0.w + y1.w) + (y2.w + y3.w);
        }
        mx = fmaxf(fmaxf(fmaxf(sx[0], sx[1]), fmaxf(sx[2], sx[3])), fmaxf(fmaxf(sx[4], sx[5]), fmaxf(sx[6], sx[7])));
        mx = fmaxf(mx, __shfl_xor_sync(0xffffffffu, mx, 1)); mx = fmaxf(mx, __shfl_xor_sync(0xffffffffu, mx, 2));
        mx *= c1;
#pragma unroll
        for (int i = 0; i < 8; i++) sx[i] = ex2(fmaf(sx[i], c1, -mx));
        uint32_t p0 = pack_bf16(sx[0], sx[1]), p1 = pack_bf16(sx[2], sx[3]), p2 = pack_bf16(sx[4], sx[5]), p3 = pack_bf16(sx[6], sx[7]);
        float o[4], r[4];
        mma_z(o, p0, p2, p1, p3, v0.x, v0.y); mma_z(r, p0, p2, p1, p3, v0.z, v0.w); ox[0] = o[0] + r[2]; ox[1] = o[1] + r[3];
        mma_z(o, p0, p2, p1, p3, v1.x, v1.y); mma_z(r, p0, p2, p1, p3, v1.z, v1.w); ox[2] = o[0] + r[2]; ox[3] = o[1] + r[3];
        mma_z(o, p0, p2, p1, p3, v2.x, v2.y); mma_z(r, p0, p2, p1, p3, v2.z, v2.w); ox[4] = o[0] + r[2]; ox[5] = o[1] + r[3];
        mma_z(o, p0, p2, p1, p3, v3.x, v3.y); mma_z(r, p0, p2, p1, p3, v3.z, v3.w); ox[6] = (q & 1) ? o[1] + r[3] : o[0] + r[2];
        mma_z(o, p0, p2, p1, p3, 0x3f803f80u, 0x3f803f80u); ox[7] = o[0] + o[2];
      }
      uint4* redp = acc_ptr(s + 1, j * 4 + q, lane);
      STAMP(5);
      if (ox[0] + ox[2] + ox[4] + ox[6] + ox[7] == 1.2345e-30f) sts32(sb + OFF(sinv) + 8, 0);
      BAR_SYNC(3, 256);
      const uint32_t ub = l16 + OFF(uQ) + q * 2048;
      uint4 u0 = lds128(ub), u1 = lds128(ub + 512), u2 = lds128(ub + 1024), u3 = lds128(ub + 1536);
      float nsc, ninv;
      {
        uint4 m4 = lds128(sb + OFF(smax));
        uint32_t mb = max(max(m4.x, m4.y), max(m4.z, m4.w));
        float mh = fmaxf(__uint_as_float(mb << 16) * inv, __uint_as_float(lds32(sb + OFF(xmax) + s * 4)));
        float bound = mh * bmax;
        int e = (int)(__float_as_uint(bound) >> 23) - 127 + 10;
        int se = min(max(15 - e, -100), 100);
        nsc = __uint_as_float((uint32_t)(127 + se) << 23); ninv = __uint_as_float((uint32_t)(127 - se) << 23);
      }
      STAMP(6);
      wait_bar1(bar_sm, s & 1);
      STAMP(7);
      {
        float2 t0 = lds64f(l8 + OFF(sm)), t1 = lds64f(l8 + OFF(sm) + 256), t2 = lds64f(l8 + OFF(sm) + 512), t3 = lds64f(l8 + OFF(sm) + 768);
        float s0 = ((t0.x + t1.x) + (t2.x + t3.x)) * inv * c1, s1 = ((t0.y + t1.y) + (t2.y + t3.y)) * inv * c1;
        float m = fmaxf(fmaxf(s0, s1), mx);
        m = fmaxf(m, __shfl_xor_sync(0xffffffffu, m, 1)); m = fmaxf(m, __shfl_xor_sync(0xffffffffu, m, 2));
        float e0 = ex2(s0 - m), e1 = ex2(s1 - m), al = ex2(mx - m);
        uint32_t pm = pack_bf16(e0 * inv, e1 * inv);
        float z[4], ya[4], yb[4], yc[4], yd[4];
        mma_z(z, pm, 0u, 0u, pm, sc_bf, sc_bf);
        mma_z(ya, pm, 0u, 0u, pm, u0.x, u0.y); mma_z(yb, pm, 0u, 0u, pm, u0.z, u0.w);
        mma_z(yc, pm, 0u, 0u, pm, u1.x, u1.y); mma_z(yd, pm, 0u, 0u, pm, u1.z, u1.w);
        mma16816(ya, pm, 0u, 0u, pm, u2.x, u2.y); mma16816(yb, pm, 0u, 0u, pm, u2.z, u2.w);
        mma16816(yc, pm, 0u, 0u, pm, u3.x, u3.y); mma16816(yd, pm, 0u, 0u, pm, u3.z, u3.w);
        float iz; asm("rcp.approx.ftz.f32 %0, %1;" : "=f"(iz) : "f"(fmaf(ox[7], al, z[0])));
        iz *= nsc;
#pragma unroll
        for (int i = 0; i < 7; i++) ox[i] *= al;
        const float y6 = (q & 1) ? yb[3] + yd[3] : yb[2] + yd[2];
        red_h8(redp, pack_f16(((ya[0] + ox[0]) + yc[0]) * iz, ((ya[1] + ox[1]) + yc[1]) * iz), pack_f16(((ya[2] + ox[2]) + yc[2]) * iz, ((ya[3] + ox[3]) + yc[3]) * iz),
               pack_f16(((yb[0] + ox[4]) + yd[0]) * iz, ((yb[1] + ox[5]) + yd[1]) * iz), pack_f16((y6 + ox[6]) * iz, 1.f));
      }
      if (q == 0) sts32(sb + OFF(sinv) + ((s + 1) & 1) * 4, __float_as_uint(ninv));
      BAR_ARRIVE(4, 256);
      STAMP(8);
      {
        auto us = [&](uint32_t a, uint32_t b, uint32_t c, uint32_t d) { return pack_bf16(((bf_lo(a) + bf_lo(b)) + (bf_lo(c) + bf_lo(d))) * inv, ((bf_hi(a) + bf_hi(b)) + (bf_hi(c) + bf_hi(d))) * inv); };
        uint32_t* uf = g_UF + ((s * NH + h) * 56 + 14 * j) * 32 + lane;
        uf[(nt0 + 0) * 32] = us(u0.x, u1.x, u2.x, u3.x); uf[(nt0 + 1) * 32] = us(u0.y, u1.y, u2.y, u3.y); uf[(nt0 + 2) * 32] = us(u0.z, u1.z, u2.z, u3.z);
        if ((q & 1) == 0) uf[nts * 32] = us(u0.w, u1.w, u2.w, u3.w);
      }
      inv = ninv; { uint32_t t = __float_as_uint(nsc) >> 16; sc_bf = t | (t << 16); }
    }
  }
  asm volatile("barrier.cluster.arrive.release.aligned;\nbarrier.cluster.wait.acquire.aligned;" ::: "memory");
}

__global__ void n_seed(const bf16* mem0) {
  __shared__ unsigned smx;
  if (threadIdx.x == 0) smx = 0;
  __syncthreads();
  float m = 0.f;
  for (int i = threadIdx.x; i < 8 * DM; i += 512) m = fmaxf(m, fabsf(b2f(mem0[i])));
  atomicMax(&smx, __float_as_uint(m));
  __syncthreads();
  int e = (int)(smx >> 23) - 127 + 1;
  int se = min(max(15 - e, -100), 100);
  float sc = __uint_as_float((uint32_t)(127 + se) << 23);
  if (threadIdx.x == 0) g_inv0 = __uint_as_float((uint32_t)(127 - se) << 23);
  int vec = threadIdx.x >> 5, lane = threadIdx.x & 31, j = vec >> 2, q = vec & 3;
  int nt0 = q < 2 ? q * 3 : 8 + (q - 2) * 3, nts = 6 + (q >> 1);
  const bf16* r = mem0 + (lane >> 2) * DM + j * 112 + (lane & 3) * 2;
  auto val = [&](int nt, int e2) { return b2f(r[nt * 8 + e2]) * sc; };
  *acc_ptr(0, vec, lane) = make_uint4(pack_f16(val(nt0, 0), val(nt0, 1)), pack_f16(val(nt0 + 1, 0), val(nt0 + 1, 1)), pack_f16(val(nt0 + 2, 0), val(nt0 + 2, 1)), pack_f16(val(nts, q & 1), 16.f));
}

__global__ void n_stats(const bf16* x) {
  if (blockIdx.x < 64) {
    float m = 0.f;
    for (int i = threadIdx.x; i < 32 * DM; i += 256) m = fmaxf(m, fabsf(b2f(x[blockIdx.x * 32 * DM + i])));
    atomicMax((unsigned*)&g_xmax[blockIdx.x], __float_as_uint(m));
  } else {
    int r = (blockIdx.x - 64) * 256 + threadIdx.x;
    if (r < NH * DM) { float a = 0.f; for (int k = 0; k < DM; k++) { float v = wf_elem(1, r / DM, r % DM, k); a += v * v; } atomicMax((unsigned*)&g_bmax, __float_as_uint(sqrtf(a))); }
  }
}

int g_poll_delay = POLL_DELAY;
extern "C" void kernel_launch(void* const* d_in, const int* in_sizes, int n_in, void* d_out, int out_size) {
  const bf16* x = (const bf16*)d_in[0];
  const bf16* wqkv = (const bf16*)d_in[1];
  const bf16* wphi = (const bf16*)d_in[2];
  const bf16* wo_a = (const bf16*)d_in[3];
  const bf16* mem0 = (const bf16*)d_in[5];
  const bf16* Wq = (const bf16*)d_in[6];
  const bf16* Wk = (const bf16*)d_in[7];
  const bf16* Wv = (const bf16*)d_in[8];
  const bf16* Wo = (const bf16*)d_in[9];
  const bf16* gate_w = (const bf16*)d_in[11];
  bf16* out = (bf16*)d_out;
  cudaFuncSetAttribute(r_kernel, cudaFuncAttributeMaxDynamicSharedMemorySize, (int)sizeof(RSmem));
  n_zero<<<(NSEG * 40 * 32 + 255) / 256, 256>>>();
  n_prep<<<(2 * NH * 28 * 28 * 32 + 255) / 256, 256>>>(Wq, Wk, Wv, Wo);
  n_stats<<<64 + 28, 256>>>(x);
  n_seed<<<1, 512>>>(mem0);
  n_xgemm<<<2 * NH * 28 * NSEG * 32 / 256, 256>>>(x);
  r_kernel<<<64, 384, sizeof(RSmem)>>>(mem0, g_poll_delay);
  n_qkv<<<(S_LEN * 1344 + 255) / 256, 256>>>(x, wqkv);
  n_phi<<<(S_LEN * 2 * NH + 255) / 256, 256>>>(wphi);
  n_kv<<<(32 * NH * 56 * 29 + 255) / 256, 256>>>();
  n_oa<<<(S_LEN * DM + 255) / 256, 256>>>();
  n_x3<<<NSEG, 512>>>(x, wo_a, gate_w, out);
}
```

```cpp
#include <cuda_runtime.h>
#include <cuda_bf16.h>
#include <stdint.h>
#include <stddef.h>

typedef __nv_bfloat16 bf16;
#define S_LEN 2048
#define DM 448
#define NH 16
#define NSEG 64
#define SPIN_LIMIT (1 << 22)

__device__ uint4 g_WF[2 * NH * 28 * 28 * 32];
__device__ uint4 g_KF[NSEG * NH * 4 * 4 * 4 * 32];
__device__ uint4 g_VF[NSEG * NH * 56 * 32];
__device__ float4 g_SXM[NSEG * NH * 4 * 2 * 32];
__device__ uint4 g_XF[NSEG * 4 * 14 * 32];
__device__ uint32_t g_UF[NSEG * NH * 56 * 32];
__device__ uint4 g_ACC16[(NSEG + 2) * 16 * 32];
__device__ float g_xmax[NSEG];
__device__ float g_bmax;
__device__ float g_inv0;
__device__ float g_qkv[S_LEN * 1344];
__device__ float g_phiq[S_LEN * NH * 56];
__device__ float g_phik[S_LEN * NH * 56];
__device__ float g_kv[NH * 56 * 29];
__device__ float g_oa[S_LEN * DM];
__device__ int g_err;
__device__ unsigned g_ts[64 * 64 * 16];

__device__ __forceinline__ uint32_t pack_bf16(float lo, float hi) {
  uint32_t r; asm("cvt.rn.bf16x2.f32 %0, %1, %2;" : "=r"(r) : "f"(hi), "f"(lo)); return r;
}
__device__ __forceinline__ float bf_lo(uint32_t v) { return __uint_as_float(v << 16); }
__device__ __forceinline__ float bf_hi(uint32_t v) { return __uint_as_float(v & 0xffff0000u); }
__device__ __forceinline__ float b2f(bf16 v) { return __bfloat162float(v); }

__global__ void n_prep(const bf16* Wq, const bf16* Wk, const bf16* Wv, const bf16* Wo) {
  int idx = blockIdx.x * blockDim.x + threadIdx.x;
  if (idx >= 2 * NH * 28 * 28 * 32) return;
  int lane = idx & 31, r = idx >> 5;
  int ks = r % 28; r /= 28; int tile = r % 28; r /= 28; int h = r % NH; int mat = r / NH;
  int g = lane >> 2, tq = lane & 3;
  float v[8];
  for (int i = 0; i < 8; i++) {
    int row = tile * 16 + g + ((i >> 1) & 1) * 8;
    int col = ks * 16 + tq * 2 + (i & 1) + (i >> 2) * 8;
    float acc = 0.f;
    if (mat == 0) { for (int e = 0; e < 256; e++) acc += b2f(Wq[(row * NH + h) * 256 + e]) * b2f(Wk[(col * NH + h) * 256 + e]); acc *= 0.0625f; }
    else { for (int e = 0; e < 256; e++) acc += b2f(Wo[(h * 256 + e) * DM + row]) * b2f(Wv[(col * NH + h) * 256 + e]); }
    v[i] = acc;
  }
  g_WF[idx] = make_uint4(pack_bf16(v[0], v[1]), pack_bf16(v[2], v[3]), pack_bf16(v[4], v[5]), pack_bf16(v[6], v[7]));
}
__device__ __forceinline__ float wf_elem(int mat, int h, int row, int col) {
  int tile = row >> 4, ks = col >> 4, rr = row & 15, cc = col & 15;
  int lane = (rr & 7) * 4 + ((cc & 7) >> 1);
  int reg = (rr >> 3) + (cc >> 3) * 2;
  uint32_t w = ((const uint32_t*)g_WF)[((((mat * NH + h) * 28 + tile) * 28 + ks) * 32 + lane) * 4 + reg];
  return (cc & 1) ? bf_hi(w) : bf_lo(w);
}
__device__ __forceinline__ void mma16816(float* d, uint32_t a0, uint32_t a1, uint32_t a2, uint32_t a3, uint32_t b0, uint32_t b1) {
  asm volatile("mma.sync.aligned.m16n8k16.row.col.f32.bf16.bf16.f32 {%0,%1,%2,%3}, {%4,%5,%6,%7}, {%8,%9}, {%0,%1,%2,%3};"
    : "+f"(d[0]), "+f"(d[1]), "+f"(d[2]), "+f"(d[3]) : "r"(a0), "r"(a1), "r"(a2), "r"(a3), "r"(b0), "r"(b1));
}
__device__ __forceinline__ void mma1688(float* d, uint32_t a0, uint32_t a1, uint32_t b0) {
  asm volatile("mma.sync.aligned.m16n8k8.row.col.f32.bf16.bf16.f32 {%0,%1,%2,%3}, {%4,%5}, {%6}, {%0,%1,%2,%3};"
    : "+f"(d[0]), "+f"(d[1]), "+f"(d[2]), "+f"(d[3]) : "r"(a0), "r"(a1), "r"(b0));
}
__device__ __forceinline__ uint32_t movm(uint32_t a) { uint32_t d; asm volatile("movmatrix.sync.aligned.m8n8.trans.b16 %0, %1;" : "=r"(d) : "r"(a)); return d; }

__global__ void n_xgemm(const bf16* x) {
  int wid = (blockIdx.x * blockDim.x + threadIdx.x) >> 5, lane = threadIdx.x & 31;
  int seg = wid % NSEG; int r = wid / NSEG;
  int tile = r % 28; r /= 28; int h = r % NH; int mat = r / NH;
  if (mat >= 2) return;
  int g = lane >> 2, tq = lane & 3;
  float d[4][4] = {};
  const uint4* wf = g_WF + (((mat * NH + h) * 28 + tile) * 28) * 32 + lane;
  for (int ks = 0; ks < 28; ks++) {
    uint4 a = wf[ks * 32];
    for (int kg = 0; kg < 4; kg++) {
      const uint32_t* xr = (const uint32_t*)(x + (seg * 32 + kg * 8 + g) * DM + ks * 16 + tq * 2);
      mma16816(d[kg], a.x, a.y, a.z, a.w, xr[0], xr[4]);
    }
  }
  if (mat == 0) {
    for (int kg = 0; kg < 4; kg++) {
      uint32_t b0 = movm(pack_bf16(d[kg][0], d[kg][1])), b1 = movm(pack_bf16(d[kg][2], d[kg][3]));
      int jj = tile / 7, i = tile % 7;
      uint32_t* dst = (uint32_t*)&g_KF[((((seg * NH + h) * 4 + kg) * 4 + jj) * 4 + (i >> 1)) * 32 + lane];
      if (i == 6) { dst[0] = b0; dst[1] = b1; } else { dst[i & 1] = b0; dst[2 + (i & 1)] = b1; }
    }
  } else {
    g_VF[((seg * NH + h) * 56 + tile * 2) * 32 + lane] = make_uint4(pack_bf16(d[0][0], d[0][1]), pack_bf16(d[1][0], d[1][1]), pack_bf16(d[2][0], d[2][1]), pack_bf16(d[3][0], d[3][1]));
    g_VF[((seg * NH + h) * 56 + tile * 2 + 1) * 32 + lane] = make_uint4(pack_bf16(d[0][2], d[0][3]), pack_bf16(d[1][2], d[1][3]), pack_bf16(d[2][2], d[2][3]), pack_bf16(d[3][2], d[3][3]));
  }
}
__global__ void n_zero() {
  int i = blockIdx.x * blockDim.x + threadIdx.x;
  if (i < (NSEG + 2) * 16 * 32) g_ACC16[i] = make_uint4(0, 0, 0, 0);
  if (i < NSEG) g_xmax[i] = 0.f;
  if (i == 0) g_bmax = 0.f;
  if (i < NH * 56 * 29) g_kv[i] = 0.f;
}
__global__ void n_qkv(const bf16* x, const bf16* w) {
  int i = blockIdx.x * blockDim.x + threadIdx.x;
  if (i >= S_LEN * 1344) return;
  int n = i % 1344, t = i / 1344;
  float acc = 0.f;
  for (int k = 0; k < DM; k++) acc += b2f(x[t * DM + k]) * b2f(w[k * 1344 + n]);
  g_qkv[i] = acc;
}
__global__ void n_phi(const bf16* wphi) {
  int i = blockIdx.x * blockDim.x + threadIdx.x;
  if (i >= S_LEN * 2 * NH) return;
  int h = i % NH, which = (i / NH) % 2, t = i / (2 * NH);
  float p[28]; float mx = -1e30f, mn = 1e30f;
  for (int f = 0; f < 28; f++) {
    float acc = 0.f;
    for (int d = 0; d < 28; d++) acc += g_qkv[t * 1344 + which * 448 + h * 28 + d] * b2f(wphi[(h * 28 + d) * 28 + f]);
    p[f] = acc; mx = fmaxf(mx, acc); mn = fminf(mn, acc);
  }
  float s1 = 0.f, s2 = 0.f;
  for (int f = 0; f < 28; f++) { s1 += __expf(p[f] - mx); s2 += __expf(mn - p[f]); }
  float* o = (which ? g_phik : g_phiq) + (t * NH + h) * 56;
  for (int f = 0; f < 28; f++) { o[f] = __expf(p[f] - mx) / s1; o[28 + f] = __expf(mn - p[f]) / s2; }
}
__global__ void n_kv() {
  int i = blockIdx.x * blockDim.x + threadIdx.x;
  if (i >= 32 * NH * 56 * 29) return;
  int d = i % 29, f = (i / 29) % 56, h = (i / (29 * 56)) % NH, ch = i / (29 * 56 * NH);
  float acc = 0.f;
  for (int t = ch * 64; t < ch * 64 + 64; t++) acc += g_phik[(t * NH + h) * 56 + f] * (d < 28 ? g_qkv[t * 1344 + 896 + h * 28 + d] : 1.f);
  atomicAdd(&g_kv[(h * 56 + f) * 29 + d], acc);
}
__global__ void n_oa() {
  int i = blockIdx.x * blockDim.x + threadIdx.x;
  if (i >= S_LEN * DM) return;
  int c = i % DM, t = i / DM, h = c / 28, d = c % 28;
  float num = 0.f, den = 0.f;
  for (int f = 0; f < 56; f++) { float p = g_phiq[(t * NH + h) * 56 + f]; num += p * g_kv[(h * 56 + f) * 29 + d]; den += p * g_kv[(h * 56 + f) * 29 + 28]; }
  g_oa[i] = num / (den + 1e-6f);
}

__global__ void __launch_bounds__(512) n_x3(const bf16* x, const bf16* wo, const bf16* gate_w, bf16* out) {
  __shared__ uint32_t sP[NH][2][32][10];
  __shared__ float sG[32];
  int seg = blockIdx.x, w = threadIdx.x >> 5, lane = threadIdx.x & 31, g = lane >> 2, tq = lane & 3;
  for (int r = w; r < 32; r += 16) {
    float acc = 0.f;
    for (int k = lane; k < DM; k += 32) acc += b2f(x[(seg * 32 + r) * DM + k]) * b2f(gate_w[k]);
    for (int o = 16; o; o >>= 1) acc += __shfl_xor_sync(0xffffffffu, acc, o);
    if (lane == 0) sG[r] = 1.f / (1.f + __expf(-acc));
  }
  {
    int h = w;
    float s[2][5][4] = {};
    for (int ct = 0; ct < 28; ct++) {
      uint32_t a[2][4];
      for (int m = 0; m < 2; m++) {
        const uint32_t* r0 = (const uint32_t*)(x + (seg * 32 + m * 16 + g) * DM + ct * 16 + tq * 2);
        const uint32_t* r1 = (const uint32_t*)(x + (seg * 32 + m * 16 + g + 8) * DM + ct * 16 + tq * 2);
        a[m][0] = r0[0]; a[m][1] = r1[0]; a[m][2] = r0[4]; a[m][3] = r1[4];
      }
      int j = ct / 7, i = ct % 7;
      for (int kg = 0; kg < 4; kg++) {
        const uint32_t* src = (const uint32_t*)&g_KF[((((seg * NH + h) * 4 + kg) * 4 + j) * 4 + (i >> 1)) * 32 + lane];
        uint2 b = i == 6 ? make_uint2(src[0], src[1]) : make_uint2(src[i & 1], src[2 + (i & 1)]);
        for (int m = 0; m < 2; m++) mma16816(s[m][1 + kg], a[m][0], a[m][1], a[m][2], a[m][3], b.x, b.y);
      }
    }
    for (int m = 0; m < 2; m++) for (int j = 0; j < 4; j++) {
      float4 t = g_SXM[(((seg * NH + h) * 4 + j) * 2 + m) * 32 + lane];
      s[m][0][0] += t.x; s[m][0][1] += t.y; s[m][0][2] += t.z; s[m][0][3] += t.w;
    }
    for (int m = 0; m < 2; m++) for (int hf = 0; hf < 2; hf++) {
      int t = m * 16 + hf * 8 + g;
      float v[10]; float mx = -1e30f;
      for (int n = 0; n < 5; n++) for (int e = 0; e < 2; e++) {
        float val = s[m][n][hf * 2 + e];
        if (n > 0 && (n - 1) * 8 + tq * 2 + e > t) val = -1e30f;
        v[n * 2 + e] = val; mx = fmaxf(mx, val);
      }
      mx = fmaxf(mx, __shfl_xor_sync(0xffffffffu, mx, 1)); mx = fmaxf(mx, __shfl_xor_sync(0xffffffffu, mx, 2));
      float z = 0.f;
      for (int i = 0; i < 10; i++) { v[i] = __expf(v[i] - mx); z += v[i]; }
      z += __shfl_xor_sync(0xffffffffu, z, 1); z += __shfl_xor_sync(0xffffffffu, z, 2);
      float iz = 1.f / z;
      sP[h][m][lane][hf] = pack_bf16(v[0] * iz, v[1] * iz);
      sP[h][m][lane][2 + hf] = pack_bf16(v[2] * iz, v[3] * iz);
      sP[h][m][lane][4 + hf] = pack_bf16(v[4] * iz, v[5] * iz);
      sP[h][m][lane][6 + hf] = pack_bf16(v[6] * iz, v[7] * iz);
      sP[h][m][lane][8 + hf] = pack_bf16(v[8] * iz, v[9] * iz);
    }
  }
  __syncthreads();
  if (w < 14) {
    float o[2][4][4] = {};
    for (int h = 0; h < NH; h++) {
      for (int n = 0; n < 4; n++) {
        int nt = w * 4 + n;
        uint4 v = g_VF[((seg * NH + h) * 56 + nt) * 32 + lane];
        uint32_t u = g_UF[((seg * NH + h) * 56 + nt) * 32 + lane];
        for (int m = 0; m < 2; m++) {
          const uint32_t* p = sP[h][m][lane];
          mma1688(o[m][n], p[0], p[1], u);
          mma16816(o[m][n], p[2], p[3], p[4], p[5], v.x, v.y);
          mma16816(o[m][n], p[6], p[7], p[8], p[9], v.z, v.w);
        }
      }
    }
    for (int m = 0; m < 2; m++) for (int n = 0; n < 4; n++) for (int i = 0; i < 4; i++) {
      int r = m * 16 + (i >> 1) * 8 + g, c = (w * 4 + n) * 8 + tq * 2 + (i & 1);
      int t = seg * 32 + r;
      float a = 0.f;
      for (int k = 0; k < DM; k++) a += g_oa[t * DM + k] * b2f(wo[k * DM + c]);
      float gt = sG[r];
      out[t * DM + c] = __float2bfloat16(gt * a + (1.f - gt) * o[m][n][i]);
    }
  }
}

__device__ __forceinline__ uint32_t smem_u32(const void* p) { return (uint32_t)__cvta_generic_to_shared(p); }
__device__ __forceinline__ uint32_t mapa(uint32_t a, uint32_t r) { uint32_t o; asm volatile("mapa.shared::cluster.u32 %0, %1, %2;" : "=r"(o) : "r"(a), "r"(r)); return o; }
__device__ __forceinline__ bool try_wait(uint32_t bar, uint32_t parity) {
  uint32_t ok; asm volatile("{\n.reg .pred p;\nmbarrier.try_wait.parity.shared::cta.b64 p, [%1], %2;\nselp.u32 %0, 1, 0, p;\n}" : "=r"(ok) : "r"(bar), "r"(parity) : "memory"); return ok; }
__device__ __forceinline__ void wait_bar(uint32_t bar, uint32_t parity) {
  int n = 0; while (!try_wait(bar, parity)) { if (++n > SPIN_LIMIT) { g_err = 1; break; } } }
__device__ __forceinline__ void arm_bar(uint32_t bar, uint32_t bytes) { asm volatile("mbarrier.arrive.expect_tx.shared::cta.b64 _, [%0], %1;" :: "r"(bar), "r"(bytes) : "memory"); }
__device__ __forceinline__ float4 ld_relaxed4(const void* p) { float4 v; asm volatile("ld.relaxed.gpu.global.v4.f32 {%0,%1,%2,%3}, [%4];" : "=f"(v.x), "=f"(v.y), "=f"(v.z), "=f"(v.w) : "l"(p) : "memory"); return v; }
__device__ __forceinline__ void red4(void* p, float a, float b, float c, float d) { asm volatile("red.relaxed.gpu.global.add.v4.f32 [%0], {%1,%2,%3,%4};" :: "l"(p), "f"(a), "f"(b), "f"(c), "f"(d) : "memory"); }
__device__ __forceinline__ void st_async2(uint32_t dst, float a, float b, uint32_t bar) { asm volatile("st.async.shared::cluster.mbarrier::complete_tx::bytes.v2.f32 [%0], {%1,%2}, [%3];" :: "r"(dst), "f"(a), "f"(b), "r"(bar) : "memory"); }
__device__ __forceinline__ void bulk_g2s(uint32_t dst, const void* src, uint32_t bytes, uint32_t bar) {
  asm volatile("cp.async.bulk.shared::cluster.global.mbarrier::complete_tx::bytes [%0], [%1], %2, [%3];" :: "r"(dst), "l"(src), "r"(bytes), "r"(bar) : "memory"); }
__device__ __forceinline__ unsigned clk() { unsigned c; asm volatile("mov.u32 %0, %%clock;" : "=r"(c) :: "memory"); return c; }
__device__ __forceinline__ float ex2(float x) { float y; asm("ex2.approx.ftz.f32 %0, %1;" : "=f"(y) : "f"(x)); return y; }

#define NST 4
struct QBlk {
  uint4 memF[4][32];
  uint4 wA[7][32], wB[7][32];
  uint4 kf[NST][4][32];
  float4 xred[2][32];
  float4 red[32];
  uint4 uQ[4][32];
};
#define QB ((uint32_t)sizeof(QBlk))
#define QOFF(f) ((uint32_t)offsetof(QBlk, f))
struct RSmem {
  QBlk qb[4];
  uint4 vf[NST][14][32];
  uint4 xf[NST][14][32];
  float4 sx[2][32];
  float4 sm[2][32];
  uint32_t smax[4];
  float xmax[NSEG];
  float sinv[4];
  unsigned long long bar_ld[NST], bar_sx, bar_sm;
  unsigned ts[64 * 16];
};
#define LD_BYTES (8192 + 7168 + 7168)
#define POLL_DELAY 300
#define STAMP(i)
__device__ __forceinline__ void wait_slow(uint32_t bar, uint32_t parity) {
#pragma unroll 1
  for (int n = 0; n < SPIN_LIMIT; n++) if (try_wait(bar, parity)) return;
  g_err = 1;
}
__device__ __forceinline__ void wait_bar1(uint32_t bar, uint32_t parity) { if (!try_wait(bar, parity)) wait_slow(bar, parity); }
__device__ __forceinline__ uint4 ld_relaxed_u4(const void* p) { uint4 v; asm volatile("ld.relaxed.gpu.global.v4.u32 {%0,%1,%2,%3}, [%4];" : "=r"(v.x), "=r"(v.y), "=r"(v.z), "=r"(v.w) : "l"(p) : "memory"); return v; }
__device__ __forceinline__ void red_h8(void* p, uint32_t a, uint32_t b, uint32_t c, uint32_t d) { asm volatile("red.relaxed.gpu.global.add.noftz.v4.f16x2 [%0], {%1,%2,%3,%4};" :: "l"(p), "r"(a), "r"(b), "r"(c), "r"(d) : "memory"); }
__device__ __forceinline__ uint32_t pack_f16(float lo, float hi) { uint32_t r; asm("cvt.rn.f16x2.f32 %0, %1, %2;" : "=r"(r) : "f"(hi), "f"(lo)); return r; }
__device__ __forceinline__ uint32_t h2_to_bf2(uint32_t v) {
  float lo, hi; asm("{.reg .f16 l, h; mov.b32 {l, h}, %2; cvt.f32.f16 %0, l; cvt.f32.f16 %1, h;}" : "=f"(lo), "=f"(hi) : "r"(v)); return pack_bf16(lo, hi); }
__device__ __forceinline__ uint2 lds64(uint32_t a) { uint2 v; asm volatile("ld.shared.v2.u32 {%0,%1}, [%2];" : "=r"(v.x), "=r"(v.y) : "r"(a) : "memory"); return v; }
__device__ __forceinline__ float2 lds64f(uint32_t a) { float2 v; asm volatile("ld.shared.v2.f32 {%0,%1}, [%2];" : "=f"(v.x), "=f"(v.y) : "r"(a) : "memory"); return v; }
__device__ __forceinline__ uint4 lds128(uint32_t a) { uint4 v; asm volatile("ld.shared.v4.u32 {%0,%1,%2,%3}, [%4];" : "=r"(v.x), "=r"(v.y), "=r"(v.z), "=r"(v.w) : "r"(a) : "memory"); return v; }
__device__ __forceinline__ uint32_t lds32(uint32_t a) { uint32_t v; asm volatile("ld.shared.u32 %0, [%1];" : "=r"(v) : "r"(a) : "memory"); return v; }
__device__ __forceinline__ void sts64(uint32_t a, uint32_t x, uint32_t y) { asm volatile("st.shared.v2.u32 [%0], {%1,%2};" :: "r"(a), "r"(x), "r"(y) : "memory"); }
__device__ __forceinline__ void sts64f(uint32_t a, float x, float y) { asm volatile("st.shared.v2.f32 [%0], {%1,%2};" :: "r"(a), "f"(x), "f"(y) : "memory"); }
__device__ __forceinline__ void sts32(uint32_t a, uint32_t x) { asm volatile("st.shared.u32 [%0], %1;" :: "r"(a), "r"(x) : "memory"); }
__device__ __forceinline__ void mma_z(float* d, uint32_t a0, uint32_t a1, uint32_t a2, uint32_t a3, uint32_t b0, uint32_t b1) {
  asm volatile("mma.sync.aligned.m16n8k16.row.col.f32.bf16.bf16.f32 {%0,%1,%2,%3}, {%4,%5,%6,%7}, {%8,%9}, {%10,%10,%10,%10};"
    : "=f"(d[0]), "=f"(d[1]), "=f"(d[2]), "=f"(d[3]) : "r"(a0), "r"(a1), "r"(a2), "r"(a3), "r"(b0), "r"(b1), "f"(0.f));
}
__device__ __forceinline__ void mma8_z(float* d, uint32_t a0, uint32_t a1, uint32_t b0) {
  asm volatile("mma.sync.aligned.m16n8k8.row.col.f32.bf16.bf16.f32 {%0,%1,%2,%3}, {%4,%5}, {%6}, {%7,%7,%7,%7};"
    : "=f"(d[0]), "=f"(d[1]), "=f"(d[2]), "=f"(d[3]) : "r"(a0), "r"(a1), "r"(b0), "f"(0.f));
}
#define OFF(f) ((uint32_t)offsetof(RSmem, f))
#define BAR_SYNC(id, n) asm volatile("bar.sync %0, %1;" :: "n"(id), "n"(n) : "memory")
#define BAR_ARRIVE(id, n) asm volatile("bar.arrive %0, %1;" :: "n"(id), "n"(n) : "memory")

__device__ __forceinline__ void sts128(uint32_t a, uint32_t x, uint32_t y, uint32_t z, uint32_t w) { asm volatile("st.shared.v4.u32 [%0], {%1,%2,%3,%4};" :: "r"(a), "r"(x), "r"(y), "r"(z), "r"(w) : "memory"); }
template <int K>
__device__ __forceinline__ void kstep(const uint4 (&W)[42], float (&acc)[7][4], uint32_t b0, uint32_t b1, uint4& w6, uint32_t ws) {
#pragma unroll
  for (int t = 0; t < 6; t++) {
    const uint4& w = W[K * 6 + t];
    if (K == 0) mma_z(acc[t], w.x, w.y, w.z, w.w, b0, b1); else mma16816(acc[t], w.x, w.y, w.z, w.w, b0, b1);
  }
  if (K == 0) mma_z(acc[6], w6.x, w6.y, w6.z, w6.w, b0, b1); else mma16816(acc[6], w6.x, w6.y, w6.z, w6.w, b0, b1);
  if (K < 6) w6 = lds128(ws + (K + 1) * 512);
}
__device__ __forceinline__ uint4* acc_ptr(int step, int vec, int lane) { return g_ACC16 + (((step >> 1) * 16 + vec) * 2 + (step & 1)) * 32 + lane; }

__device__ __forceinline__ bool elect1() { uint32_t p; asm volatile("{.reg .pred p; elect.sync _|p, 0xffffffff; selp.u32 %0, 1, 0, p;}" : "=r"(p)); return p; }
__device__ __forceinline__ float4 lds128f(uint32_t a) { float4 v; asm volatile("ld.shared.v4.f32 {%0,%1,%2,%3}, [%4];" : "=f"(v.x), "=f"(v.y), "=f"(v.z), "=f"(v.w) : "r"(a) : "memory"); return v; }
__device__ __forceinline__ uint32_t amax2(uint32_t m, uint32_t x, uint32_t y) { return __vmaxu2(m, __vmaxu2(x & 0x7fff7fffu, y & 0x7fff7fffu)); }

#define FENCE(n) do { _Pragma("unroll 1") for (int i_ = (poll_delay >> (16 + (n))) & 3; i_ > 0; i_--) asm volatile("nanosleep.u32 %0;" :: "n"(n) : "memory"); } while (0)
#define BAR_SYNC_R(id, n) asm volatile("bar.sync %0, %1;" :: "r"(id), "n"(n) : "memory")
#define BAR_ARRIVE_R(id, n) asm volatile("bar.arrive %0, %1;" :: "r"(id), "n"(n) : "memory")
#define MMW(A, WW, B0, B1, first) do { if (first) mma_z(A, WW.x, WW.y, WW.z, WW.w, B0, B1); else mma16816(A, WW.x, WW.y, WW.z, WW.w, B0, B1); } while (0)
__device__ __forceinline__ void issue_loads(uint32_t sb, int s, int h, int j) {
  const int st = s & (NST - 1);
  const uint32_t bar = sb + OFF(bar_ld) + 8 * st;
  arm_bar(bar, LD_BYTES);
#pragma unroll
  for (int qq = 0; qq < 4; qq++) bulk_g2s(sb + qq * QB + QOFF(kf) + st * 2048, g_KF + ((s * NH + h) * 4 + j) * 512 + qq * 128, 2048, bar);
  bulk_g2s(sb + OFF(vf) + st * 7168, g_VF + ((s * NH + h) * 56 + 14 * j) * 32, 7168, bar);
  bulk_g2s(sb + OFF(xf) + st * 7168, g_XF + (s * 4 + j) * 448, 7168, bar);
  asm volatile("prefetch.global.L2 [%0];" :: "l"(acc_ptr(s, h, j * 8)));
}
__device__ __forceinline__ int opaque_lane() { return __shfl_sync(0xffffffffu, threadIdx.x & 31, threadIdx.x & 31); }

__global__ void __cluster_dims__(4, 1, 1) __launch_bounds__(384, 1) r_kernel(const bf16* mem0, int poll_delay) {
  extern __shared__ __align__(128) unsigned char smem_raw[];
  RSmem& sm = *reinterpret_cast<RSmem*>(smem_raw);
  const int h = blockIdx.x >> 2, j = blockIdx.x & 3;
  const int w = __shfl_sync(0xffffffffu, threadIdx.x >> 5, 0), q = w & 3, role = w >> 2;
  const uint32_t sb = smem_u32(smem_raw);
  const uint32_t bar_ld = sb + OFF(bar_ld), bar_sx = sb + OFF(bar_sx), bar_sm = sb + OFF(bar_sm);
  if (threadIdx.x == 0) {
    for (int i = 0; i < NST; i++) asm volatile("mbarrier.init.shared::cta.b64 [%0], 1;" :: "r"(bar_ld + 8 * i));
    asm volatile("mbarrier.init.shared::cta.b64 [%0], 1;" :: "r"(bar_sx));
    asm volatile("mbarrier.init.shared::cta.b64 [%0], 1;" :: "r"(bar_sm));
    asm volatile("fence.mbarrier_init.release.cluster;" ::: "memory");
    arm_bar(bar_sx, 1024); arm_bar(bar_sm, 1024);
    for (int s = 0; s < NST - 1; s++) issue_loads(sb, s, h, j);
    sm.sinv[0] = g_inv0;
  }
  if (threadIdx.x < NSEG) sm.xmax[threadIdx.x] = g_xmax[threadIdx.x];
  if (role < 2) {
    const int lane = threadIdx.x & 31;
    const uint4* wf = g_WF + (((role * NH + h) * 28 + 7 * j + 6) * 28 + 7 * q) * 32 + lane;
#pragma unroll
    for (int e = 0; e < 7; e++) (role ? sm.qb[q].wB : sm.qb[q].wA)[e][lane] = wf[e * 32];
  }
  asm volatile("barrier.cluster.arrive.release.aligned;\nbarrier.cluster.wait.acquire.aligned;" ::: "memory");
  const float LOG2E = 1.4426950408889634f;

  if (role == 0) {
    asm volatile("setmaxnreg.inc.sync.aligned.u32 224;");
    const int lane = opaque_lane();
    const uint32_t l16 = sb + lane * 16;
    uint4 W[42];
    {
      const uint4* wf = g_WF + ((h * 28 + 7 * j) * 28 + 7 * q) * 32 + lane;
#pragma unroll
      for (int k = 0; k < 7; k++)
#pragma unroll
        for (int t = 0; t < 6; t++) W[k * 6 + t] = wf[(t * 28 + k) * 32];
    }
    const uint32_t lq = l16 + q * QB, mj = l16 + j * QB;
#define ws (lq + QOFF(wA))
#define mq lq
    const uint32_t dst_sm = mapa(l16 + OFF(sm) + (j >> 1) * 512 + (j & 1) * 8, q), dst_bar = mapa(bar_sm, q);
    const uint4* p = acc_ptr(0, q * 4, lane);
#pragma unroll 1
    for (int s = 0; s < NSEG; s++) {
      STAMP(0);
      uint4 v0 = ld_relaxed_u4(p), v1 = ld_relaxed_u4(p + 64), v2 = ld_relaxed_u4(p + 128), v3 = ld_relaxed_u4(p + 192);
      if (!__all_sync(0xffffffffu, __byte_perm(v0.w, v1.w, 0x7632) == 0x4C004C00u && __byte_perm(v2.w, v3.w, 0x7632) == 0x4C004C00u)) {
#pragma unroll 1
        for (int n = 0; n < SPIN_LIMIT; n++) {
          v0 = ld_relaxed_u4(p); v1 = ld_relaxed_u4(p + 64); v2 = ld_relaxed_u4(p + 128); v3 = ld_relaxed_u4(p + 192);
          if (__all_sync(0xffffffffu, __byte_perm(v0.w, v1.w, 0x7632) == 0x4C004C00u && __byte_perm(v2.w, v3.w, 0x7632) == 0x4C004C00u)) break;
        }
      }
      STAMP(1);
      uint32_t b[14];
      b[0] = h2_to_bf2(v0.x); b[1] = h2_to_bf2(v0.y); b[2] = h2_to_bf2(v0.z); b[3] = h2_to_bf2(v1.x); b[4] = h2_to_bf2(v1.y); b[5] = h2_to_bf2(v1.z);
      b[6] = h2_to_bf2(__byte_perm(v0.w, v1.w, 0x5410)); b[7] = h2_to_bf2(__byte_perm(v2.w, v3.w, 0x5410));
      b[8] = h2_to_bf2(v2.x); b[9] = h2_to_bf2(v2.y); b[10] = h2_to_bf2(v2.z); b[11] = h2_to_bf2(v3.x); b[12] = h2_to_bf2(v3.y); b[13] = h2_to_bf2(v3.z);
      sts128(mq, b[0], b[1], b[2], b[3]); sts128(mq + 512, b[4], b[5], b[6], b[7]); sts128(mq + 1024, b[8], b[9], b[10], b[11]); sts64(mq + 1536, b[12], b[13]);
      BAR_ARRIVE_R(5 + q, 64);
      float acc[7][4];
      uint4 w6a = lds128(ws), w6b = lds128(ws + 512);
#pragma unroll
      for (int k = 0; k < 7; k++)
#pragma unroll
        for (int t = 0; t < 4; t++) MMW(acc[t], W[k * 6 + t], b[2 * k], b[2 * k + 1], k == 0);
      FENCE(2);
      BAR_SYNC(1, 128);
      uint4 a0 = lds128(mj), a1 = lds128(mj + 512);
      uint32_t kl[7], kh[7];
      float dl[4], dh[4], el[4], eh[4];
#define B2(k) do { MMW(acc[4], W[(k) * 6 + 4], b[2 * (k)], b[2 * (k) + 1], (k) == 0); MMW(acc[5], W[(k) * 6 + 5], b[2 * (k)], b[2 * (k) + 1], (k) == 0); \
        if ((k) & 1) { MMW(acc[6], w6b, b[2 * (k)], b[2 * (k) + 1], (k) == 0); if ((k) + 2 < 7) w6b = lds128(ws + ((k) + 2) * 512); } \
        else { MMW(acc[6], w6a, b[2 * (k)], b[2 * (k) + 1], (k) == 0); if ((k) + 2 < 7) w6a = lds128(ws + ((k) + 2) * 512); } } while (0)
      B2(0); B2(1);
#pragma unroll
      for (int t = 0; t < 4; t++) { kl[t] = movm(pack_bf16(acc[t][0], acc[t][1])); kh[t] = movm(pack_bf16(acc[t][2], acc[t][3])); }
      B2(2); B2(3); B2(4);
      FENCE(4);
      BAR_ARRIVE_R(10 + q, 64);
      uint4 a2 = lds128(mj + 1024); uint2 a3 = lds64(mj + 1536);
      mma_z(dl, a0.x, a0.y, a0.z, a0.w, kl[0], kl[1]); mma_z(dh, a0.x, a0.y, a0.z, a0.w, kh[0], kh[1]);
      B2(5);
      mma_z(el, a1.x, a1.y, a1.z, a1.w, kl[2], kl[3]); mma_z(eh, a1.x, a1.y, a1.z, a1.w, kh[2], kh[3]);
      B2(6);
      STAMP(3);
#pragma unroll
      for (int t = 4; t < 7; t++) { kl[t] = movm(pack_bf16(acc[t][0], acc[t][1])); kh[t] = movm(pack_bf16(acc[t][2], acc[t][3])); }
      mma16816(dl, a2.x, a2.y, a2.z, a2.w, kl[4], kl[5]); mma16816(dh, a2.x, a2.y, a2.z, a2.w, kh[4], kh[5]);
      mma1688(el, a3.x, a3.y, kl[6]); mma1688(eh, a3.x, a3.y, kh[6]);
      sts64f(lq + QOFF(red), (dl[0] + dh[2]) + (el[0] + eh[2]), (dl[1] + dh[3]) + (el[1] + eh[3]));
      BAR_SYNC(2, 128);
      {
        float2 t0 = lds64f(l16 + QOFF(red)), t1 = lds64f(l16 + QOFF(red) + QB), t2 = lds64f(l16 + QOFF(red) + 2 * QB), t3 = lds64f(l16 + QOFF(red) + 3 * QB);
        st_async2(dst_sm, (t0.x + t1.x) + (t2.x + t3.x), (t0.y + t1.y) + (t2.y + t3.y), dst_bar);
      }
      STAMP(4);
      const float inv = __uint_as_float(lds32(sb + OFF(sinv) + (s & 1) * 4));
      p += (s & 1) ? (1024 - 32) : 32;
      BAR_SYNC(4, 256);
      unsigned tred = clk();
      if (q == 0) { if (elect1()) { arm_bar(bar_sx, 1024); arm_bar(bar_sm, 1024); } __syncwarp(); }
      {
        const uint32_t xb = l16 + OFF(xf) + (s & (NST - 1)) * 7168;
        float y[2][4];
#pragma unroll
        for (int f = 0; f < 7; f++)
#pragma unroll
          for (int m = 0; m < 2; m++) {
            uint4 xa = lds128(xb + (f * 2 + m) * 512);
            const uint32_t b0 = f == 6 ? kl[6] : ((f & 1) ? kh[f & ~1] : kl[f & ~1]), b1 = f == 6 ? kh[6] : ((f & 1) ? kh[f | 1] : kl[f | 1]);
            MMW(y[m], xa, b0, b1, f == 0);
          }
        sts128(lq + QOFF(xred), __float_as_uint(y[0][0]), __float_as_uint(y[0][1]), __float_as_uint(y[0][2]), __float_as_uint(y[0][3]));
        sts128(lq + QOFF(xred) + 512, __float_as_uint(y[1][0]), __float_as_uint(y[1][1]), __float_as_uint(y[1][2]), __float_as_uint(y[1][3]));
        BAR_SYNC(2, 128);
        if (q < 2) {
          uint32_t xr = l16 + QOFF(xred) + q * 512; asm volatile("" : "+r"(xr));
          float4 t0 = lds128f(xr), t1 = lds128f(xr + QB), t2 = lds128f(xr + 2 * QB), t3 = lds128f(xr + 3 * QB);
          *(float4*)((char*)(g_SXM + ((((s * NH + h) * 4 + j) * 2 + q) * 32)) + (l16 - sb)) = make_float4(((t0.x + t1.x) + (t2.x + t3.x)) * inv, ((t0.y + t1.y) + (t2.y + t3.y)) * inv, ((t0.z + t1.z) + (t2.z + t3.z)) * inv, ((t0.w + t1.w) + (t2.w + t3.w)) * inv);
        }
      }
      BAR_ARRIVE(15, 160);
      while (clk() - tred < (unsigned)poll_delay) {}
    }
  } else if (role == 1) {
    asm volatile("setmaxnreg.inc.sync.aligned.u32 216;");
    const int lane = opaque_lane();
    const uint32_t l16 = sb + lane * 16;
    uint4 W[42];
    {
      const uint4* wf = g_WF + (((NH + h) * 28 + 7 * j) * 28 + 7 * q) * 32 + lane;
#pragma unroll
      for (int k = 0; k < 7; k++)
#pragma unroll
        for (int t = 0; t < 6; t++) W[k * 6 + t] = wf[(t * 28 + k) * 32];
    }
#undef ws
#define ws (lq + QOFF(wB))
    const uint32_t lq = l16 + q * QB;
#define uq (lq + QOFF(uQ))
    const uint32_t dst_sx = mapa(l16 + OFF(sx) + (j >> 1) * 512 + (j & 1) * 8, q), dst_bar = mapa(bar_sx, q);
#pragma unroll 1
    for (int s = 0; s < NSEG; s++) {
      const int st = s & (NST - 1);
      wait_bar1(bar_ld + 8 * st, (s / NST) & 1);
      uint4 p0, p1, p2; uint2 p3;
      {
        const uint32_t kb = lq + QOFF(kf) + st * 2048;
        uint4 k0 = lds128(kb), k1 = lds128(kb + 512), k2 = lds128(kb + 1024); uint2 k3 = lds64(kb + 1536);
        BAR_SYNC_R(5 + q, 64);
        STAMP(2);
        p0 = lds128(mq); p1 = lds128(mq + 512); p2 = lds128(mq + 1024); p3 = lds64(mq + 1536);
        float dl[4], dh[4], el[4], eh[4];
        mma_z(dl, p0.x, p0.y, p0.z, p0.w, k0.x, k0.y); mma_z(dh, p0.x, p0.y, p0.z, p0.w, k0.z, k0.w);
        mma_z(el, p1.x, p1.y, p1.z, p1.w, k1.x, k1.y); mma_z(eh, p1.x, p1.y, p1.z, p1.w, k1.z, k1.w);
        mma16816(dl, p2.x, p2.y, p2.z, p2.w, k2.x, k2.y); mma16816(dh, p2.x, p2.y, p2.z, p2.w, k2.z, k2.w);
        mma1688(el, p3.x, p3.y, k3.x); mma1688(eh, p3.x, p3.y, k3.y);
        sts64f(lq + QOFF(red) + 8, (dl[0] + dh[2]) + (el[0] + eh[2]), (dl[1] + dh[3]) + (el[1] + eh[3]));
        BAR_SYNC(14, 128);
        float2 t0 = lds64f(l16 + QOFF(red) + 8), t1 = lds64f(l16 + QOFF(red) + 8 + QB), t2 = lds64f(l16 + QOFF(red) + 8 + 2 * QB), t3 = lds64f(l16 + QOFF(red) + 8 + 3 * QB);
        st_async2(dst_sx, (t0.x + t1.x) + (t2.x + t3.x), (t0.y + t1.y) + (t2.y + t3.y), dst_bar);
      }
      STAMP(9);
      FENCE(6);
      {
        uint32_t m = amax2(amax2(amax2(amax2(0u, p0.x, p0.y), p0.z, p0.w), p1.x, p1.y), p1.z, p1.w);
        m = amax2(amax2(amax2(m, p2.x, p2.y), p2.z, p2.w), p3.x, p3.y);
        m = max(m & 0xffffu, m >> 16);
        m = __reduce_max_sync(0xffffffffu, m);
        sts32(sb + OFF(smax) + q * 4, m);
      }
      BAR_SYNC_R(10 + q, 64);
      p0 = lds128(mq);
      STAMP(10);
      const uint32_t b[14] = {p0.x, p0.y, p0.z, p0.w, p1.x, p1.y, p1.z, p1.w, p2.x, p2.y, p2.z, p2.w, p3.x, p3.y};
      float acc[7][4];
#pragma unroll
      for (int k = 0; k < 7; k++)
#pragma unroll
        for (int t = 0; t < 4; t++) MMW(acc[t], W[k * 6 + t], b[2 * k], b[2 * k + 1], k == 0);
      uint4 w6a = lds128(ws), w6b = lds128(ws + 512);
      uint32_t u7;
#define UP(nt) pack_bf16(acc[(nt) >> 1][((nt) & 1) * 2], acc[(nt) >> 1][((nt) & 1) * 2 + 1])
#pragma unroll
      for (int k = 0; k < 7; k++) {
        MMW(acc[4], W[k * 6 + 4], b[2 * k], b[2 * k + 1], k == 0);
        MMW(acc[5], W[k * 6 + 5], b[2 * k], b[2 * k + 1], k == 0);
        if (k & 1) { MMW(acc[6], w6b, b[2 * k], b[2 * k + 1], k == 0); if (k + 2 < 7) w6b = lds128(ws + (k + 2) * 512); }
        else { MMW(acc[6], w6a, b[2 * k], b[2 * k + 1], k == 0); if (k + 2 < 7) w6a = lds128(ws + (k + 2) * 512); }
        if (k == 1) { uint32_t u6 = UP(6); u7 = UP(7); sts128(uq, UP(0), UP(1), UP(2), u6); sts128(uq + 512, UP(3), UP(4), UP(5), u6); }
      }
      sts128(uq + 1024, UP(8), UP(9), UP(10), u7); sts128(uq + 1536, UP(11), UP(12), UP(13), u7);
      BAR_ARRIVE(3, 256);
      STAMP(11);
      if (q == 0) {
        if (s > 0) BAR_SYNC(15, 160);
        if (s + NST - 1 < NSEG) { if (elect1()) issue_loads(sb, s + NST - 1, h, j); __syncwarp(); }
      }
    }
    if (q == 0) BAR_SYNC(15, 160);
  } else {
    asm volatile("setmaxnreg.dec.sync.aligned.u32 64;");
    const int lane = opaque_lane();
    const uint32_t l16 = sb + lane * 16;
    const int nt0 = q < 2 ? q * 3 : 8 + (q - 2) * 3, nts = 6 + (q >> 1);
    const float bmax = g_bmax;
    float inv = g_inv0;
    uint32_t sc_bf; { uint32_t t = (0x7f000000u - __float_as_uint(inv)) >> 16; sc_bf = t | (t << 16); }
    uint4* redp = acc_ptr(1, j * 4 + q, lane);
#pragma unroll 1
    for (int s = 0; s < NSEG; s++) {
      const int st = s & (NST - 1);
      float ox[8];
      float mx;
      const float c1 = LOG2E * inv;
      {
        const uint32_t vb = l16 + OFF(vf) + st * 7168;
        wait_bar1(bar_ld + 8 * st, (s / NST) & 1);
        uint4 v0 = lds128(vb + nt0 * 512), v1 = lds128(vb + nt0 * 512 + 512), v2 = lds128(vb + nt0 * 512 + 1024), v3 = lds128(vb + nts * 512);
        wait_bar1(bar_sx, s & 1);
        STAMP(12);
        float4 x0 = lds128f(l16 + OFF(sx)), x1 = lds128f(l16 + OFF(sx) + 512);
        float sx[8] = {x0.x, x0.y, x0.z, x0.w, x1.x, x1.y, x1.z, x1.w};
        mx = fmaxf(fmaxf(fmaxf(sx[0], sx[1]), fmaxf(sx[2], sx[3])), fmaxf(fmaxf(sx[4], sx[5]), fmaxf(sx[6], sx[7])));
        mx = fmaxf(mx, __shfl_xor_sync(0xffffffffu, mx, 1)); mx = fmaxf(mx, __shfl_xor_sync(0xffffffffu, mx, 2));
        mx *= c1;
#pragma unroll
        for (int i = 0; i < 8; i++) sx[i] = ex2(fmaf(sx[i], c1, -mx));
        uint32_t p0 = pack_bf16(sx[0], sx[1]), p1 = pack_bf16(sx[2], sx[3]), p2 = pack_bf16(sx[4], sx[5]), p3 = pack_bf16(sx[6], sx[7]);
        float o[4], r[4];
        mma_z(o, p0, p2, p1, p3, v0.x, v0.y); mma_z(r, p0, p2, p1, p3, v0.z, v0.w); ox[0] = o[0] + r[2]; ox[1] = o[1] + r[3];
        mma_z(o, p0, p2, p1, p3, v1.x, v1.y); mma_z(r, p0, p2, p1, p3, v1.z, v1.w); ox[2] = o[0] + r[2]; ox[3] = o[1] + r[3];
        mma_z(o, p0, p2, p1, p3, v2.x, v2.y); mma_z(r, p0, p2, p1, p3, v2.z, v2.w); ox[4] = o[0] + r[2]; ox[5] = o[1] + r[3];
        mma_z(o, p0, p2, p1, p3, v3.x, v3.y); mma_z(r, p0, p2, p1, p3, v3.z, v3.w); ox[6] = (q & 1) ? o[1] + r[3] : o[0] + r[2];
        mma_z(o, p0, p2, p1, p3, 0x3f803f80u, 0x3f803f80u); ox[7] = o[0] + o[2];
      }
      STAMP(5);
      FENCE(8);
      BAR_SYNC(3, 256);
      const uint32_t ub = l16 + QOFF(uQ) + q * 512;
      uint4 u0 = lds128(ub), u1 = lds128(ub + QB), u2 = lds128(ub + 2 * QB), u3 = lds128(ub + 3 * QB);
      float nsc, ninv;
      {
        uint4 m4 = lds128(sb + OFF(smax));
        uint32_t mb = max(max(m4.x, m4.y), max(m4.z, m4.w));
        float mh = fmaxf(__uint_as_float(mb << 16) * inv, __uint_as_float(lds32(sb + OFF(xmax) + s * 4)));
        float bound = mh * bmax;
        int e = (int)(__float_as_uint(bound) >> 23) - 127 + 10;
        int se = min(max(15 - e, -100), 100);
        nsc = __uint_as_float((uint32_t)(127 + se) << 23); ninv = __uint_as_float((uint32_t)(127 - se) << 23);
      }
      STAMP(6);
      wait_bar1(bar_sm, s & 1);
      STAMP(7);
      {
        float4 t0 = lds128f(l16 + OFF(sm)), t1 = lds128f(l16 + OFF(sm) + 512);
        float s0 = ((t0.x + t0.z) + (t1.x + t1.z)) * inv * c1, s1 = ((t0.y + t0.w) + (t1.y + t1.w)) * inv * c1;
        float m = fmaxf(fmaxf(s0, s1), mx);
        m = fmaxf(m, __shfl_xor_sync(0xffffffffu, m, 1)); m = fmaxf(m, __shfl_xor_sync(0xffffffffu, m, 2));
        float e0 = ex2(s0 - m), e1 = ex2(s1 - m), al = ex2(mx - m);
        uint32_t pm = pack_bf16(e0 * inv, e1 * inv);
        float z[4], ya[4], yb[4], yc[4], yd[4];
        mma_z(z, pm, 0u, 0u, pm, sc_bf, sc_bf);
        mma_z(ya, pm, 0u, 0u, pm, u0.x, u0.y); mma_z(yb, pm, 0u, 0u, pm, u0.z, u0.w);
        mma_z(yc, pm, 0u, 0u, pm, u1.x, u1.y); mma_z(yd, pm, 0u, 0u, pm, u1.z, u1.w);
        mma16816(ya, pm, 0u, 0u, pm, u2.x, u2.y); mma16816(yb, pm, 0u, 0u, pm, u2.z, u2.w);
        mma16816(yc, pm, 0u, 0u, pm, u3.x, u3.y); mma16816(yd, pm, 0u, 0u, pm, u3.z, u3.w);
        float iz; asm("rcp.approx.ftz.f32 %0, %1;" : "=f"(iz) : "f"(fmaf(ox[7], al, z[0])));
        iz *= nsc;
#pragma unroll
        for (int i = 0; i < 7; i++) ox[i] *= al;
        const float y6 = (q & 1) ? yb[3] + yd[3] : yb[2] + yd[2];
        red_h8(redp, pack_f16(((ya[0] + ox[0]) + yc[0]) * iz, ((ya[1] + ox[1]) + yc[1]) * iz), pack_f16(((ya[2] + ox[2]) + yc[2]) * iz, ((ya[3] + ox[3]) + yc[3]) * iz),
               pack_f16(((yb[0] + ox[4]) + yd[0]) * iz, ((yb[1] + ox[5]) + yd[1]) * iz), pack_f16((y6 + ox[6]) * iz, 1.f));
      }
      BAR_ARRIVE(4, 256);
      FENCE(10);
      STAMP(8);
      if (q == 0) sts32(sb + OFF(sinv) + ((s + 1) & 1) * 4, __float_as_uint(ninv));
      redp += (s & 1) ? 32 : (1024 - 32);
      {
        auto us = [&](uint32_t a, uint32_t b, uint32_t c, uint32_t d) { return pack_bf16(((bf_lo(a) + bf_lo(b)) + (bf_lo(c) + bf_lo(d))) * inv, ((bf_hi(a) + bf_hi(b)) + (bf_hi(c) + bf_hi(d))) * inv); };
        uint32_t* uf = g_UF + ((s * NH + h) * 56 + 14 * j) * 32 + lane;
        { uf[(nt0 + 0) * 32] = us(u0.x, u1.x, u2.x, u3.x); uf[(nt0 + 1) * 32] = us(u0.y, u1.y, u2.y, u3.y); uf[(nt0 + 2) * 32] = us(u0.z, u1.z, u2.z, u3.z);
        if ((q & 1) == 0) uf[nts * 32] = us(u0.w, u1.w, u2.w, u3.w); }
      }
      inv = ninv; { uint32_t t = __float_as_uint(nsc) >> 16; sc_bf = t | (t << 16); }
    }
  }
  asm volatile("barrier.cluster.arrive.release.aligned;\nbarrier.cluster.wait.acquire.aligned;" ::: "memory");
}

__global__ void n_xf(const bf16* x) {
  int i = blockIdx.x * blockDim.x + threadIdx.x;
  if (i >= NSEG * 4 * 14 * 32) return;
  int lane = i & 31, r = i >> 5, m = r & 1; r >>= 1; int f = r % 7; r /= 7; int j = r & 3, seg = r >> 2;
  int c0 = f == 6 ? 96 : (f & ~1) * 16 + (f & 1) * 8, c1 = f == 6 ? 104 : (f | 1) * 16 + (f & 1) * 8;
  const bf16* r0 = x + (seg * 32 + m * 16 + (lane >> 2)) * DM + j * 112 + (lane & 3) * 2;
  const bf16* r1 = r0 + 8 * DM;
  g_XF[i] = make_uint4(*(const uint32_t*)(r0 + c0), *(const uint32_t*)(r1 + c0), *(const uint32_t*)(r0 + c1), *(const uint32_t*)(r1 + c1));
}

__global__ void n_seed(const bf16* mem0) {
  __shared__ unsigned smx;
  if (threadIdx.x == 0) smx = 0;
  __syncthreads();
  float m = 0.f;
  for (int i = threadIdx.x; i < 8 * DM; i += 512) m = fmaxf(m, fabsf(b2f(mem0[i])));
  atomicMax(&smx, __float_as_uint(m));
  __syncthreads();
  int e = (int)(smx >> 23) - 127 + 1;
  int se = min(max(15 - e, -100), 100);
  float sc = __uint_as_float((uint32_t)(127 + se) << 23);
  if (threadIdx.x == 0) g_inv0 = __uint_as_float((uint32_t)(127 - se) << 23);
  int vec = threadIdx.x >> 5, lane = threadIdx.x & 31, j = vec >> 2, q = vec & 3;
  int nt0 = q < 2 ? q * 3 : 8 + (q - 2) * 3, nts = 6 + (q >> 1);
  const bf16* r = mem0 + (lane >> 2) * DM + j * 112 + (lane & 3) * 2;
  auto val = [&](int nt, int e2) { return b2f(r[nt * 8 + e2]) * sc; };
  *acc_ptr(0, vec, lane) = make_uint4(pack_f16(val(nt0, 0), val(nt0, 1)), pack_f16(val(nt0 + 1, 0), val(nt0 + 1, 1)), pack_f16(val(nt0 + 2, 0), val(nt0 + 2, 1)), pack_f16(val(nts, q & 1), 16.f));
}

__global__ void n_stats(const bf16* x) {
  if (blockIdx.x < 64) {
    float m = 0.f;
    for (int i = threadIdx.x; i < 32 * DM; i += 256) m = fmaxf(m, fabsf(b2f(x[blockIdx.x * 32 * DM + i])));
    atomicMax((unsigned*)&g_xmax[blockIdx.x], __float_as_uint(m));
  } else {
    int r = (blockIdx.x - 64) * 256 + threadIdx.x;
    if (r < NH * DM) { float a = 0.f; for (int k = 0; k < DM; k++) { float v = wf_elem(1, r / DM, r % DM, k); a += v * v; } atomicMax((unsigned*)&g_bmax, __float_as_uint(sqrtf(a))); }
  }
}

int g_poll_delay = POLL_DELAY;
extern "C" void kernel_launch(void* const* d_in, const int* in_sizes, int n_in, void* d_out, int out_size) {
  const bf16* x = (const bf16*)d_in[0];
  const bf16* wqkv = (const bf16*)d_in[1];
  const bf16* wphi = (const bf16*)d_in[2];
  const bf16* wo_a = (const bf16*)d_in[3];
  const bf16* mem0 = (const bf16*)d_in[5];
  const bf16* Wq = (const bf16*)d_in[6];
  const bf16* Wk = (const bf16*)d_in[7];
  const bf16* Wv = (const bf16*)d_in[8];
  const bf16* Wo = (const bf16*)d_in[9];
  const bf16* gate_w = (const bf16*)d_in[11];
  bf16* out = (bf16*)d_out;
  cudaFuncSetAttribute(r_kernel, cudaFuncAttributeMaxDynamicSharedMemorySize, (int)sizeof(RSmem));
  n_zero<<<(NSEG * 40 * 32 + 255) / 256, 256>>>();
  n_prep<<<(2 * NH * 28 * 28 * 32 + 255) / 256, 256>>>(Wq, Wk, Wv, Wo);
  n_stats<<<64 + 28, 256>>>(x);
  n_seed<<<1, 512>>>(mem0);
  n_xf<<<NSEG * 4 * 14 * 32 / 256, 256>>>(x);
  n_xgemm<<<2 * NH * 28 * NSEG * 32 / 256, 256>>>(x);
  r_kernel<<<64, 384, sizeof(RSmem)>>>(mem0, g_poll_delay);
  n_qkv<<<(S_LEN * 1344 + 255) / 256, 256>>>(x, wqkv);
  n_phi<<<(S_LEN * 2 * NH + 255) / 256, 256>>>(wphi);
  n_kv<<<(32 * NH * 56 * 29 + 255) / 256, 256>>>();
  n_oa<<<(S_LEN * DM + 255) / 256, 256>>>();
  n_x3<<<NSEG, 512>>>(x, wo_a, gate_w, out);
}
```

```cpp
#include <cuda_runtime.h>
#include <cuda_bf16.h>
#include <stdint.h>
#include <stddef.h>

typedef __nv_bfloat16 bf16;
#define S_LEN 2048
#define DM 448
#define NH 16
#define NSEG 64
#define SPIN_LIMIT (1 << 22)

__device__ uint4 g_WF[2 * NH * 28 * 28 * 32];
__device__ uint4 g_KF[NSEG * NH * 4 * 4 * 4 * 32];
__device__ uint4 g_VF[NSEG * NH * 56 * 32];
__device__ float4 g_SXM[NSEG * NH * 4 * 2 * 32];
__device__ uint4 g_XF[NSEG * 4 * 14 * 32];
__device__ uint32_t g_UF[NSEG * NH * 56 * 32];
__device__ uint4 g_ACC16[(NSEG + 2) * 16 * 32];
__device__ float g_xmax[NSEG];
__device__ float g_bmax;
__device__ float g_inv0;
__device__ float g_qkv[S_LEN * 1344];
__device__ float g_phiq[S_LEN * NH * 56];
__device__ float g_phik[S_LEN * NH * 56];
__device__ float g_kv[NH * 56 * 29];
__device__ float g_oa[S_LEN * DM];
__device__ int g_err;
__device__ unsigned g_ts[64 * 64 * 16];

__device__ __forceinline__ uint32_t pack_bf16(float lo, float hi) {
  uint32_t r; asm("cvt.rn.bf16x2.f32 %0, %1, %2;" : "=r"(r) : "f"(hi), "f"(lo)); return r;
}
__device__ __forceinline__ float bf_lo(uint32_t v) { return __uint_as_float(v << 16); }
__device__ __forceinline__ float bf_hi(uint32_t v) { return __uint_as_float(v & 0xffff0000u); }
__device__ __forceinline__ float b2f(bf16 v) { return __bfloat162float(v); }

__global__ void n_prep(const bf16* Wq, const bf16* Wk, const bf16* Wv, const bf16* Wo) {
  int idx = blockIdx.x * blockDim.x + threadIdx.x;
  if (idx >= 2 * NH * 28 * 28 * 32) return;
  int lane = idx & 31, r = idx >> 5;
  int ks = r % 28; r /= 28; int tile = r % 28; r /= 28; int h = r % NH; int mat = r / NH;
  int g = lane >> 2, tq = lane & 3;
  float v[8];
  for (int i = 0; i < 8; i++) {
    int row = tile * 16 + g + ((i >> 1) & 1) * 8;
    int col = ks * 16 + tq * 2 + (i & 1) + (i >> 2) * 8;
    float acc = 0.f;
    if (mat == 0) { for (int e = 0; e < 256; e++) acc += b2f(Wq[(row * NH + h) * 256 + e]) * b2f(Wk[(col * NH + h) * 256 + e]); acc *= 0.0625f; }
    else { for (int e = 0; e < 256; e++) acc += b2f(Wo[(h * 256 + e) * DM + row]) * b2f(Wv[(col * NH + h) * 256 + e]); }
    v[i] = acc;
  }
  g_WF[idx] = make_uint4(pack_bf16(v[0], v[1]), pack_bf16(v[2], v[3]), pack_bf16(v[4], v[5]), pack_bf16(v[6], v[7]));
}
__device__ __forceinline__ float wf_elem(int mat, int h, int row, int col) {
  int tile = row >> 4, ks = col >> 4, rr = row & 15, cc = col & 15;
  int lane = (rr & 7) * 4 + ((cc & 7) >> 1);
  int reg = (rr >> 3) + (cc >> 3) * 2;
  uint32_t w = ((const uint32_t*)g_WF)[((((mat * NH + h) * 28 + tile) * 28 + ks) * 32 + lane) * 4 + reg];
  return (cc & 1) ? bf_hi(w) : bf_lo(w);
}
__device__ __forceinline__ void mma16816(float* d, uint32_t a0, uint32_t a1, uint32_t a2, uint32_t a3, uint32_t b0, uint32_t b1) {
  asm volatile("mma.sync.aligned.m16n8k16.row.col.f32.bf16.bf16.f32 {%0,%1,%2,%3}, {%4,%5,%6,%7}, {%8,%9}, {%0,%1,%2,%3};"
    : "+f"(d[0]), "+f"(d[1]), "+f"(d[2]), "+f"(d[3]) : "r"(a0), "r"(a1), "r"(a2), "r"(a3), "r"(b0), "r"(b1));
}
__device__ __forceinline__ void mma1688(float* d, uint32_t a0, uint32_t a1, uint32_t b0) {
  asm volatile("mma.sync.aligned.m16n8k8.row.col.f32.bf16.bf16.f32 {%0,%1,%2,%3}, {%4,%5}, {%6}, {%0,%1,%2,%3};"
    : "+f"(d[0]), "+f"(d[1]), "+f"(d[2]), "+f"(d[3]) : "r"(a0), "r"(a1), "r"(b0));
}
__device__ __forceinline__ uint32_t movm(uint32_t a) { uint32_t d; asm volatile("movmatrix.sync.aligned.m8n8.trans.b16 %0, %1;" : "=r"(d) : "r"(a)); return d; }

__global__ void n_xgemm(const bf16* x) {
  int wid = (blockIdx.x * blockDim.x + threadIdx.x) >> 5, lane = threadIdx.x & 31;
  int seg = wid % NSEG; int r = wid / NSEG;
  int tile = r % 28; r /= 28; int h = r % NH; int mat = r / NH;
  if (mat >= 2) return;
  int g = lane >> 2, tq = lane & 3;
  float d[4][4] = {};
  const uint4* wf = g_WF + (((mat * NH + h) * 28 + tile) * 28) * 32 + lane;
  for (int ks = 0; ks < 28; ks++) {
    uint4 a = wf[ks * 32];
    for (int kg = 0; kg < 4; kg++) {
      const uint32_t* xr = (const uint32_t*)(x + (seg * 32 + kg * 8 + g) * DM + ks * 16 + tq * 2);
      mma16816(d[kg], a.x, a.y, a.z, a.w, xr[0], xr[4]);
    }
  }
  if (mat == 0) {
    for (int kg = 0; kg < 4; kg++) {
      uint32_t b0 = movm(pack_bf16(d[kg][0], d[kg][1])), b1 = movm(pack_bf16(d[kg][2], d[kg][3]));
      int jj = tile / 7, i = tile % 7;
      uint32_t* dst = (uint32_t*)&g_KF[((((seg * NH + h) * 4 + kg) * 4 + jj) * 4 + (i >> 1)) * 32 + lane];
      if (i == 6) { dst[0] = b0; dst[1] = b1; } else { dst[i & 1] = b0; dst[2 + (i & 1)] = b1; }
    }
  } else {
    g_VF[((seg * NH + h) * 56 + tile * 2) * 32 + lane] = make_uint4(pack_bf16(d[0][0], d[0][1]), pack_bf16(d[1][0], d[1][1]), pack_bf16(d[2][0], d[2][1]), pack_bf16(d[3][0], d[3][1]));
    g_VF[((seg * NH + h) * 56 + tile * 2 + 1) * 32 + lane] = make_uint4(pack_bf16(d[0][2], d[0][3]), pack_bf16(d[1][2], d[1][3]), pack_bf16(d[2][2], d[2][3]), pack_bf16(d[3][2], d[3][3]));
  }
}
__global__ void n_zero() {
  int i = blockIdx.x * blockDim.x + threadIdx.x;
  if (i < (NSEG + 2) * 16 * 32) g_ACC16[i] = make_uint4(0, 0, 0, 0);
  if (i < NSEG) g_xmax[i] = 0.f;
  if (i == 0) g_bmax = 0.f;
  if (i < NH * 56 * 29) g_kv[i] = 0.f;
}
__global__ void n_qkv(const bf16* x, const bf16* w) {
  int i = blockIdx.x * blockDim.x + threadIdx.x;
  if (i >= S_LEN * 1344) return;
  int n = i % 1344, t = i / 1344;
  float acc = 0.f;
  for (int k = 0; k < DM; k++) acc += b2f(x[t * DM + k]) * b2f(w[k * 1344 + n]);
  g_qkv[i] = acc;
}
__global__ void n_phi(const bf16* wphi) {
  int i = blockIdx.x * blockDim.x + threadIdx.x;
  if (i >= S_LEN * 2 * NH) return;
  int h = i % NH, which = (i / NH) % 2, t = i / (2 * NH);
  float p[28]; float mx = -1e30f, mn = 1e30f;
  for (int f = 0; f < 28; f++) {
    float acc = 0.f;
    for (int d = 0; d < 28; d++) acc += g_qkv[t * 1344 + which * 448 + h * 28 + d] * b2f(wphi[(h * 28 + d) * 28 + f]);
    p[f] = acc; mx = fmaxf(mx, acc); mn = fminf(mn, acc);
  }
  float s1 = 0.f, s2 = 0.f;
  for (int f = 0; f < 28; f++) { s1 += __expf(p[f] - mx); s2 += __expf(mn - p[f]); }
  float* o = (which ? g_phik : g_phiq) + (t * NH + h) * 56;
  for (int f = 0; f < 28; f++) { o[f] = __expf(p[f] - mx) / s1; o[28 + f] = __expf(mn - p[f]) / s2; }
}
__global__ void n_kv() {
  int i = blockIdx.x * blockDim.x + threadIdx.x;
  if (i >= 32 * NH * 56 * 29) return;
  int d = i % 29, f = (i / 29) % 56, h = (i / (29 * 56)) % NH, ch = i / (29 * 56 * NH);
  float acc = 0.f;
  for (int t = ch * 64; t < ch * 64 + 64; t++) acc += g_phik[(t * NH + h) * 56 + f] * (d < 28 ? g_qkv[t * 1344 + 896 + h * 28 + d] : 1.f);
  atomicAdd(&g_kv[(h * 56 + f) * 29 + d], acc);
}
__global__ void n_oa() {
  int i = blockIdx.x * blockDim.x + threadIdx.x;
  if (i >= S_LEN * DM) return;
  int c = i % DM, t = i / DM, h = c / 28, d = c % 28;
  float num = 0.f, den = 0.f;
  for (int f = 0; f < 56; f++) { float p = g_phiq[(t * NH + h) * 56 + f]; num += p * g_kv[(h * 56 + f) * 29 + d]; den += p * g_kv[(h * 56 + f) * 29 + 28]; }
  g_oa[i] = num / (den + 1e-6f);
}

__global__ void __launch_bounds__(512) n_x3(const bf16* x, const bf16* wo, const bf16* gate_w, bf16* out) {
  __shared__ uint32_t sP[NH][2][32][10];
  __shared__ float sG[32];
  int seg = blockIdx.x, w = threadIdx.x >> 5, lane = threadIdx.x & 31, g = lane >> 2, tq = lane & 3;
  for (int r = w; r < 32; r += 16) {
    float acc = 0.f;
    for (int k = lane; k < DM; k += 32) acc += b2f(x[(seg * 32 + r) * DM + k]) * b2f(gate_w[k]);
    for (int o = 16; o; o >>= 1) acc += __shfl_xor_sync(0xffffffffu, acc, o);
    if (lane == 0) sG[r] = 1.f / (1.f + __expf(-acc));
  }
  {
    int h = w;
    float s[2][5][4] = {};
    for (int ct = 0; ct < 28; ct++) {
      uint32_t a[2][4];
      for (int m = 0; m < 2; m++) {
        const uint32_t* r0 = (const uint32_t*)(x + (seg * 32 + m * 16 + g) * DM + ct * 16 + tq * 2);
        const uint32_t* r1 = (const uint32_t*)(x + (seg * 32 + m * 16 + g + 8) * DM + ct * 16 + tq * 2);
        a[m][0] = r0[0]; a[m][1] = r1[0]; a[m][2] = r0[4]; a[m][3] = r1[4];
      }
      int j = ct / 7, i = ct % 7;
      for (int kg = 0; kg < 4; kg++) {
        const uint32_t* src = (const uint32_t*)&g_KF[((((seg * NH + h) * 4 + kg) * 4 + j) * 4 + (i >> 1)) * 32 + lane];
        uint2 b = i == 6 ? make_uint2(src[0], src[1]) : make_uint2(src[i & 1], src[2 + (i & 1)]);
        for (int m = 0; m < 2; m++) mma16816(s[m][1 + kg], a[m][0], a[m][1], a[m][2], a[m][3], b.x, b.y);
      }
    }
    for (int m = 0; m < 2; m++) for (int j = 0; j < 4; j++) {
      float4 t = g_SXM[(((seg * NH + h) * 4 + j) * 2 + m) * 32 + lane];
      s[m][0][0] += t.x; s[m][0][1] += t.y; s[m][0][2] += t.z; s[m][0][3] += t.w;
    }
    for (int m = 0; m < 2; m++) for (int hf = 0; hf < 2; hf++) {
      int t = m * 16 + hf * 8 + g;
      float v[10]; float mx = -1e30f;
      for (int n = 0; n < 5; n++) for (int e = 0; e < 2; e++) {
        float val = s[m][n][hf * 2 + e];
        if (n > 0 && (n - 1) * 8 + tq * 2 + e > t) val = -1e30f;
        v[n * 2 + e] = val; mx = fmaxf(mx, val);
      }
      mx = fmaxf(mx, __shfl_xor_sync(0xffffffffu, mx, 1)); mx = fmaxf(mx, __shfl_xor_sync(0xffffffffu, mx, 2));
      float z = 0.f;
      for (int i = 0; i < 10; i++) { v[i] = __expf(v[i] - mx); z += v[i]; }
      z += __shfl_xor_sync(0xffffffffu, z, 1); z += __shfl_xor_sync(0xffffffffu, z, 2);
      float iz = 1.f / z;
      sP[h][m][lane][hf] = pack_bf16(v[0] * iz, v[1] * iz);
      sP[h][m][lane][2 + hf] = pack_bf16(v[2] * iz, v[3] * iz);
      sP[h][m][lane][4 + hf] = pack_bf16(v[4] * iz, v[5] * iz);
      sP[h][m][lane][6 + hf] = pack_bf16(v[6] * iz, v[7] * iz);
      sP[h][m][lane][8 + hf] = pack_bf16(v[8] * iz, v[9] * iz);
    }
  }
  __syncthreads();
  if (w < 14) {
    float o[2][4][4] = {};
    for (int h = 0; h < NH; h++) {
      for (int n = 0; n < 4; n++) {
        int nt = w * 4 + n;
        uint4 v = g_VF[((seg * NH + h) * 56 + nt) * 32 + lane];
        uint32_t u = g_UF[((seg * NH + h) * 56 + nt) * 32 + lane];
        for (int m = 0; m < 2; m++) {
          const uint32_t* p = sP[h][m][lane];
          mma1688(o[m][n], p[0], p[1], u);
          mma16816(o[m][n], p[2], p[3], p[4], p[5], v.x, v.y);
          mma16816(o[m][n], p[6], p[7], p[8], p[9], v.z, v.w);
        }
      }
    }
    for (int m = 0; m < 2; m++) for (int n = 0; n < 4; n++) for (int i = 0; i < 4; i++) {
      int r = m * 16 + (i >> 1) * 8 + g, c = (w * 4 + n) * 8 + tq * 2 + (i & 1);
      int t = seg * 32 + r;
      float a = 0.f;
      for (int k = 0; k < DM; k++) a += g_oa[t * DM + k] * b2f(wo[k * DM + c]);
      float gt = sG[r];
      out[t * DM + c] = __float2bfloat16(gt * a + (1.f - gt) * o[m][n][i]);
    }
  }
}

__device__ __forceinline__ uint32_t smem_u32(const void* p) { return (uint32_t)__cvta_generic_to_shared(p); }
__device__ __forceinline__ uint32_t mapa(uint32_t a, uint32_t r) { uint32_t o; asm volatile("mapa.shared::cluster.u32 %0, %1, %2;" : "=r"(o) : "r"(a), "r"(r)); return o; }
__device__ __forceinline__ bool try_wait(uint32_t bar, uint32_t parity) {
  uint32_t ok; asm volatile("{\n.reg .pred p;\nmbarrier.try_wait.parity.shared::cta.b64 p, [%1], %2;\nselp.u32 %0, 1, 0, p;\n}" : "=r"(ok) : "r"(bar), "r"(parity) : "memory"); return ok; }
__device__ __forceinline__ void wait_bar(uint32_t bar, uint32_t parity) {
  int n = 0; while (!try_wait(bar, parity)) { if (++n > SPIN_LIMIT) { g_err = 1; break; } } }
__device__ __forceinline__ void arm_bar(uint32_t bar, uint32_t bytes) { asm volatile("mbarrier.arrive.expect_tx.shared::cta.b64 _, [%0], %1;" :: "r"(bar), "r"(bytes) : "memory"); }
__device__ __forceinline__ float4 ld_relaxed4(const void* p) { float4 v; asm volatile("ld.relaxed.gpu.global.v4.f32 {%0,%1,%2,%3}, [%4];" : "=f"(v.x), "=f"(v.y), "=f"(v.z), "=f"(v.w) : "l"(p) : "memory"); return v; }
__device__ __forceinline__ void red4(void* p, float a, float b, float c, float d) { asm volatile("red.relaxed.gpu.global.add.v4.f32 [%0], {%1,%2,%3,%4};" :: "l"(p), "f"(a), "f"(b), "f"(c), "f"(d) : "memory"); }
__device__ __forceinline__ void st_async2(uint32_t dst, float a, float b, uint32_t bar) { asm volatile("st.async.shared::cluster.mbarrier::complete_tx::bytes.v2.f32 [%0], {%1,%2}, [%3];" :: "r"(dst), "f"(a), "f"(b), "r"(bar) : "memory"); }
__device__ __forceinline__ void bulk_g2s(uint32_t dst, const void* src, uint32_t bytes, uint32_t bar) {
  asm volatile("cp.async.bulk.shared::cluster.global.mbarrier::complete_tx::bytes [%0], [%1], %2, [%3];" :: "r"(dst), "l"(src), "r"(bytes), "r"(bar) : "memory"); }
__device__ __forceinline__ unsigned clk() { unsigned c; asm volatile("mov.u32 %0, %%clock;" : "=r"(c) :: "memory"); return c; }
__device__ __forceinline__ float ex2(float x) { float y; asm("ex2.approx.ftz.f32 %0, %1;" : "=f"(y) : "f"(x)); return y; }

#define NST 4
struct QBlk {
  uint4 memF[4][32];
  uint4 wA[7][32], wB[7][32];
  uint4 kf[NST][4][32];
  float4 xred[2][32];
  float4 red[32];
  uint4 uQ[4][32];
  uint4 kq[4][32];
};
#define QB ((uint32_t)sizeof(QBlk))
#define QOFF(f) ((uint32_t)offsetof(QBlk, f))
struct RSmem {
  QBlk qb[4];
  uint4 vf[NST][14][32];
  uint4 xf[NST][14][32];
  float4 sx[2][32];
  float4 sm[2][32];
  uint32_t smax[4];
  float xmax[NSEG];
  float sinv[4];
  unsigned long long bar_ld[NST], bar_sx, bar_sm;
  unsigned ts[64 * 16];
};
#define LD_BYTES (8192 + 7168 + 7168)
#define POLL_DELAY 300
#define STAMP(i)
__device__ __forceinline__ void wait_slow(uint32_t bar, uint32_t parity) {
#pragma unroll 1
  for (int n = 0; n < SPIN_LIMIT; n++) if (try_wait(bar, parity)) return;
  g_err = 1;
}
__device__ __forceinline__ void wait_bar1(uint32_t bar, uint32_t parity) { if (!try_wait(bar, parity)) wait_slow(bar, parity); }
__device__ __forceinline__ uint4 ld_relaxed_u4(const void* p) { uint4 v; asm volatile("ld.relaxed.gpu.global.v4.u32 {%0,%1,%2,%3}, [%4];" : "=r"(v.x), "=r"(v.y), "=r"(v.z), "=r"(v.w) : "l"(p) : "memory"); return v; }
__device__ __forceinline__ void red_h8(void* p, uint32_t a, uint32_t b, uint32_t c, uint32_t d) { asm volatile("red.relaxed.gpu.global.add.noftz.v4.f16x2 [%0], {%1,%2,%3,%4};" :: "l"(p), "r"(a), "r"(b), "r"(c), "r"(d) : "memory"); }
__device__ __forceinline__ uint32_t pack_f16(float lo, float hi) { uint32_t r; asm("cvt.rn.f16x2.f32 %0, %1, %2;" : "=r"(r) : "f"(hi), "f"(lo)); return r; }
__device__ __forceinline__ uint32_t h2_to_bf2(uint32_t v) {
  float lo, hi; asm("{.reg .f16 l, h; mov.b32 {l, h}, %2; cvt.f32.f16 %0, l; cvt.f32.f16 %1, h;}" : "=f"(lo), "=f"(hi) : "r"(v)); return pack_bf16(lo, hi); }
__device__ __forceinline__ uint2 lds64(uint32_t a) { uint2 v; asm volatile("ld.shared.v2.u32 {%0,%1}, [%2];" : "=r"(v.x), "=r"(v.y) : "r"(a) : "memory"); return v; }
__device__ __forceinline__ float2 lds64f(uint32_t a) { float2 v; asm volatile("ld.shared.v2.f32 {%0,%1}, [%2];" : "=f"(v.x), "=f"(v.y) : "r"(a) : "memory"); return v; }
__device__ __forceinline__ uint4 lds128(uint32_t a) { uint4 v; asm volatile("ld.shared.v4.u32 {%0,%1,%2,%3}, [%4];" : "=r"(v.x), "=r"(v.y), "=r"(v.z), "=r"(v.w) : "r"(a) : "memory"); return v; }
__device__ __forceinline__ uint32_t lds32(uint32_t a) { uint32_t v; asm volatile("ld.shared.u32 %0, [%1];" : "=r"(v) : "r"(a) : "memory"); return v; }
__device__ __forceinline__ void sts64(uint32_t a, uint32_t x, uint32_t y) { asm volatile("st.shared.v2.u32 [%0], {%1,%2};" :: "r"(a), "r"(x), "r"(y) : "memory"); }
__device__ __forceinline__ void sts64f(uint32_t a, float x, float y) { asm volatile("st.shared.v2.f32 [%0], {%1,%2};" :: "r"(a), "f"(x), "f"(y) : "memory"); }
__device__ __forceinline__ void sts32(uint32_t a, uint32_t x) { asm volatile("st.shared.u32 [%0], %1;" :: "r"(a), "r"(x) : "memory"); }
__device__ __forceinline__ void mma_z(float* d, uint32_t a0, uint32_t a1, uint32_t a2, uint32_t a3, uint32_t b0, uint32_t b1) {
  asm volatile("mma.sync.aligned.m16n8k16.row.col.f32.bf16.bf16.f32 {%0,%1,%2,%3}, {%4,%5,%6,%7}, {%8,%9}, {%10,%10,%10,%10};"
    : "=f"(d[0]), "=f"(d[1]), "=f"(d[2]), "=f"(d[3]) : "r"(a0), "r"(a1), "r"(a2), "r"(a3), "r"(b0), "r"(b1), "f"(0.f));
}
__device__ __forceinline__ void mma8_z(float* d, uint32_t a0, uint32_t a1, uint32_t b0) {
  asm volatile("mma.sync.aligned.m16n8k8.row.col.f32.bf16.bf16.f32 {%0,%1,%2,%3}, {%4,%5}, {%6}, {%7,%7,%7,%7};"
    : "=f"(d[0]), "=f"(d[1]), "=f"(d[2]), "=f"(d[3]) : "r"(a0), "r"(a1), "r"(b0), "f"(0.f));
}
#define OFF(f) ((uint32_t)offsetof(RSmem, f))
#define BAR_SYNC(id, n) asm volatile("bar.sync %0, %1;" :: "n"(id), "n"(n) : "memory")
#define BAR_ARRIVE(id, n) asm volatile("bar.arrive %0, %1;" :: "n"(id), "n"(n) : "memory")

__device__ __forceinline__ void sts128(uint32_t a, uint32_t x, uint32_t y, uint32_t z, uint32_t w) { asm volatile("st.shared.v4.u32 [%0], {%1,%2,%3,%4};" :: "r"(a), "r"(x), "r"(y), "r"(z), "r"(w) : "memory"); }
template <int K>
__device__ __forceinline__ void kstep(const uint4 (&W)[42], float (&acc)[7][4], uint32_t b0, uint32_t b1, uint4& w6, uint32_t ws) {
#pragma unroll
  for (int t = 0; t < 6; t++) {
    const uint4& w = W[K * 6 + t];
    if (K == 0) mma_z(acc[t], w.x, w.y, w.z, w.w, b0, b1); else mma16816(acc[t], w.x, w.y, w.z, w.w, b0, b1);
  }
  if (K == 0) mma_z(acc[6], w6.x, w6.y, w6.z, w6.w, b0, b1); else mma16816(acc[6], w6.x, w6.y, w6.z, w6.w, b0, b1);
  if (K < 6) w6 = lds128(ws + (K + 1) * 512);
}
__device__ __forceinline__ uint4* acc_ptr(int step, int vec, int lane) { return g_ACC16 + (((step >> 1) * 16 + vec) * 2 + (step & 1)) * 32 + lane; }

__device__ __forceinline__ bool elect1() { uint32_t p; asm volatile("{.reg .pred p; elect.sync _|p, 0xffffffff; selp.u32 %0, 1, 0, p;}" : "=r"(p)); return p; }
__device__ __forceinline__ float4 lds128f(uint32_t a) { float4 v; asm volatile("ld.shared.v4.f32 {%0,%1,%2,%3}, [%4];" : "=f"(v.x), "=f"(v.y), "=f"(v.z), "=f"(v.w) : "r"(a) : "memory"); return v; }
__device__ __forceinline__ uint32_t amax2(uint32_t m, uint32_t x, uint32_t y) { return __vmaxu2(m, __vmaxu2(x & 0x7fff7fffu, y & 0x7fff7fffu)); }

#define FENCE(n) do { if (__builtin_expect((poll_delay >> (16 + (n))) & 1, 0)) { _Pragma("unroll 1") for (int i_ = poll_delay & 7; i_ > 0; i_--) asm volatile("nanosleep.u32 %0;" :: "n"(n) : "memory"); } } while (0)
#define BAR_SYNC_R(id, n) asm volatile("bar.sync %0, %1;" :: "r"(id), "n"(n) : "memory")
#define BAR_ARRIVE_R(id, n) asm volatile("bar.arrive %0, %1;" :: "r"(id), "n"(n) : "memory")
#define MMW(A, WW, B0, B1, first) do { if (first) mma_z(A, WW.x, WW.y, WW.z, WW.w, B0, B1); else mma16816(A, WW.x, WW.y, WW.z, WW.w, B0, B1); } while (0)
__device__ __forceinline__ void issue_loads(uint32_t sb, int s, int h, int j) {
  const int st = s & (NST - 1);
  const uint32_t bar = sb + OFF(bar_ld) + 8 * st;
  arm_bar(bar, LD_BYTES);
#pragma unroll
  for (int qq = 0; qq < 4; qq++) bulk_g2s(sb + qq * QB + QOFF(kf) + st * 2048, g_KF + ((s * NH + h) * 4 + j) * 512 + qq * 128, 2048, bar);
  bulk_g2s(sb + OFF(vf) + st * 7168, g_VF + ((s * NH + h) * 56 + 14 * j) * 32, 7168, bar);
  bulk_g2s(sb + OFF(xf) + st * 7168, g_XF + (s * 4 + j) * 448, 7168, bar);
  asm volatile("prefetch.global.L2 [%0];" :: "l"(acc_ptr(s, h, j * 8)));
}
__device__ __forceinline__ int opaque_lane() { return __shfl_sync(0xffffffffu, threadIdx.x & 31, threadIdx.x & 31); }

__global__ void __cluster_dims__(4, 1, 1) __launch_bounds__(384, 1) r_kernel(const bf16* mem0, int poll_delay) {
  extern __shared__ __align__(128) unsigned char smem_raw[];
  RSmem& sm = *reinterpret_cast<RSmem*>(smem_raw);
  const int h = blockIdx.x >> 2, j = blockIdx.x & 3;
  const int w = __shfl_sync(0xffffffffu, threadIdx.x >> 5, 0), q = w & 3, role = w >> 2;
  const uint32_t sb = smem_u32(smem_raw);
  const uint32_t bar_ld = sb + OFF(bar_ld), bar_sx = sb + OFF(bar_sx), bar_sm = sb + OFF(bar_sm);
  if (threadIdx.x == 0) {
    for (int i = 0; i < NST; i++) asm volatile("mbarrier.init.shared::cta.b64 [%0], 1;" :: "r"(bar_ld + 8 * i));
    asm volatile("mbarrier.init.shared::cta.b64 [%0], 1;" :: "r"(bar_sx));
    asm volatile("mbarrier.init.shared::cta.b64 [%0], 1;" :: "r"(bar_sm));
    asm volatile("fence.mbarrier_init.release.cluster;" ::: "memory");
    arm_bar(bar_sx, 1024); arm_bar(bar_sm, 1024);
    for (int s = 0; s < NST; s++) issue_loads(sb, s, h, j);
    sm.sinv[0] = g_inv0;
  }
  if (threadIdx.x < NSEG) sm.xmax[threadIdx.x] = g_xmax[threadIdx.x];
  if (role < 2) {
    const int lane = threadIdx.x & 31;
    const uint4* wf = g_WF + (((role * NH + h) * 28 + 7 * j + 6) * 28 + 7 * q) * 32 + lane;
#pragma unroll
    for (int e = 0; e < 7; e++) (role ? sm.qb[q].wB : sm.qb[q].wA)[e][lane] = wf[e * 32];
  }
  asm volatile("barrier.cluster.arrive.release.aligned;\nbarrier.cluster.wait.acquire.aligned;" ::: "memory");
  const float LOG2E = 1.4426950408889634f;

  if (role == 0) {
    asm volatile("setmaxnreg.inc.sync.aligned.u32 216;");
    const int lane = opaque_lane();
    const uint32_t l16 = sb + lane * 16;
    uint4 W[42];
    {
      const uint4* wf = g_WF + ((h * 28 + 7 * j) * 28 + 7 * q) * 32 + lane;
#pragma unroll
      for (int k = 0; k < 7; k++)
#pragma unroll
        for (int t = 0; t < 6; t++) W[k * 6 + t] = wf[(t * 28 + k) * 32];
    }
    const uint32_t lq = l16 + q * QB, mj = l16 + j * QB;
#define ws (lq + QOFF(wA))
#define mq lq
    const uint32_t dst_sm = mapa(l16 + OFF(sm) + (j >> 1) * 512 + (j & 1) * 8, q), dst_bar = mapa(bar_sm, q);
    const uint4* p = acc_ptr(0, q * 4, lane);
#pragma unroll 1
    for (int s = 0; s < NSEG; s++) {
      STAMP(0);
      uint4 v0 = ld_relaxed_u4(p), v1 = ld_relaxed_u4(p + 64), v2 = ld_relaxed_u4(p + 128), v3 = ld_relaxed_u4(p + 192);
      if (!__all_sync(0xffffffffu, __byte_perm(v0.w, v1.w, 0x7632) == 0x4C004C00u && __byte_perm(v2.w, v3.w, 0x7632) == 0x4C004C00u)) {
#pragma unroll 1
        for (int n = 0; n < SPIN_LIMIT; n++) {
          v0 = ld_relaxed_u4(p); v1 = ld_relaxed_u4(p + 64); v2 = ld_relaxed_u4(p + 128); v3 = ld_relaxed_u4(p + 192);
          if (__all_sync(0xffffffffu, __byte_perm(v0.w, v1.w, 0x7632) == 0x4C004C00u && __byte_perm(v2.w, v3.w, 0x7632) == 0x4C004C00u)) break;
        }
      }
      STAMP(1);
      uint32_t b[14];
      b[0] = h2_to_bf2(v0.x); b[1] = h2_to_bf2(v0.y); b[2] = h2_to_bf2(v0.z); b[3] = h2_to_bf2(v1.x); b[4] = h2_to_bf2(v1.y); b[5] = h2_to_bf2(v1.z);
      b[6] = h2_to_bf2(__byte_perm(v0.w, v1.w, 0x5410)); b[7] = h2_to_bf2(__byte_perm(v2.w, v3.w, 0x5410));
      b[8] = h2_to_bf2(v2.x); b[9] = h2_to_bf2(v2.y); b[10] = h2_to_bf2(v2.z); b[11] = h2_to_bf2(v3.x); b[12] = h2_to_bf2(v3.y); b[13] = h2_to_bf2(v3.z);
      sts128(mq, b[0], b[1], b[2], b[3]); sts128(mq + 512, b[4], b[5], b[6], b[7]); sts128(mq + 1024, b[8], b[9], b[10], b[11]); sts64(mq + 1536, b[12], b[13]);
      BAR_ARRIVE_R(5 + q, 64);
      float acc[7][4];
      uint4 w6a = lds128(ws), w6b = lds128(ws + 512);
#pragma unroll
      for (int k = 0; k < 7; k++)
#pragma unroll
        for (int t = 0; t < 4; t++) MMW(acc[t], W[k * 6 + t], b[2 * k], b[2 * k + 1], k == 0);
      FENCE(2);
      BAR_SYNC(1, 128);
      uint4 a0 = lds128(mj), a1 = lds128(mj + 512);
      uint32_t kl[7], kh[7];
      float dl[4], dh[4], el[4], eh[4];
#define B2(k) do { MMW(acc[4], W[(k) * 6 + 4], b[2 * (k)], b[2 * (k) + 1], (k) == 0); MMW(acc[5], W[(k) * 6 + 5], b[2 * (k)], b[2 * (k) + 1], (k) == 0); \
        if ((k) & 1) { MMW(acc[6], w6b, b[2 * (k)], b[2 * (k) + 1], (k) == 0); if ((k) + 2 < 7) w6b = lds128(ws + ((k) + 2) * 512); } \
        else { MMW(acc[6], w6a, b[2 * (k)], b[2 * (k) + 1], (k) == 0); if ((k) + 2 < 7) w6a = lds128(ws + ((k) + 2) * 512); } } while (0)
      B2(0); B2(1);
#pragma unroll
      for (int t = 0; t < 4; t++) { kl[t] = movm(pack_bf16(acc[t][0], acc[t][1])); kh[t] = movm(pack_bf16(acc[t][2], acc[t][3])); }
      B2(2); B2(3);
      FENCE(4);
      uint4 a2 = lds128(mj + 1024); uint2 a3 = lds64(mj + 1536);
      B2(4);
      mma_z(dl, a0.x, a0.y, a0.z, a0.w, kl[0], kl[1]);
      B2(5);
      mma_z(dh, a0.x, a0.y, a0.z, a0.w, kh[0], kh[1]);
      B2(6);
      mma_z(el, a1.x, a1.y, a1.z, a1.w, kl[2], kl[3]); mma_z(eh, a1.x, a1.y, a1.z, a1.w, kh[2], kh[3]);
      BAR_ARRIVE_R(10 + q, 64);
      FENCE(5);
      STAMP(3);
#pragma unroll
      for (int t = 4; t < 7; t++) { kl[t] = movm(pack_bf16(acc[t][0], acc[t][1])); kh[t] = movm(pack_bf16(acc[t][2], acc[t][3])); }
      mma16816(dl, a2.x, a2.y, a2.z, a2.w, kl[4], kl[5]); mma16816(dh, a2.x, a2.y, a2.z, a2.w, kh[4], kh[5]);
      mma1688(el, a3.x, a3.y, kl[6]); mma1688(eh, a3.x, a3.y, kh[6]);
      sts64f(lq + QOFF(red), (dl[0] + dh[2]) + (el[0] + eh[2]), (dl[1] + dh[3]) + (el[1] + eh[3]));
      BAR_SYNC(2, 128);
      {
        float2 t0 = lds64f(l16 + QOFF(red)), t1 = lds64f(l16 + QOFF(red) + QB), t2 = lds64f(l16 + QOFF(red) + 2 * QB), t3 = lds64f(l16 + QOFF(red) + 3 * QB);
        st_async2(dst_sm, (t0.x + t1.x) + (t2.x + t3.x), (t0.y + t1.y) + (t2.y + t3.y), dst_bar);
      }
      STAMP(4);
      sts128(lq + QOFF(kq), kl[0], kl[1], kh[0], kh[1]); sts128(lq + QOFF(kq) + 512, kl[2], kl[3], kh[2], kh[3]);
      sts128(lq + QOFF(kq) + 1024, kl[4], kl[5], kh[4], kh[5]); sts64(lq + QOFF(kq) + 1536, kl[6], kh[6]);
      p += (s & 1) ? (1024 - 32) : 32;
      BAR_SYNC(4, 384);
      unsigned tred = clk();
      if (q == 0) { if (elect1()) { arm_bar(bar_sx, 1024); arm_bar(bar_sm, 1024); } __syncwarp(); }
      while (clk() - tred < (unsigned)(poll_delay & 0xffff)) {}
    }
  } else if (role == 1) {
    asm volatile("setmaxnreg.inc.sync.aligned.u32 216;");
    const int lane = opaque_lane();
    const uint32_t l16 = sb + lane * 16;
    uint4 W[42];
    {
      const uint4* wf = g_WF + (((NH + h) * 28 + 7 * j) * 28 + 7 * q) * 32 + lane;
#pragma unroll
      for (int k = 0; k < 7; k++)
#pragma unroll
        for (int t = 0; t < 6; t++) W[k * 6 + t] = wf[(t * 28 + k) * 32];
    }
#undef ws
#define ws (lq + QOFF(wB))
    const uint32_t lq = l16 + q * QB;
#define uq (lq + QOFF(uQ))
    const uint32_t dst_sx = mapa(l16 + OFF(sx) + (j >> 1) * 512 + (j & 1) * 8, q), dst_bar = mapa(bar_sx, q);
#pragma unroll 1
    for (int s = 0; s < NSEG; s++) {
      const int st = s & (NST - 1);
      wait_bar1(bar_ld + 8 * st, (s / NST) & 1);
      uint4 p0, p1, p2; uint2 p3;
      {
        const uint32_t kb = lq + QOFF(kf) + st * 2048;
        uint4 k0 = lds128(kb), k1 = lds128(kb + 512), k2 = lds128(kb + 1024); uint2 k3 = lds64(kb + 1536);
        BAR_SYNC_R(5 + q, 64);
        STAMP(2);
        p0 = lds128(mq); p1 = lds128(mq + 512); p2 = lds128(mq + 1024); p3 = lds64(mq + 1536);
        float dl[4], dh[4], el[4], eh[4];
        mma_z(dl, p0.x, p0.y, p0.z, p0.w, k0.x, k0.y); mma_z(dh, p0.x, p0.y, p0.z, p0.w, k0.z, k0.w);
        mma_z(el, p1.x, p1.y, p1.z, p1.w, k1.x, k1.y); mma_z(eh, p1.x, p1.y, p1.z, p1.w, k1.z, k1.w);
        mma16816(dl, p2.x, p2.y, p2.z, p2.w, k2.x, k2.y); mma16816(dh, p2.x, p2.y, p2.z, p2.w, k2.z, k2.w);
        mma1688(el, p3.x, p3.y, k3.x); mma1688(eh, p3.x, p3.y, k3.y);
        sts64f(lq + QOFF(red) + 8, (dl[0] + dh[2]) + (el[0] + eh[2]), (dl[1] + dh[3]) + (el[1] + eh[3]));
        BAR_SYNC(14, 128);
        float2 t0 = lds64f(l16 + QOFF(red) + 8), t1 = lds64f(l16 + QOFF(red) + 8 + QB), t2 = lds64f(l16 + QOFF(red) + 8 + 2 * QB), t3 = lds64f(l16 + QOFF(red) + 8 + 3 * QB);
        st_async2(dst_sx, (t0.x + t1.x) + (t2.x + t3.x), (t0.y + t1.y) + (t2.y + t3.y), dst_bar);
      }
      STAMP(9);
      FENCE(6);
      {
        uint32_t m = amax2(amax2(amax2(amax2(0u, p0.x, p0.y), p0.z, p0.w), p1.x, p1.y), p1.z, p1.w);
        m = amax2(amax2(amax2(m, p2.x, p2.y), p2.z, p2.w), p3.x, p3.y);
        m = max(m & 0xffffu, m >> 16);
        m = __reduce_max_sync(0xffffffffu, m);
        sts32(sb + OFF(smax) + q * 4, m);
      }
      BAR_ARRIVE(9, 256);
      uint4 w6a = lds128(ws), w6b = lds128(ws + 512);
      BAR_SYNC_R(10 + q, 64);
      FENCE(7);
      STAMP(10);
      const uint32_t b[14] = {p0.x, p0.y, p0.z, p0.w, p1.x, p1.y, p1.z, p1.w, p2.x, p2.y, p2.z, p2.w, p3.x, p3.y};
      float acc[7][4];
      B2(0); B2(1); B2(2); B2(3); B2(4); B2(5); B2(6);
      FENCE(8);
#define UP(nt) pack_bf16(acc[(nt) >> 1][((nt) & 1) * 2], acc[(nt) >> 1][((nt) & 1) * 2 + 1])
#pragma unroll
      for (int k = 0; k < 7; k++)
#pragma unroll
        for (int t = 0; t < 4; t++) MMW(acc[3 - t], W[k * 6 + 3 - t], b[2 * k], b[2 * k + 1], k == 0);
      { uint32_t u6 = UP(6), u7 = UP(7);
        sts128(uq + 1024, UP(8), UP(9), UP(10), u7); sts128(uq + 1536, UP(11), UP(12), UP(13), u7);
        sts128(uq + 512, UP(3), UP(4), UP(5), u6); sts128(uq, UP(0), UP(1), UP(2), u6); }
      BAR_ARRIVE(3, 256);
      STAMP(11);
      const float inv = __uint_as_float(lds32(sb + OFF(sinv) + (s & 1) * 4));
      BAR_SYNC(4, 384);
      {
        const int nt0 = q < 2 ? q * 3 : 8 + (q - 2) * 3, nts = 6 + (q >> 1);
        uint32_t ub = l16 + QOFF(uQ) + q * 512; asm volatile("" : "+r"(ub));
        uint4 u0 = lds128(ub), u1 = lds128(ub + QB), u2 = lds128(ub + 2 * QB), u3 = lds128(ub + 3 * QB);
        auto us = [&](uint32_t a, uint32_t b, uint32_t c, uint32_t d) { return pack_bf16(((bf_lo(a) + bf_lo(b)) + (bf_lo(c) + bf_lo(d))) * inv, ((bf_hi(a) + bf_hi(b)) + (bf_hi(c) + bf_hi(d))) * inv); };
        uint32_t* uf = (uint32_t*)((char*)(g_UF + ((s * NH + h) * 56 + 14 * j) * 32) + ((l16 - sb) >> 2));
        { uf[(nt0 + 0) * 32] = us(u0.x, u1.x, u2.x, u3.x); uf[(nt0 + 1) * 32] = us(u0.y, u1.y, u2.y, u3.y); uf[(nt0 + 2) * 32] = us(u0.z, u1.z, u2.z, u3.z);
        if ((q & 1) == 0) uf[nts * 32] = us(u0.w, u1.w, u2.w, u3.w); }
      }
      {
        const uint32_t xb = l16 + OFF(xf) + st * 7168;
        uint4 k0 = lds128(lq + QOFF(kq)), k1 = lds128(lq + QOFF(kq) + 512), k2 = lds128(lq + QOFF(kq) + 1024); uint2 k3 = lds64(lq + QOFF(kq) + 1536);
        const uint32_t kk[14] = {k0.x, k0.y, k0.z, k0.w, k1.x, k1.y, k1.z, k1.w, k2.x, k2.y, k2.z, k2.w, k3.x, k3.y};
        float y[2][4];
#pragma unroll
        for (int f = 0; f < 7; f++)
#pragma unroll
          for (int m = 0; m < 2; m++) {
            uint4 xa = lds128(xb + (f * 2 + m) * 512);
            MMW(y[m], xa, kk[2 * f], kk[2 * f + 1], f == 0);
          }
        sts128(lq + QOFF(xred), __float_as_uint(y[0][0]), __float_as_uint(y[0][1]), __float_as_uint(y[0][2]), __float_as_uint(y[0][3]));
        sts128(lq + QOFF(xred) + 512, __float_as_uint(y[1][0]), __float_as_uint(y[1][1]), __float_as_uint(y[1][2]), __float_as_uint(y[1][3]));
        BAR_SYNC(14, 128);
        if (q < 2) {
          uint32_t xr = l16 + QOFF(xred) + q * 512; asm volatile("" : "+r"(xr));
          float4 t0 = lds128f(xr), t1 = lds128f(xr + QB), t2 = lds128f(xr + 2 * QB), t3 = lds128f(xr + 3 * QB);
          *(float4*)((char*)(g_SXM + ((((s * NH + h) * 4 + j) * 2 + q) * 32)) + (l16 - sb)) = make_float4(((t0.x + t1.x) + (t2.x + t3.x)) * inv, ((t0.y + t1.y) + (t2.y + t3.y)) * inv, ((t0.z + t1.z) + (t2.z + t3.z)) * inv, ((t0.w + t1.w) + (t2.w + t3.w)) * inv);
        } else if (q == 3 && s + NST < NSEG) {
          if (elect1()) issue_loads(sb, s + NST, h, j);
          __syncwarp();
        }
      }
    }
  } else {
    asm volatile("setmaxnreg.dec.sync.aligned.u32 72;");
    const int lane = opaque_lane();
    const uint32_t l16 = sb + lane * 16;
    const int nt0 = q < 2 ? q * 3 : 8 + (q - 2) * 3, nts = 6 + (q >> 1);
    const float bmax = g_bmax;
    float inv = g_inv0;
    uint32_t sc_bf; { uint32_t t = (0x7f000000u - __float_as_uint(inv)) >> 16; sc_bf = t | (t << 16); }
    uint4* redp = acc_ptr(1, j * 4 + q, lane);
#pragma unroll 1
    for (int s = 0; s < NSEG; s++) {
      const int st = s & (NST - 1);
      float ox[8];
      float mx, nsc;
      const float c1 = LOG2E * inv;
      {
        const uint32_t vb = l16 + OFF(vf) + st * 7168;
        wait_bar1(bar_ld + 8 * st, (s / NST) & 1);
        uint4 v0 = lds128(vb + nt0 * 512), v1 = lds128(vb + nt0 * 512 + 512), v2 = lds128(vb + nt0 * 512 + 1024), v3 = lds128(vb + nts * 512);
        BAR_SYNC(9, 256);
        {
          uint4 m4 = lds128(sb + OFF(smax));
          uint32_t mb = max(max(m4.x, m4.y), max(m4.z, m4.w));
          float mh = fmaxf(__uint_as_float(mb << 16) * inv, __uint_as_float(lds32(sb + OFF(xmax) + s * 4)));
          float bound = mh * bmax;
          int e = (int)(__float_as_uint(bound) >> 23) - 127 + 10;
          int se = min(max(15 - e, -100), 100);
          nsc = __uint_as_float((uint32_t)(127 + se) << 23);
        }
        wait_bar1(bar_sx, s & 1);
        STAMP(12);
        float4 x0 = lds128f(l16 + OFF(sx)), x1 = lds128f(l16 + OFF(sx) + 512);
        float sx[8] = {x0.x, x0.y, x0.z, x0.w, x1.x, x1.y, x1.z, x1.w};
        mx = fmaxf(fmaxf(fmaxf(sx[0], sx[1]), fmaxf(sx[2], sx[3])), fmaxf(fmaxf(sx[4], sx[5]), fmaxf(sx[6], sx[7])));
        mx = fmaxf(mx, __shfl_xor_sync(0xffffffffu, mx, 1)); mx = fmaxf(mx, __shfl_xor_sync(0xffffffffu, mx, 2));
        mx *= c1;
#pragma unroll
        for (int i = 0; i < 8; i++) sx[i] = ex2(fmaf(sx[i], c1, -mx));
        uint32_t p0 = pack_bf16(sx[0], sx[1]), p1 = pack_bf16(sx[2], sx[3]), p2 = pack_bf16(sx[4], sx[5]), p3 = pack_bf16(sx[6], sx[7]);
        float o[4], r[4];
        mma_z(o, p0, p2, p1, p3, v0.x, v0.y); mma_z(r, p0, p2, p1, p3, v0.z, v0.w); ox[0] = o[0] + r[2]; ox[1] = o[1] + r[3];
        mma_z(o, p0, p2, p1, p3, v1.x, v1.y); mma_z(r, p0, p2, p1, p3, v1.z, v1.w); ox[2] = o[0] + r[2]; ox[3] = o[1] + r[3];
        mma_z(o, p0, p2, p1, p3, v2.x, v2.y); mma_z(r, p0, p2, p1, p3, v2.z, v2.w); ox[4] = o[0] + r[2]; ox[5] = o[1] + r[3];
        mma_z(o, p0, p2, p1, p3, v3.x, v3.y); mma_z(r, p0, p2, p1, p3, v3.z, v3.w); ox[6] = (q & 1) ? o[1] + r[3] : o[0] + r[2];
        mma_z(o, p0, p2, p1, p3, 0x3f803f80u, 0x3f803f80u); ox[7] = o[0] + o[2];
      }
      STAMP(5);
      wait_bar1(bar_sm, s & 1);
      STAMP(7);
      uint4 u0, u1, u2, u3;
      {
        float4 t0 = lds128f(l16 + OFF(sm)), t1 = lds128f(l16 + OFF(sm) + 512);
        float s0 = ((t0.x + t0.z) + (t1.x + t1.z)) * inv * c1, s1 = ((t0.y + t0.w) + (t1.y + t1.w)) * inv * c1;
        float m = fmaxf(fmaxf(s0, s1), mx);
        m = fmaxf(m, __shfl_xor_sync(0xffffffffu, m, 1)); m = fmaxf(m, __shfl_xor_sync(0xffffffffu, m, 2));
        FENCE(10);
        BAR_SYNC(3, 256);
        const uint32_t ub = l16 + QOFF(uQ) + q * 512;
        u0 = lds128(ub); u1 = lds128(ub + QB); u2 = lds128(ub + 2 * QB); u3 = lds128(ub + 3 * QB);
        STAMP(6);
        float e0 = ex2(s0 - m), e1 = ex2(s1 - m), al = ex2(mx - m);
        uint32_t pm = pack_bf16(e0 * inv, e1 * inv);
        float z[4], ya[4], yb[4], yc[4], yd[4];
        mma_z(z, pm, 0u, 0u, pm, sc_bf, sc_bf);
        mma_z(ya, pm, 0u, 0u, pm, u0.x, u0.y); mma_z(yb, pm, 0u, 0u, pm, u0.z, u0.w);
        mma_z(yc, pm, 0u, 0u, pm, u1.x, u1.y); mma_z(yd, pm, 0u, 0u, pm, u1.z, u1.w);
        mma16816(ya, pm, 0u, 0u, pm, u2.x, u2.y); mma16816(yb, pm, 0u, 0u, pm, u2.z, u2.w);
        mma16816(yc, pm, 0u, 0u, pm, u3.x, u3.y); mma16816(yd, pm, 0u, 0u, pm, u3.z, u3.w);
        float iz; asm("rcp.approx.ftz.f32 %0, %1;" : "=f"(iz) : "f"(fmaf(ox[7], al, z[0])));
        iz *= nsc;
#pragma unroll
        for (int i = 0; i < 7; i++) ox[i] *= al;
        const float y6 = (q & 1) ? yb[3] + yd[3] : yb[2] + yd[2];
        red_h8(redp, pack_f16(((ya[0] + ox[0]) + yc[0]) * iz, ((ya[1] + ox[1]) + yc[1]) * iz), pack_f16(((ya[2] + ox[2]) + yc[2]) * iz, ((ya[3] + ox[3]) + yc[3]) * iz),
               pack_f16(((yb[0] + ox[4]) + yd[0]) * iz, ((yb[1] + ox[5]) + yd[1]) * iz), pack_f16((y6 + ox[6]) * iz, 1.f));
      }
      const float ninv = __uint_as_float(0x7f000000u - __float_as_uint(nsc));
      BAR_ARRIVE(4, 384);
      STAMP(8);
      if (q == 0) sts32(sb + OFF(sinv) + ((s + 1) & 1) * 4, __float_as_uint(ninv));
      redp += (s & 1) ? 32 : (1024 - 32);
      inv = ninv; { uint32_t t = __float_as_uint(nsc) >> 16; sc_bf = t | (t << 16); }
    }
  }
  asm volatile("barrier.cluster.arrive.release.aligned;\nbarrier.cluster.wait.acquire.aligned;" ::: "memory");
}

__global__ void n_xf(const bf16* x) {
  int i = blockIdx.x * blockDim.x + threadIdx.x;
  if (i >= NSEG * 4 * 14 * 32) return;
  int lane = i & 31, r = i >> 5, m = r & 1; r >>= 1; int f = r % 7; r /= 7; int j = r & 3, seg = r >> 2;
  int c0 = f == 6 ? 96 : (f & ~1) * 16 + (f & 1) * 8, c1 = f == 6 ? 104 : (f | 1) * 16 + (f & 1) * 8;
  const bf16* r0 = x + (seg * 32 + m * 16 + (lane >> 2)) * DM + j * 112 + (lane & 3) * 2;
  const bf16* r1 = r0 + 8 * DM;
  g_XF[i] = make_uint4(*(const uint32_t*)(r0 + c0), *(const uint32_t*)(r1 + c0), *(const uint32_t*)(r0 + c1), *(const uint32_t*)(r1 + c1));
}

__global__ void n_seed(const bf16* mem0) {
  __shared__ unsigned smx;
  if (threadIdx.x == 0) smx = 0;
  __syncthreads();
  float m = 0.f;
  for (int i = threadIdx.x; i < 8 * DM; i += 512) m = fmaxf(m, fabsf(b2f(mem0[i])));
  atomicMax(&smx, __float_as_uint(m));
  __syncthreads();
  int e = (int)(smx >> 23) - 127 + 1;
  int se = min(max(15 - e, -100), 100);
  float sc = __uint_as_float((uint32_t)(127 + se) << 23);
  if (threadIdx.x == 0) g_inv0 = __uint_as_float((uint32_t)(127 - se) << 23);
  int vec = threadIdx.x >> 5, lane = threadIdx.x & 31, j = vec >> 2, q = vec & 3;
  int nt0 = q < 2 ? q * 3 : 8 + (q - 2) * 3, nts = 6 + (q >> 1);
  const bf16* r = mem0 + (lane >> 2) * DM + j * 112 + (lane & 3) * 2;
  auto val = [&](int nt, int e2) { return b2f(r[nt * 8 + e2]) * sc; };
  *acc_ptr(0, vec, lane) = make_uint4(pack_f16(val(nt0, 0), val(nt0, 1)), pack_f16(val(nt0 + 1, 0), val(nt0 + 1, 1)), pack_f16(val(nt0 + 2, 0), val(nt0 + 2, 1)), pack_f16(val(nts, q & 1), 16.f));
}

__global__ void n_stats(const bf16* x) {
  if (blockIdx.x < 64) {
    float m = 0.f;
    for (int i = threadIdx.x; i < 32 * DM; i += 256) m = fmaxf(m, fabsf(b2f(x[blockIdx.x * 32 * DM + i])));
    atomicMax((unsigned*)&g_xmax[blockIdx.x], __float_as_uint(m));
  } else {
    int r = (blockIdx.x - 64) * 256 + threadIdx.x;
    if (r < NH * DM) { float a = 0.f; for (int k = 0; k < DM; k++) { float v = wf_elem(1, r / DM, r % DM, k); a += v * v; } atomicMax((unsigned*)&g_bmax, __float_as_uint(sqrtf(a))); }
  }
}

int g_poll_delay = POLL_DELAY;
extern "C" void kernel_launch(void* const* d_in, const int* in_sizes, int n_in, void* d_out, int out_size) {
  const bf16* x = (const bf16*)d_in[0];
  const bf16* wqkv = (const bf16*)d_in[1];
  const bf16* wphi = (const bf16*)d_in[2];
  const bf16* wo_a = (const bf16*)d_in[3];
  const bf16* mem0 = (const bf16*)d_in[5];
  const bf16* Wq = (const bf16*)d_in[6];
  const bf16* Wk = (const bf16*)d_in[7];
  const bf16* Wv = (const bf16*)d_in[8];
  const bf16* Wo = (const bf16*)d_in[9];
  const bf16* gate_w = (const bf16*)d_in[11];
  bf16* out = (bf16*)d_out;
  cudaFuncSetAttribute(r_kernel, cudaFuncAttributeMaxDynamicSharedMemorySize, (int)sizeof(RSmem));
  n_zero<<<(NSEG * 40 * 32 + 255) / 256, 256>>>();
  n_prep<<<(2 * NH * 28 * 28 * 32 + 255) / 256, 256>>>(Wq, Wk, Wv, Wo);
  n_stats<<<64 + 28, 256>>>(x);
  n_seed<<<1, 512>>>(mem0);
  n_xf<<<NSEG * 4 * 14 * 32 / 256, 256>>>(x);
  n_xgemm<<<2 * NH * 28 * NSEG * 32 / 256, 256>>>(x);
  r_kernel<<<64, 384, sizeof(RSmem)>>>(mem0, g_poll_delay);
  n_qkv<<<(S_LEN * 1344 + 255) / 256, 256>>>(x, wqkv);
  n_phi<<<(S_LEN * 2 * NH + 255) / 256, 256>>>(wphi);
  n_kv<<<(32 * NH * 56 * 29 + 255) / 256, 256>>>();
  n_oa<<<(S_LEN * DM + 255) / 256, 256>>>();
  n_x3<<<NSEG, 512>>>(x, wo_a, gate_w, out);
}
```

```cpp
#include <cuda_runtime.h>
#include <cuda_bf16.h>
#include <stdint.h>
#include <stddef.h>

typedef __nv_bfloat16 bf16;
#define S_LEN 2048
#define DM 448
#define NH 16
#define NSEG 64
#define SPIN_LIMIT (1 << 22)

__device__ uint4 g_WF[2 * NH * 28 * 28 * 32];
__device__ uint4 g_KF[NSEG * NH * 4 * 4 * 4 * 32];
__device__ uint4 g_VF[NSEG * NH * 56 * 32];
__device__ float4 g_SXM[NSEG * NH * 4 * 2 * 32];
__device__ uint4 g_XF[NSEG * 4 * 14 * 32];
__device__ uint32_t g_UF[NSEG * NH * 56 * 32];
__device__ uint4 g_ACC16[(NSEG + 2) * 16 * 32];
__device__ float g_xmax[NSEG];
__device__ float g_bmax;
__device__ float g_inv0;
__device__ float g_qkv[S_LEN * 1344];
__device__ float g_phiq[S_LEN * NH * 56];
__device__ float g_phik[S_LEN * NH * 56];
__device__ float g_kv[NH * 56 * 29];
__device__ float g_oa[S_LEN * DM];
__device__ int g_err;
__device__ unsigned g_ts[64 * 64 * 16];

__device__ __forceinline__ uint32_t pack_bf16(float lo, float hi) {
  uint32_t r; asm("cvt.rn.bf16x2.f32 %0, %1, %2;" : "=r"(r) : "f"(hi), "f"(lo)); return r;
}
__device__ __forceinline__ float bf_lo(uint32_t v) { return __uint_as_float(v << 16); }
__device__ __forceinline__ float bf_hi(uint32_t v) { return __uint_as_float(v & 0xffff0000u); }
__device__ __forceinline__ float b2f(bf16 v) { return __bfloat162float(v); }

__global__ void n_prep(const bf16* Wq, const bf16* Wk, const bf16* Wv, const bf16* Wo) {
  int idx = blockIdx.x * blockDim.x + threadIdx.x;
  if (idx >= 2 * NH * 28 * 28 * 32) return;
  int lane = idx & 31, r = idx >> 5;
  int ks = r % 28; r /= 28; int tile = r % 28; r /= 28; int h = r % NH; int mat = r / NH;
  int g = lane >> 2, tq = lane & 3;
  float v[8];
  for (int i = 0; i < 8; i++) {
    int row = tile * 16 + g + ((i >> 1) & 1) * 8;
    int col = ks * 16 + tq * 2 + (i & 1) + (i >> 2) * 8;
    float acc = 0.f;
    if (mat == 0) { for (int e = 0; e < 256; e++) acc += b2f(Wq[(row * NH + h) * 256 + e]) * b2f(Wk[(col * NH + h) * 256 + e]); acc *= 0.0625f; }
    else { for (int e = 0; e < 256; e++) acc += b2f(Wo[(h * 256 + e) * DM + row]) * b2f(Wv[(col * NH + h) * 256 + e]); }
    v[i] = acc;
  }
  g_WF[idx] = make_uint4(pack_bf16(v[0], v[1]), pack_bf16(v[2], v[3]), pack_bf16(v[4], v[5]), pack_bf16(v[6], v[7]));
}
__device__ __forceinline__ float wf_elem(int mat, int h, int row, int col) {
  int tile = row >> 4, ks = col >> 4, rr = row & 15, cc = col & 15;
  int lane = (rr & 7) * 4 + ((cc & 7) >> 1);
  int reg = (rr >> 3) + (cc >> 3) * 2;
  uint32_t w = ((const uint32_t*)g_WF)[((((mat * NH + h) * 28 + tile) * 28 + ks) * 32 + lane) * 4 + reg];
  return (cc & 1) ? bf_hi(w) : bf_lo(w);
}
__device__ __forceinline__ void mma16816(float* d, uint32_t a0, uint32_t a1, uint32_t a2, uint32_t a3, uint32_t b0, uint32_t b1) {
  asm volatile("mma.sync.aligned.m16n8k16.row.col.f32.bf16.bf16.f32 {%0,%1,%2,%3}, {%4,%5,%6,%7}, {%8,%9}, {%0,%1,%2,%3};"
    : "+f"(d[0]), "+f"(d[1]), "+f"(d[2]), "+f"(d[3]) : "r"(a0), "r"(a1), "r"(a2), "r"(a3), "r"(b0), "r"(b1));
}
__device__ __forceinline__ void mma1688(float* d, uint32_t a0, uint32_t a1, uint32_t b0) {
  asm volatile("mma.sync.aligned.m16n8k8.row.col.f32.bf16.bf16.f32 {%0,%1,%2,%3}, {%4,%5}, {%6}, {%0,%1,%2,%3};"
    : "+f"(d[0]), "+f"(d[1]), "+f"(d[2]), "+f"(d[3]) : "r"(a0), "r"(a1), "r"(b0));
}
__device__ __forceinline__ uint32_t movm(uint32_t a) { uint32_t d; asm volatile("movmatrix.sync.aligned.m8n8.trans.b16 %0, %1;" : "=r"(d) : "r"(a)); return d; }

__global__ void n_xgemm(const bf16* x) {
  int wid = (blockIdx.x * blockDim.x + threadIdx.x) >> 5, lane = threadIdx.x & 31;
  int seg = wid % NSEG; int r = wid / NSEG;
  int tile = r % 28; r /= 28; int h = r % NH; int mat = r / NH;
  if (mat >= 2) return;
  int g = lane >> 2, tq = lane & 3;
  float d[4][4] = {};
  const uint4* wf = g_WF + (((mat * NH + h) * 28 + tile) * 28) * 32 + lane;
  for (int ks = 0; ks < 28; ks++) {
    uint4 a = wf[ks * 32];
    for (int kg = 0; kg < 4; kg++) {
      const uint32_t* xr = (const uint32_t*)(x + (seg * 32 + kg * 8 + g) * DM + ks * 16 + tq * 2);
      mma16816(d[kg], a.x, a.y, a.z, a.w, xr[0], xr[4]);
    }
  }
  if (mat == 0) {
    for (int kg = 0; kg < 4; kg++) {
      uint32_t b0 = movm(pack_bf16(d[kg][0], d[kg][1])), b1 = movm(pack_bf16(d[kg][2], d[kg][3]));
      int jj = tile / 7, i = tile % 7;
      uint32_t* dst = (uint32_t*)&g_KF[((((seg * NH + h) * 4 + kg) * 4 + jj) * 4 + (i >> 1)) * 32 + lane];
      if (i == 6) { dst[0] = b0; dst[1] = b1; } else { dst[i & 1] = b0; dst[2 + (i & 1)] = b1; }
    }
  } else {
    g_VF[((seg * NH + h) * 56 + tile * 2) * 32 + lane] = make_uint4(pack_bf16(d[0][0], d[0][1]), pack_bf16(d[1][0], d[1][1]), pack_bf16(d[2][0], d[2][1]), pack_bf16(d[3][0], d[3][1]));
    g_VF[((seg * NH + h) * 56 + tile * 2 + 1) * 32 + lane] = make_uint4(pack_bf16(d[0][2], d[0][3]), pack_bf16(d[1][2], d[1][3]), pack_bf16(d[2][2], d[2][3]), pack_bf16(d[3][2], d[3][3]));
  }
}
__global__ void n_zero() {
  int i = blockIdx.x * blockDim.x + threadIdx.x;
  if (i < (NSEG + 2) * 16 * 32) g_ACC16[i] = make_uint4(0, 0, 0, 0);
  if (i < NSEG) g_xmax[i] = 0.f;
  if (i == 0) g_bmax = 0.f;
  if (i < NH * 56 * 29) g_kv[i] = 0.f;
}
__global__ void n_qkv(const bf16* x, const bf16* w) {
  int i = blockIdx.x * blockDim.x + threadIdx.x;
  if (i >= S_LEN * 1344) return;
  int n = i % 1344, t = i / 1344;
  float acc = 0.f;
  for (int k = 0; k < DM; k++) acc += b2f(x[t * DM + k]) * b2f(w[k * 1344 + n]);
  g_qkv[i] = acc;
}
__global__ void n_phi(const bf16* wphi) {
  int i = blockIdx.x * blockDim.x + threadIdx.x;
  if (i >= S_LEN * 2 * NH) return;
  int h = i % NH, which = (i / NH) % 2, t = i / (2 * NH);
  float p[28]; float mx = -1e30f, mn = 1e30f;
  for (int f = 0; f < 28; f++) {
    float acc = 0.f;
    for (int d = 0; d < 28; d++) acc += g_qkv[t * 1344 + which * 448 + h * 28 + d] * b2f(wphi[(h * 28 + d) * 28 + f]);
    p[f] = acc; mx = fmaxf(mx, acc); mn = fminf(mn, acc);
  }
  float s1 = 0.f, s2 = 0.f;
  for (int f = 0; f < 28; f++) { s1 += __expf(p[f] - mx); s2 += __expf(mn - p[f]); }
  float* o = (which ? g_phik : g_phiq) + (t * NH + h) * 56;
  for (int f = 0; f < 28; f++) { o[f] = __expf(p[f] - mx) / s1; o[28 + f] = __expf(mn - p[f]) / s2; }
}
__global__ void n_kv() {
  int i = blockIdx.x * blockDim.x + threadIdx.x;
  if (i >= 32 * NH * 56 * 29) return;
  int d = i % 29, f = (i / 29) % 56, h = (i / (29 * 56)) % NH, ch = i / (29 * 56 * NH);
  float acc = 0.f;
  for (int t = ch * 64; t < ch * 64 + 64; t++) acc += g_phik[(t * NH + h) * 56 + f] * (d < 28 ? g_qkv[t * 1344 + 896 + h * 28 + d] : 1.f);
  atomicAdd(&g_kv[(h * 56 + f) * 29 + d], acc);
}
__global__ void n_oa() {
  int i = blockIdx.x * blockDim.x + threadIdx.x;
  if (i >= S_LEN * DM) return;
  int c = i % DM, t = i / DM, h = c / 28, d = c % 28;
  float num = 0.f, den = 0.f;
  for (int f = 0; f < 56; f++) { float p = g_phiq[(t * NH + h) * 56 + f]; num += p * g_kv[(h * 56 + f) * 29 + d]; den += p * g_kv[(h * 56 + f) * 29 + 28]; }
  g_oa[i] = num / (den + 1e-6f);
}

__global__ void __launch_bounds__(512) n_x3(const bf16* x, const bf16* wo, const bf16* gate_w, bf16* out) {
  __shared__ uint32_t sP[NH][2][32][10];
  __shared__ float sG[32];
  int seg = blockIdx.x, w = threadIdx.x >> 5, lane = threadIdx.x & 31, g = lane >> 2, tq = lane & 3;
  for (int r = w; r < 32; r += 16) {
    float acc = 0.f;
    for (int k = lane; k < DM; k += 32) acc += b2f(x[(seg * 32 + r) * DM + k]) * b2f(gate_w[k]);
    for (int o = 16; o; o >>= 1) acc += __shfl_xor_sync(0xffffffffu, acc, o);
    if (lane == 0) sG[r] = 1.f / (1.f + __expf(-acc));
  }
  {
    int h = w;
    float s[2][5][4] = {};
    for (int ct = 0; ct < 28; ct++) {
      uint32_t a[2][4];
      for (int m = 0; m < 2; m++) {
        const uint32_t* r0 = (const uint32_t*)(x + (seg * 32 + m * 16 + g) * DM + ct * 16 + tq * 2);
        const uint32_t* r1 = (const uint32_t*)(x + (seg * 32 + m * 16 + g + 8) * DM + ct * 16 + tq * 2);
        a[m][0] = r0[0]; a[m][1] = r1[0]; a[m][2] = r0[4]; a[m][3] = r1[4];
      }
      int j = ct / 7, i = ct % 7;
      for (int kg = 0; kg < 4; kg++) {
        const uint32_t* src = (const uint32_t*)&g_KF[((((seg * NH + h) * 4 + kg) * 4 + j) * 4 + (i >> 1)) * 32 + lane];
        uint2 b = i == 6 ? make_uint2(src[0], src[1]) : make_uint2(src[i & 1], src[2 + (i & 1)]);
        for (int m = 0; m < 2; m++) mma16816(s[m][1 + kg], a[m][0], a[m][1], a[m][2], a[m][3], b.x, b.y);
      }
    }
    for (int m = 0; m < 2; m++) for (int j = 0; j < 4; j++) {
      float4 t = g_SXM[(((seg * NH + h) * 4 + j) * 2 + m) * 32 + lane];
      s[m][0][0] += t.x; s[m][0][1] += t.y; s[m][0][2] += t.z; s[m][0][3] += t.w;
    }
    for (int m = 0; m < 2; m++) for (int hf = 0; hf < 2; hf++) {
      int t = m * 16 + hf * 8 + g;
      float v[10]; float mx = -1e30f;
      for (int n = 0; n < 5; n++) for (int e = 0; e < 2; e++) {
        float val = s[m][n][hf * 2 + e];
        if (n > 0 && (n - 1) * 8 + tq * 2 + e > t) val = -1e30f;
        v[n * 2 + e] = val; mx = fmaxf(mx, val);
      }
      mx = fmaxf(mx, __shfl_xor_sync(0xffffffffu, mx, 1)); mx = fmaxf(mx, __shfl_xor_sync(0xffffffffu, mx, 2));
      float z = 0.f;
      for (int i = 0; i < 10; i++) { v[i] = __expf(v[i] - mx); z += v[i]; }
      z += __shfl_xor_sync(0xffffffffu, z, 1); z += __shfl_xor_sync(0xffffffffu, z, 2);
      float iz = 1.f / z;
      sP[h][m][lane][hf] = pack_bf16(v[0] * iz, v[1] * iz);
      sP[h][m][lane][2 + hf] = pack_bf16(v[2] * iz, v[3] * iz);
      sP[h][m][lane][4 + hf] = pack_bf16(v[4] * iz, v[5] * iz);
      sP[h][m][lane][6 + hf] = pack_bf16(v[6] * iz, v[7] * iz);
      sP[h][m][lane][8 + hf] = pack_bf16(v[8] * iz, v[9] * iz);
    }
  }
  __syncthreads();
  if (w < 14) {
    float o[2][4][4] = {};
    for (int h = 0; h < NH; h++) {
      for (int n = 0; n < 4; n++) {
        int nt = w * 4 + n;
        uint4 v = g_VF[((seg * NH + h) * 56 + nt) * 32 + lane];
        uint32_t u = g_UF[((seg * NH + h) * 56 + nt) * 32 + lane];
        for (int m = 0; m < 2; m++) {
          const uint32_t* p = sP[h][m][lane];
          mma1688(o[m][n], p[0], p[1], u);
          mma16816(o[m][n], p[2], p[3], p[4], p[5], v.x, v.y);
          mma16816(o[m][n], p[6], p[7], p[8], p[9], v.z, v.w);
        }
      }
    }
    for (int m = 0; m < 2; m++) for (int n = 0; n < 4; n++) for (int i = 0; i < 4; i++) {
      int r = m * 16 + (i >> 1) * 8 + g, c = (w * 4 + n) * 8 + tq * 2 + (i & 1);
      int t = seg * 32 + r;
      float a = 0.f;
      for (int k = 0; k < DM; k++) a += g_oa[t * DM + k] * b2f(wo[k * DM + c]);
      float gt = sG[r];
      out[t * DM + c] = __float2bfloat16(gt * a + (1.f - gt) * o[m][n][i]);
    }
  }
}

__device__ __forceinline__ uint32_t smem_u32(const void* p) { return (uint32_t)__cvta_generic_to_shared(p); }
__device__ __forceinline__ uint32_t mapa(uint32_t a, uint32_t r) { uint32_t o; asm volatile("mapa.shared::cluster.u32 %0, %1, %2;" : "=r"(o) : "r"(a), "r"(r)); return o; }
__device__ __forceinline__ bool try_wait(uint32_t bar, uint32_t parity) {
  uint32_t ok; asm volatile("{\n.reg .pred p;\nmbarrier.try_wait.parity.shared::cta.b64 p, [%1], %2;\nselp.u32 %0, 1, 0, p;\n}" : "=r"(ok) : "r"(bar), "r"(parity) : "memory"); return ok; }
__device__ __forceinline__ void wait_bar(uint32_t bar, uint32_t parity) {
  int n = 0; while (!try_wait(bar, parity)) { if (++n > SPIN_LIMIT) { g_err = 1; break; } } }
__device__ __forceinline__ void arm_bar(uint32_t bar, uint32_t bytes) { asm volatile("mbarrier.arrive.expect_tx.shared::cta.b64 _, [%0], %1;" :: "r"(bar), "r"(bytes) : "memory"); }
__device__ __forceinline__ float4 ld_relaxed4(const void* p) { float4 v; asm volatile("ld.relaxed.gpu.global.v4.f32 {%0,%1,%2,%3}, [%4];" : "=f"(v.x), "=f"(v.y), "=f"(v.z), "=f"(v.w) : "l"(p) : "memory"); return v; }
__device__ __forceinline__ void red4(void* p, float a, float b, float c, float d) { asm volatile("red.relaxed.gpu.global.add.v4.f32 [%0], {%1,%2,%3,%4};" :: "l"(p), "f"(a), "f"(b), "f"(c), "f"(d) : "memory"); }
__device__ __forceinline__ void st_async2(uint32_t dst, float a, float b, uint32_t bar) { asm volatile("st.async.shared::cluster.mbarrier::complete_tx::bytes.v2.f32 [%0], {%1,%2}, [%3];" :: "r"(dst), "f"(a), "f"(b), "r"(bar) : "memory"); }
__device__ __forceinline__ void bulk_g2s(uint32_t dst, const void* src, uint32_t bytes, uint32_t bar) {
  asm volatile("cp.async.bulk.shared::cluster.global.mbarrier::complete_tx::bytes [%0], [%1], %2, [%3];" :: "r"(dst), "l"(src), "r"(bytes), "r"(bar) : "memory"); }
__device__ __forceinline__ unsigned clk() { unsigned c; asm volatile("mov.u32 %0, %%clock;" : "=r"(c) :: "memory"); return c; }
__device__ __forceinline__ float ex2(float x) { float y; asm("ex2.approx.ftz.f32 %0, %1;" : "=f"(y) : "f"(x)); return y; }

#define NST 4
struct QBlk {
  uint4 memF[4][32];
  uint4 wA[7][32], wB[7][32];
  uint4 kf[NST][4][32];
  float4 xred[2][32];
  float4 red[32];
  uint4 uQ[4][32];
  uint4 kq[4][32];
};
#define QB ((uint32_t)sizeof(QBlk))
#define QOFF(f) ((uint32_t)offsetof(QBlk, f))
struct RSmem {
  QBlk qb[4];
  uint4 vf[NST][14][32];
  uint4 xf[NST][14][32];
  float4 sx[2][32];
  float4 sm[2][32];
  uint32_t smax[4];
  float xmax[NSEG];
  float sinv[4];
  unsigned long long bar_ld[NST], bar_sx, bar_sm;
  unsigned ts[64 * 16];
};
#define LD_BYTES (8192 + 7168 + 7168)
#define POLL_DELAY 300
#define STAMP(i)
__device__ __forceinline__ void wait_slow(uint32_t bar, uint32_t parity) {
#pragma unroll 1
  for (int n = 0; n < SPIN_LIMIT; n++) if (try_wait(bar, parity)) return;
  g_err = 1;
}
__device__ __forceinline__ void wait_bar1(uint32_t bar, uint32_t parity) { if (!try_wait(bar, parity)) wait_slow(bar, parity); }
__device__ __forceinline__ uint4 ld_relaxed_u4(const void* p) { uint4 v; asm volatile("ld.relaxed.gpu.global.v4.u32 {%0,%1,%2,%3}, [%4];" : "=r"(v.x), "=r"(v.y), "=r"(v.z), "=r"(v.w) : "l"(p) : "memory"); return v; }
__device__ __forceinline__ void red_h8(void* p, uint32_t a, uint32_t b, uint32_t c, uint32_t d) { asm volatile("red.relaxed.gpu.global.add.noftz.v4.f16x2 [%0], {%1,%2,%3,%4};" :: "l"(p), "r"(a), "r"(b), "r"(c), "r"(d) : "memory"); }
__device__ __forceinline__ uint32_t pack_f16(float lo, float hi) { uint32_t r; asm("cvt.rn.f16x2.f32 %0, %1, %2;" : "=r"(r) : "f"(hi), "f"(lo)); return r; }
__device__ __forceinline__ uint32_t h2_to_bf2(uint32_t v) {
  float lo, hi; asm("{.reg .f16 l, h; mov.b32 {l, h}, %2; cvt.f32.f16 %0, l; cvt.f32.f16 %1, h;}" : "=f"(lo), "=f"(hi) : "r"(v)); return pack_bf16(lo, hi); }
__device__ __forceinline__ uint2 lds64(uint32_t a) { uint2 v; asm volatile("ld.shared.v2.u32 {%0,%1}, [%2];" : "=r"(v.x), "=r"(v.y) : "r"(a) : "memory"); return v; }
__device__ __forceinline__ float2 lds64f(uint32_t a) { float2 v; asm volatile("ld.shared.v2.f32 {%0,%1}, [%2];" : "=f"(v.x), "=f"(v.y) : "r"(a) : "memory"); return v; }
__device__ __forceinline__ uint4 lds128(uint32_t a) { uint4 v; asm volatile("ld.shared.v4.u32 {%0,%1,%2,%3}, [%4];" : "=r"(v.x), "=r"(v.y), "=r"(v.z), "=r"(v.w) : "r"(a) : "memory"); return v; }
__device__ __forceinline__ uint32_t lds32(uint32_t a) { uint32_t v; asm volatile("ld.shared.u32 %0, [%1];" : "=r"(v) : "r"(a) : "memory"); return v; }
__device__ __forceinline__ void sts64(uint32_t a, uint32_t x, uint32_t y) { asm volatile("st.shared.v2.u32 [%0], {%1,%2};" :: "r"(a), "r"(x), "r"(y) : "memory"); }
__device__ __forceinline__ void sts64f(uint32_t a, float x, float y) { asm volatile("st.shared.v2.f32 [%0], {%1,%2};" :: "r"(a), "f"(x), "f"(y) : "memory"); }
__device__ __forceinline__ void sts32(uint32_t a, uint32_t x) { asm volatile("st.shared.u32 [%0], %1;" :: "r"(a), "r"(x) : "memory"); }
__device__ __forceinline__ void mma_z(float* d, uint32_t a0, uint32_t a1, uint32_t a2, uint32_t a3, uint32_t b0, uint32_t b1) {
  asm volatile("mma.sync.aligned.m16n8k16.row.col.f32.bf16.bf16.f32 {%0,%1,%2,%3}, {%4,%5,%6,%7}, {%8,%9}, {%10,%10,%10,%10};"
    : "=f"(d[0]), "=f"(d[1]), "=f"(d[2]), "=f"(d[3]) : "r"(a0), "r"(a1), "r"(a2), "r"(a3), "r"(b0), "r"(b1), "f"(0.f));
}
__device__ __forceinline__ void mma8_z(float* d, uint32_t a0, uint32_t a1, uint32_t b0) {
  asm volatile("mma.sync.aligned.m16n8k8.row.col.f32.bf16.bf16.f32 {%0,%1,%2,%3}, {%4,%5}, {%6}, {%7,%7,%7,%7};"
    : "=f"(d[0]), "=f"(d[1]), "=f"(d[2]), "=f"(d[3]) : "r"(a0), "r"(a1), "r"(b0), "f"(0.f));
}
#define OFF(f) ((uint32_t)offsetof(RSmem, f))
#define BAR_SYNC(id, n) asm volatile("bar.sync %0, %1;" :: "n"(id), "n"(n) : "memory")
#define BAR_ARRIVE(id, n) asm volatile("bar.arrive %0, %1;" :: "n"(id), "n"(n) : "memory")

__device__ __forceinline__ void sts128(uint32_t a, uint32_t x, uint32_t y, uint32_t z, uint32_t w) { asm volatile("st.shared.v4.u32 [%0], {%1,%2,%3,%4};" :: "r"(a), "r"(x), "r"(y), "r"(z), "r"(w) : "memory"); }
template <int K>
__device__ __forceinline__ void kstep(const uint4 (&W)[42], float (&acc)[7][4], uint32_t b0, uint32_t b1, uint4& w6, uint32_t ws) {
#pragma unroll
  for (int t = 0; t < 6; t++) {
    const uint4& w = W[K * 6 + t];
    if (K == 0) mma_z(acc[t], w.x, w.y, w.z, w.w, b0, b1); else mma16816(acc[t], w.x, w.y, w.z, w.w, b0, b1);
  }
  if (K == 0) mma_z(acc[6], w6.x, w6.y, w6.z, w6.w, b0, b1); else mma16816(acc[6], w6.x, w6.y, w6.z, w6.w, b0, b1);
  if (K < 6) w6 = lds128(ws + (K + 1) * 512);
}
__device__ __forceinline__ uint4* acc_ptr(int step, int vec, int lane) { return g_ACC16 + (((step >> 1) * 16 + vec) * 2 + (step & 1)) * 32 + lane; }

__device__ __forceinline__ bool elect1() { uint32_t p; asm volatile("{.reg .pred p; elect.sync _|p, 0xffffffff; selp.u32 %0, 1, 0, p;}" : "=r"(p)); return p; }
__device__ __forceinline__ float4 lds128f(uint32_t a) { float4 v; asm volatile("ld.shared.v4.f32 {%0,%1,%2,%3}, [%4];" : "=f"(v.x), "=f"(v.y), "=f"(v.z), "=f"(v.w) : "r"(a) : "memory"); return v; }
__device__ __forceinline__ uint32_t amax2(uint32_t m, uint32_t x, uint32_t y) { return __vmaxu2(m, __vmaxu2(x & 0x7fff7fffu, y & 0x7fff7fffu)); }

#define FENCE(n) do { if (__builtin_expect((poll_delay >> (16 + (n))) & 1, 0)) { _Pragma("unroll 1") for (int i_ = poll_delay & 7; i_ > 0; i_--) asm volatile("nanosleep.u32 %0;" :: "n"(n) : "memory"); } } while (0)
#define BAR_SYNC_R(id, n) asm volatile("bar.sync %0, %1;" :: "r"(id), "n"(n) : "memory")
#define BAR_ARRIVE_R(id, n) asm volatile("bar.arrive %0, %1;" :: "r"(id), "n"(n) : "memory")
#define MMW(A, WW, B0, B1, first) do { if (first) mma_z(A, WW.x, WW.y, WW.z, WW.w, B0, B1); else mma16816(A, WW.x, WW.y, WW.z, WW.w, B0, B1); } while (0)
__device__ __forceinline__ void issue_loads(uint32_t sb, int s, int h, int j) {
  const int st = s & (NST - 1), s0 = s;
  const uint32_t bar = sb + OFF(bar_ld) + 8 * st;
  arm_bar(bar, LD_BYTES);
#pragma unroll
  for (int qq = 0; qq < 4; qq++) bulk_g2s(sb + qq * QB + QOFF(kf) + st * 2048, g_KF + ((s * NH + h) * 4 + j) * 512 + qq * 128, 2048, bar);
  bulk_g2s(sb + OFF(vf) + st * 7168, g_VF + ((s * NH + h) * 56 + 14 * j) * 32, 7168, bar);
  bulk_g2s(sb + OFF(xf) + st * 7168, g_XF + (s * 4 + j) * 448, 7168, bar);
  asm volatile("prefetch.global.L2 [%0];" :: "l"(acc_ptr(s0, h, j * 8)));
}
__device__ __forceinline__ int opaque_lane() { return __shfl_sync(0xffffffffu, threadIdx.x & 31, threadIdx.x & 31); }

__global__ void __cluster_dims__(4, 1, 1) __launch_bounds__(384, 1) r_kernel(const bf16* mem0, int poll_delay) {
  extern __shared__ __align__(128) unsigned char smem_raw[];
  RSmem& sm = *reinterpret_cast<RSmem*>(smem_raw);
  const int h = blockIdx.x >> 2, j = blockIdx.x & 3;
  const int w = __shfl_sync(0xffffffffu, threadIdx.x >> 5, 0), q = w & 3, role = w >> 2;
  const uint32_t sb = smem_u32(smem_raw);
  const uint32_t bar_ld = sb + OFF(bar_ld), bar_sx = sb + OFF(bar_sx), bar_sm = sb + OFF(bar_sm);
  if (threadIdx.x == 0) {
    for (int i = 0; i < NST; i++) asm volatile("mbarrier.init.shared::cta.b64 [%0], 1;" :: "r"(bar_ld + 8 * i));
    asm volatile("mbarrier.init.shared::cta.b64 [%0], 1;" :: "r"(bar_sx));
    asm volatile("mbarrier.init.shared::cta.b64 [%0], 1;" :: "r"(bar_sm));
    asm volatile("fence.mbarrier_init.release.cluster;" ::: "memory");
    arm_bar(bar_sx, 1024); arm_bar(bar_sm, 1024);
    for (int s = 0; s < NST; s++) issue_loads(sb, s, h, j);
    sm.sinv[0] = g_inv0;
  }
  if (threadIdx.x < NSEG) sm.xmax[threadIdx.x] = g_xmax[threadIdx.x];
  if (role < 2) {
    const int lane = threadIdx.x & 31;
    const uint4* wf = g_WF + (((role * NH + h) * 28 + 7 * j + 6) * 28 + 7 * q) * 32 + lane;
#pragma unroll
    for (int e = 0; e < 7; e++) (role ? sm.qb[q].wB : sm.qb[q].wA)[e][lane] = wf[e * 32];
  }
  asm volatile("barrier.cluster.arrive.release.aligned;\nbarrier.cluster.wait.acquire.aligned;" ::: "memory");
  const float LOG2E = 1.4426950408889634f;

  if (role == 0) {
    asm volatile("setmaxnreg.inc.sync.aligned.u32 224;");
    const int lane = opaque_lane();
    const uint32_t l16 = sb + lane * 16;
    uint4 W[42];
    {
      const uint4* wf = g_WF + ((h * 28 + 7 * j) * 28 + 7 * q) * 32 + lane;
#pragma unroll
      for (int k = 0; k < 7; k++)
#pragma unroll
        for (int t = 0; t < 6; t++) W[k * 6 + t] = wf[(t * 28 + k) * 32];
    }
    const uint32_t lq = l16 + q * QB, mj = l16 + j * QB;
#define ws (lq + QOFF(wA))
#define mq lq
    const uint32_t dst_sm = mapa(l16 + OFF(sm) + (j >> 1) * 512 + (j & 1) * 8, q), dst_bar = mapa(bar_sm, q);
    const uint4* p = acc_ptr(0, q * 4, lane);
#define KS(k) do { _Pragma("unroll") for (int t = 0; t < 6; t++) MMW(acc[t], W[(k) * 6 + t], b[2 * (k)], b[2 * (k) + 1], (k) == 0); \
        if ((k) & 1) { MMW(acc[6], w6b, b[2 * (k)], b[2 * (k) + 1], (k) == 0); if ((k) + 2 < 7) w6b = lds128(ws + ((k) + 2) * 512); } \
        else { MMW(acc[6], w6a, b[2 * (k)], b[2 * (k) + 1], (k) == 0); if ((k) + 2 < 7) w6a = lds128(ws + ((k) + 2) * 512); } } while (0)
#define B2(k) do { MMW(acc[4], W[(k) * 6 + 4], b[2 * (k)], b[2 * (k) + 1], (k) == 0); MMW(acc[5], W[(k) * 6 + 5], b[2 * (k)], b[2 * (k) + 1], (k) == 0); \
        if ((k) & 1) { MMW(acc[6], w6b, b[2 * (k)], b[2 * (k) + 1], (k) == 0); if ((k) + 2 < 7) w6b = lds128(ws + ((k) + 2) * 512); } \
        else { MMW(acc[6], w6a, b[2 * (k)], b[2 * (k) + 1], (k) == 0); if ((k) + 2 < 7) w6a = lds128(ws + ((k) + 2) * 512); } } while (0)
    wait_bar1(bar_ld, 0);
#pragma unroll 1
    for (int s = 0; s < NSEG; s++) {
      STAMP(0);
      uint4 v0 = ld_relaxed_u4(p), v1 = ld_relaxed_u4(p + 64), v2 = ld_relaxed_u4(p + 128), v3 = ld_relaxed_u4(p + 192);
      const uint32_t kb = lq + QOFF(kf) + (s & (NST - 1)) * 2048;
      uint4 k0 = lds128(kb), k1 = lds128(kb + 512), k2 = lds128(kb + 1024); uint2 k3 = lds64(kb + 1536);
      if (!__all_sync(0xffffffffu, __byte_perm(v0.w, v1.w, 0x7632) == 0x4C004C00u && __byte_perm(v2.w, v3.w, 0x7632) == 0x4C004C00u)) {
#pragma unroll 1
        for (int n = 0; n < SPIN_LIMIT; n++) {
          v0 = ld_relaxed_u4(p); v1 = ld_relaxed_u4(p + 64); v2 = ld_relaxed_u4(p + 128); v3 = ld_relaxed_u4(p + 192);
          if (__all_sync(0xffffffffu, __byte_perm(v0.w, v1.w, 0x7632) == 0x4C004C00u && __byte_perm(v2.w, v3.w, 0x7632) == 0x4C004C00u)) break;
        }
      }
      STAMP(1);
      uint32_t b[14];
      float dl[4], dh[4], el[4], eh[4];
      b[0] = h2_to_bf2(v0.x); b[1] = h2_to_bf2(v0.y); b[2] = h2_to_bf2(v0.z); b[3] = h2_to_bf2(v1.x);
      mma_z(dl, b[0], b[1], b[2], b[3], k0.x, k0.y); mma_z(dh, b[0], b[1], b[2], b[3], k0.z, k0.w);
      b[4] = h2_to_bf2(v1.y); b[5] = h2_to_bf2(v1.z);
      b[6] = h2_to_bf2(__byte_perm(v0.w, v1.w, 0x5410)); b[7] = h2_to_bf2(__byte_perm(v2.w, v3.w, 0x5410));
      mma_z(el, b[4], b[5], b[6], b[7], k1.x, k1.y); mma_z(eh, b[4], b[5], b[6], b[7], k1.z, k1.w);
      b[8] = h2_to_bf2(v2.x); b[9] = h2_to_bf2(v2.y); b[10] = h2_to_bf2(v2.z); b[11] = h2_to_bf2(v3.x);
      mma16816(dl, b[8], b[9], b[10], b[11], k2.x, k2.y); mma16816(dh, b[8], b[9], b[10], b[11], k2.z, k2.w);
      b[12] = h2_to_bf2(v3.y); b[13] = h2_to_bf2(v3.z);
      mma1688(el, b[12], b[13], k3.x); mma1688(eh, b[12], b[13], k3.y);
      float acc[7][4];
      uint4 w6a = lds128(ws), w6b;
      KS(0);
      sts64f(lq + QOFF(red) + 8, (dl[0] + dh[2]) + (el[0] + eh[2]), (dl[1] + dh[3]) + (el[1] + eh[3]));
      BAR_ARRIVE(14, 256);
      sts128(mq, b[0], b[1], b[2], b[3]); sts128(mq + 512, b[4], b[5], b[6], b[7]); sts128(mq + 1024, b[8], b[9], b[10], b[11]); sts64(mq + 1536, b[12], b[13]);
      w6b = lds128(ws + 512);
      FENCE(2);
      KS(1); KS(2); KS(3); KS(4); KS(5);
      FENCE(4);
      BAR_SYNC(1, 256);
      uint4 a0 = lds128(mj), a1 = lds128(mj + 512), a2 = lds128(mj + 1024); uint2 a3 = lds64(mj + 1536);
      KS(6);
      STAMP(3);
      uint32_t kl[7], kh[7];
#pragma unroll
      for (int t = 0; t < 7; t++) { kl[t] = movm(pack_bf16(acc[t][0], acc[t][1])); kh[t] = movm(pack_bf16(acc[t][2], acc[t][3])); }
      mma_z(dl, a0.x, a0.y, a0.z, a0.w, kl[0], kl[1]); mma_z(dh, a0.x, a0.y, a0.z, a0.w, kh[0], kh[1]);
      mma_z(el, a1.x, a1.y, a1.z, a1.w, kl[2], kl[3]); mma_z(eh, a1.x, a1.y, a1.z, a1.w, kh[2], kh[3]);
      mma16816(dl, a2.x, a2.y, a2.z, a2.w, kl[4], kl[5]); mma16816(dh, a2.x, a2.y, a2.z, a2.w, kh[4], kh[5]);
      mma1688(el, a3.x, a3.y, kl[6]); mma1688(eh, a3.x, a3.y, kh[6]);
      sts64f(lq + QOFF(red), (dl[0] + dh[2]) + (el[0] + eh[2]), (dl[1] + dh[3]) + (el[1] + eh[3]));
      BAR_SYNC(2, 128);
      {
        float2 t0 = lds64f(l16 + QOFF(red)), t1 = lds64f(l16 + QOFF(red) + QB), t2 = lds64f(l16 + QOFF(red) + 2 * QB), t3 = lds64f(l16 + QOFF(red) + 3 * QB);
        st_async2(dst_sm, (t0.x + t1.x) + (t2.x + t3.x), (t0.y + t1.y) + (t2.y + t3.y), dst_bar);
      }
      STAMP(4);
      sts128(lq + QOFF(kq), kl[0], kl[1], kh[0], kh[1]); sts128(lq + QOFF(kq) + 512, kl[2], kl[3], kh[2], kh[3]);
      sts128(lq + QOFF(kq) + 1024, kl[4], kl[5], kh[4], kh[5]); sts64(lq + QOFF(kq) + 1536, kl[6], kh[6]);
      p += (s & 1) ? (1024 - 32) : 32;
      if (q == 1 && s >= 2 && s + 2 < NSEG) { if (elect1()) issue_loads(sb, s + 2, h, j); __syncwarp(); }
      if (s + 1 < NSEG) wait_bar1(bar_ld + 8 * ((s + 1) & (NST - 1)), ((s + 1) / NST) & 1);
      BAR_SYNC(4, 384);
      unsigned tred = clk();
      if (q == 0) { if (elect1()) { arm_bar(bar_sx, 1024); arm_bar(bar_sm, 1024); } __syncwarp(); }
      while (clk() - tred < (unsigned)(poll_delay & 0xffff)) {}
    }
  } else if (role == 1) {
    asm volatile("setmaxnreg.inc.sync.aligned.u32 216;");
    const int lane = opaque_lane();
    const uint32_t l16 = sb + lane * 16;
    uint4 W[42];
    {
      const uint4* wf = g_WF + (((NH + h) * 28 + 7 * j) * 28 + 7 * q) * 32 + lane;
#pragma unroll
      for (int k = 0; k < 7; k++)
#pragma unroll
        for (int t = 0; t < 6; t++) W[k * 6 + t] = wf[(t * 28 + k) * 32];
    }
#undef ws
#define ws (lq + QOFF(wB))
    const uint32_t lq = l16 + q * QB;
#define uq (lq + QOFF(uQ))
#pragma unroll 1
    for (int s = 0; s < NSEG; s++) {
      const int st = s & (NST - 1);
      uint4 w6a = lds128(ws), w6b = lds128(ws + 512);
      BAR_SYNC(1, 256);
      uint4 p0 = lds128(mq), p1 = lds128(mq + 512), p2 = lds128(mq + 1024); uint2 p3 = lds64(mq + 1536);
      STAMP(10);
      const uint32_t b[14] = {p0.x, p0.y, p0.z, p0.w, p1.x, p1.y, p1.z, p1.w, p2.x, p2.y, p2.z, p2.w, p3.x, p3.y};
      float acc[7][4];
      B2(0); B2(1); B2(2); B2(3); B2(4); B2(5); B2(6);
      {
        uint32_t m = amax2(amax2(amax2(amax2(0u, p0.x, p0.y), p0.z, p0.w), p1.x, p1.y), p1.z, p1.w);
        m = amax2(amax2(amax2(m, p2.x, p2.y), p2.z, p2.w), p3.x, p3.y);
        m = max(m & 0xffffu, m >> 16);
        m = __reduce_max_sync(0xffffffffu, m);
        sts32(sb + OFF(smax) + q * 4, m);
      }
      BAR_ARRIVE(9, 256);
      FENCE(8);
#define UP(nt) pack_bf16(acc[(nt) >> 1][((nt) & 1) * 2], acc[(nt) >> 1][((nt) & 1) * 2 + 1])
#pragma unroll
      for (int k = 0; k < 7; k++)
#pragma unroll
        for (int t = 0; t < 4; t++) MMW(acc[3 - t], W[k * 6 + 3 - t], b[2 * k], b[2 * k + 1], k == 0);
      { uint32_t u6 = UP(6), u7 = UP(7);
        sts128(uq + 1024, UP(8), UP(9), UP(10), u7); sts128(uq + 1536, UP(11), UP(12), UP(13), u7);
        sts128(uq + 512, UP(3), UP(4), UP(5), u6); sts128(uq, UP(0), UP(1), UP(2), u6); }
      BAR_ARRIVE(3, 256);
      STAMP(11);
      const float inv = __uint_as_float(lds32(sb + OFF(sinv) + (s & 1) * 4));
      BAR_SYNC(4, 384);
      {
        const int nt0 = q < 2 ? q * 3 : 8 + (q - 2) * 3, nts = 6 + (q >> 1);
        uint32_t ub = l16 + QOFF(uQ) + q * 512; asm volatile("" : "+r"(ub));
        uint4 u0 = lds128(ub), u1 = lds128(ub + QB), u2 = lds128(ub + 2 * QB), u3 = lds128(ub + 3 * QB);
        auto us = [&](uint32_t a, uint32_t b, uint32_t c, uint32_t d) { return pack_bf16(((bf_lo(a) + bf_lo(b)) + (bf_lo(c) + bf_lo(d))) * inv, ((bf_hi(a) + bf_hi(b)) + (bf_hi(c) + bf_hi(d))) * inv); };
        uint32_t* uf = (uint32_t*)((char*)(g_UF + ((s * NH + h) * 56 + 14 * j) * 32) + ((l16 - sb) >> 2));
        { uf[(nt0 + 0) * 32] = us(u0.x, u1.x, u2.x, u3.x); uf[(nt0 + 1) * 32] = us(u0.y, u1.y, u2.y, u3.y); uf[(nt0 + 2) * 32] = us(u0.z, u1.z, u2.z, u3.z);
        if ((q & 1) == 0) uf[nts * 32] = us(u0.w, u1.w, u2.w, u3.w); }
      }
      {
        const uint32_t xb = l16 + OFF(xf) + st * 7168;
        uint4 k0 = lds128(lq + QOFF(kq)), k1 = lds128(lq + QOFF(kq) + 512), k2 = lds128(lq + QOFF(kq) + 1024); uint2 k3 = lds64(lq + QOFF(kq) + 1536);
        const uint32_t kk[14] = {k0.x, k0.y, k0.z, k0.w, k1.x, k1.y, k1.z, k1.w, k2.x, k2.y, k2.z, k2.w, k3.x, k3.y};
        float y[2][4];
#pragma unroll
        for (int f = 0; f < 7; f++)
#pragma unroll
          for (int m = 0; m < 2; m++) {
            uint4 xa = lds128(xb + (f * 2 + m) * 512);
            MMW(y[m], xa, kk[2 * f], kk[2 * f + 1], f == 0);
          }
        sts128(lq + QOFF(xred), __float_as_uint(y[0][0]), __float_as_uint(y[0][1]), __float_as_uint(y[0][2]), __float_as_uint(y[0][3]));
        sts128(lq + QOFF(xred) + 512, __float_as_uint(y[1][0]), __float_as_uint(y[1][1]), __float_as_uint(y[1][2]), __float_as_uint(y[1][3]));
        BAR_SYNC(15, 128);
        if (q < 2) {
          uint32_t xr = l16 + QOFF(xred) + q * 512; asm volatile("" : "+r"(xr));
          float4 t0 = lds128f(xr), t1 = lds128f(xr + QB), t2 = lds128f(xr + 2 * QB), t3 = lds128f(xr + 3 * QB);
          *(float4*)((char*)(g_SXM + ((((s * NH + h) * 4 + j) * 2 + q) * 32)) + (l16 - sb)) = make_float4(((t0.x + t1.x) + (t2.x + t3.x)) * inv, ((t0.y + t1.y) + (t2.y + t3.y)) * inv, ((t0.z + t1.z) + (t2.z + t3.z)) * inv, ((t0.w + t1.w) + (t2.w + t3.w)) * inv);
        }
      }
    }
  } else {
    asm volatile("setmaxnreg.dec.sync.aligned.u32 64;");
    const int lane = opaque_lane();
    const uint32_t l16 = sb + lane * 16;
    const int nt0 = q < 2 ? q * 3 : 8 + (q - 2) * 3, nts = 6 + (q >> 1);
    const float bmax = g_bmax;
    float inv = g_inv0;
    uint32_t sc_bf; { uint32_t t = (0x7f000000u - __float_as_uint(inv)) >> 16; sc_bf = t | (t << 16); }
    uint4* redp = acc_ptr(1, j * 4 + q, lane);
    const uint32_t dst_sx = mapa(l16 + OFF(sx) + (j >> 1) * 512 + (j & 1) * 8, q), dst_bar = mapa(bar_sx, q);
#pragma unroll 1
    for (int s = 0; s < NSEG; s++) {
      const int st = s & (NST - 1);
      float ox[8];
      float mx, nsc;
      const float c1 = LOG2E * inv;
      {
        const uint32_t vb = l16 + OFF(vf) + st * 7168;
        wait_bar1(bar_ld + 8 * st, (s / NST) & 1);
        uint4 v0 = lds128(vb + nt0 * 512), v1 = lds128(vb + nt0 * 512 + 512), v2 = lds128(vb + nt0 * 512 + 1024), v3 = lds128(vb + nts * 512);
        BAR_SYNC(14, 256);
        STAMP(2);
        {
          float2 t0 = lds64f(l16 + QOFF(red) + 8), t1 = lds64f(l16 + QOFF(red) + 8 + QB), t2 = lds64f(l16 + QOFF(red) + 8 + 2 * QB), t3 = lds64f(l16 + QOFF(red) + 8 + 3 * QB);
          st_async2(dst_sx, (t0.x + t1.x) + (t2.x + t3.x), (t0.y + t1.y) + (t2.y + t3.y), dst_bar);
        }
        STAMP(9);
        wait_bar1(bar_sx, s & 1);
        STAMP(12);
        float4 x0 = lds128f(l16 + OFF(sx)), x1 = lds128f(l16 + OFF(sx) + 512);
        float sx[8] = {x0.x, x0.y, x0.z, x0.w, x1.x, x1.y, x1.z, x1.w};
        mx = fmaxf(fmaxf(fmaxf(sx[0], sx[1]), fmaxf(sx[2], sx[3])), fmaxf(fmaxf(sx[4], sx[5]), fmaxf(sx[6], sx[7])));
        mx = fmaxf(mx, __shfl_xor_sync(0xffffffffu, mx, 1)); mx = fmaxf(mx, __shfl_xor_sync(0xffffffffu, mx, 2));
        mx *= c1;
#pragma unroll
        for (int i = 0; i < 8; i++) sx[i] = ex2(fmaf(sx[i], c1, -mx));
        uint32_t p0 = pack_bf16(sx[0], sx[1]), p1 = pack_bf16(sx[2], sx[3]), p2 = pack_bf16(sx[4], sx[5]), p3 = pack_bf16(sx[6], sx[7]);
        float o[4], r[4];
        mma_z(o, p0, p2, p1, p3, v0.x, v0.y); mma_z(r, p0, p2, p1, p3, v0.z, v0.w); ox[0] = o[0] + r[2]; ox[1] = o[1] + r[3];
        mma_z(o, p0, p2, p1, p3, v1.x, v1.y); mma_z(r, p0, p2, p1, p3, v1.z, v1.w); ox[2] = o[0] + r[2]; ox[3] = o[1] + r[3];
        mma_z(o, p0, p2, p1, p3, v2.x, v2.y); mma_z(r, p0, p2, p1, p3, v2.z, v2.w); ox[4] = o[0] + r[2]; ox[5] = o[1] + r[3];
        mma_z(o, p0, p2, p1, p3, v3.x, v3.y); mma_z(r, p0, p2, p1, p3, v3.z, v3.w); ox[6] = (q & 1) ? o[1] + r[3] : o[0] + r[2];
        mma_z(o, p0, p2, p1, p3, 0x3f803f80u, 0x3f803f80u); ox[7] = o[0] + o[2];
      }
      STAMP(5);
      FENCE(9);
        BAR_SYNC(9, 256);
        {
          uint4 m4 = lds128(sb + OFF(smax));
          uint32_t mb = max(max(m4.x, m4.y), max(m4.z, m4.w));
          float mh = fmaxf(__uint_as_float(mb << 16) * inv, __uint_as_float(lds32(sb + OFF(xmax) + s * 4)));
          float bound = mh * bmax;
          int e = (int)(__float_as_uint(bound) >> 23) - 127 + 10;
          int se = min(max(15 - e, -100), 100);
          nsc = __uint_as_float((uint32_t)(127 + se) << 23);
        }
      wait_bar1(bar_sm, s & 1);
      STAMP(7);
      uint4 u0, u1, u2, u3;
      {
        float4 t0 = lds128f(l16 + OFF(sm)), t1 = lds128f(l16 + OFF(sm) + 512);
        float s0 = ((t0.x + t0.z) + (t1.x + t1.z)) * inv * c1, s1 = ((t0.y + t0.w) + (t1.y + t1.w)) * inv * c1;
        float m = fmaxf(fmaxf(s0, s1), mx);
        m = fmaxf(m, __shfl_xor_sync(0xffffffffu, m, 1)); m = fmaxf(m, __shfl_xor_sync(0xffffffffu, m, 2));
        FENCE(10);
        BAR_SYNC(3, 256);
        const uint32_t ub = l16 + QOFF(uQ) + q * 512;
        u0 = lds128(ub); u1 = lds128(ub + QB); u2 = lds128(ub + 2 * QB); u3 = lds128(ub + 3 * QB);
        STAMP(6);
        float e0 = ex2(s0 - m), e1 = ex2(s1 - m), al = ex2(mx - m);
        uint32_t pm = pack_bf16(e0 * inv, e1 * inv);
        float z[4], ya[4], yb[4], yc[4], yd[4];
        mma_z(z, pm, 0u, 0u, pm, sc_bf, sc_bf);
        mma_z(ya, pm, 0u, 0u, pm, u0.x, u0.y); mma_z(yb, pm, 0u, 0u, pm, u0.z, u0.w);
        mma_z(yc, pm, 0u, 0u, pm, u1.x, u1.y); mma_z(yd, pm, 0u, 0u, pm, u1.z, u1.w);
        mma16816(ya, pm, 0u, 0u, pm, u2.x, u2.y); mma16816(yb, pm, 0u, 0u, pm, u2.z, u2.w);
        mma16816(yc, pm, 0u, 0u, pm, u3.x, u3.y); mma16816(yd, pm, 0u, 0u, pm, u3.z, u3.w);
        float iz; asm("rcp.approx.ftz.f32 %0, %1;" : "=f"(iz) : "f"(fmaf(ox[7], al, z[0])));
        iz *= nsc;
#pragma unroll
        for (int i = 0; i < 7; i++) ox[i] *= al;
        const float y6 = (q & 1) ? yb[3] + yd[3] : yb[2] + yd[2];
        red_h8(redp, pack_f16(((ya[0] + ox[0]) + yc[0]) * iz, ((ya[1] + ox[1]) + yc[1]) * iz), pack_f16(((ya[2] + ox[2]) + yc[2]) * iz, ((ya[3] + ox[3]) + yc[3]) * iz),
               pack_f16(((yb[0] + ox[4]) + yd[0]) * iz, ((yb[1] + ox[5]) + yd[1]) * iz), pack_f16((y6 + ox[6]) * iz, 1.f));
      }
      const float ninv = __uint_as_float(0x7f000000u - __float_as_uint(nsc));
      BAR_ARRIVE(4, 384);
      STAMP(8);
      if (q == 0) sts32(sb + OFF(sinv) + ((s + 1) & 1) * 4, __float_as_uint(ninv));
      redp += (s & 1) ? 32 : (1024 - 32);
      inv = ninv; { uint32_t t = __float_as_uint(nsc) >> 16; sc_bf = t | (t << 16); }
    }
  }
  asm volatile("barrier.cluster.arrive.release.aligned;\nbarrier.cluster.wait.acquire.aligned;" ::: "memory");
}

__global__ void n_xf(const bf16* x) {
  int i = blockIdx.x * blockDim.x + threadIdx.x;
  if (i >= NSEG * 4 * 14 * 32) return;
  int lane = i & 31, r = i >> 5, m = r & 1; r >>= 1; int f = r % 7; r /= 7; int j = r & 3, seg = r >> 2;
  int c0 = f == 6 ? 96 : (f & ~1) * 16 + (f & 1) * 8, c1 = f == 6 ? 104 : (f | 1) * 16 + (f & 1) * 8;
  const bf16* r0 = x + (seg * 32 + m * 16 + (lane >> 2)) * DM + j * 112 + (lane & 3) * 2;
  const bf16* r1 = r0 + 8 * DM;
  g_XF[i] = make_uint4(*(const uint32_t*)(r0 + c0), *(const uint32_t*)(r1 + c0), *(const uint32_t*)(r0 + c1), *(const uint32_t*)(r1 + c1));
}

__global__ void n_seed(const bf16* mem0) {
  __shared__ unsigned smx;
  if (threadIdx.x == 0) smx = 0;
  __syncthreads();
  float m = 0.f;
  for (int i = threadIdx.x; i < 8 * DM; i += 512) m = fmaxf(m, fabsf(b2f(mem0[i])));
  atomicMax(&smx, __float_as_uint(m));
  __syncthreads();
  int e = (int)(smx >> 23) - 127 + 1;
  int se = min(max(15 - e, -100), 100);
  float sc = __uint_as_float((uint32_t)(127 + se) << 23);
  if (threadIdx.x == 0) g_inv0 = __uint_as_float((uint32_t)(127 - se) << 23);
  int vec = threadIdx.x >> 5, lane = threadIdx.x & 31, j = vec >> 2, q = vec & 3;
  int nt0 = q < 2 ? q * 3 : 8 + (q - 2) * 3, nts = 6 + (q >> 1);
  const bf16* r = mem0 + (lane >> 2) * DM + j * 112 + (lane & 3) * 2;
  auto val = [&](int nt, int e2) { return b2f(r[nt * 8 + e2]) * sc; };
  *acc_ptr(0, vec, lane) = make_uint4(pack_f16(val(nt0, 0), val(nt0, 1)), pack_f16(val(nt0 + 1, 0), val(nt0 + 1, 1)), pack_f16(val(nt0 + 2, 0), val(nt0 + 2, 1)), pack_f16(val(nts, q & 1), 16.f));
}

__global__ void n_stats(const bf16* x) {
  if (blockIdx.x < 64) {
    float m = 0.f;
    for (int i = threadIdx.x; i < 32 * DM; i += 256) m = fmaxf(m, fabsf(b2f(x[blockIdx.x * 32 * DM + i])));
    atomicMax((unsigned*)&g_xmax[blockIdx.x], __float_as_uint(m));
  } else {
    int r = (blockIdx.x - 64) * 256 + threadIdx.x;
    if (r < NH * DM) { float a = 0.f; for (int k = 0; k < DM; k++) { float v = wf_elem(1, r / DM, r % DM, k); a += v * v; } atomicMax((unsigned*)&g_bmax, __float_as_uint(sqrtf(a))); }
  }
}

int g_poll_delay = POLL_DELAY;
extern "C" void kernel_launch(void* const* d_in, const int* in_sizes, int n_in, void* d_out, int out_size) {
  const bf16* x = (const bf16*)d_in[0];
  const bf16* wqkv = (const bf16*)d_in[1];
  const bf16* wphi = (const bf16*)d_in[2];
  const bf16* wo_a = (const bf16*)d_in[3];
  const bf16* mem0 = (const bf16*)d_in[5];
  const bf16* Wq = (const bf16*)d_in[6];
  const bf16* Wk = (const bf16*)d_in[7];
  const bf16* Wv = (const bf16*)d_in[8];
  const bf16* Wo = (const bf16*)d_in[9];
  const bf16* gate_w = (const bf16*)d_in[11];
  bf16* out = (bf16*)d_out;
  cudaFuncSetAttribute(r_kernel, cudaFuncAttributeMaxDynamicSharedMemorySize, (int)sizeof(RSmem));
  n_zero<<<(NSEG * 40 * 32 + 255) / 256, 256>>>();
  n_prep<<<(2 * NH * 28 * 28 * 32 + 255) / 256, 256>>>(Wq, Wk, Wv, Wo);
  n_stats<<<64 + 28, 256>>>(x);
  n_seed<<<1, 512>>>(mem0);
  n_xf<<<NSEG * 4 * 14 * 32 / 256, 256>>>(x);
  n_xgemm<<<2 * NH * 28 * NSEG * 32 / 256, 256>>>(x);
  r_kernel<<<64, 384, sizeof(RSmem)>>>(mem0, g_poll_delay);
  n_qkv<<<(S_LEN * 1344 + 255) / 256, 256>>>(x, wqkv);
  n_phi<<<(S_LEN * 2 * NH + 255) / 256, 256>>>(wphi);
  n_kv<<<(32 * NH * 56 * 29 + 255) / 256, 256>>>();
  n_oa<<<(S_LEN * DM + 255) / 256, 256>>>();
  n_x3<<<NSEG, 512>>>(x, wo_a, gate_w, out);
}
```

```cpp
#include <cuda_runtime.h>
#include <cuda_bf16.h>
#include <stdint.h>
#include <stddef.h>

typedef __nv_bfloat16 bf16;
#define S_LEN 2048
#define DM 448
#define NH 16
#define NSEG 64
#define SPIN_LIMIT (1 << 22)

__device__ uint4 g_WF[2 * NH * 28 * 28 * 32];
__device__ uint4 g_KF[NSEG * NH * 4 * 4 * 4 * 32];
__device__ uint4 g_VF[NSEG * NH * 56 * 32];
__device__ float4 g_SXM[NSEG * NH * 4 * 2 * 32];
__device__ uint4 g_XF[NSEG * 4 * 14 * 32];
__device__ uint32_t g_UF[NSEG * NH * 56 * 32];
__device__ uint4 g_ACC16[(NSEG + 2) * 16 * 32];
__device__ float g_xmax[NSEG];
__device__ float g_bmax;
__device__ float g_inv0;
__device__ float g_qkv[S_LEN * 1344];
__device__ float g_phiq[S_LEN * NH * 56];
__device__ float g_phik[S_LEN * NH * 56];
__device__ float g_kv[NH * 56 * 29];
__device__ float g_oa[S_LEN * DM];
__device__ int g_err;
__device__ unsigned g_ts[64 * 64 * 64];

__device__ __forceinline__ uint32_t pack_bf16(float lo, float hi) {
  uint32_t r; asm("cvt.rn.bf16x2.f32 %0, %1, %2;" : "=r"(r) : "f"(hi), "f"(lo)); return r;
}
__device__ __forceinline__ float bf_lo(uint32_t v) { return __uint_as_float(v << 16); }
__device__ __forceinline__ float bf_hi(uint32_t v) { return __uint_as_float(v & 0xffff0000u); }
__device__ __forceinline__ float b2f(bf16 v) { return __bfloat162float(v); }

__global__ void n_prep(const bf16* Wq, const bf16* Wk, const bf16* Wv, const bf16* Wo) {
  int idx = blockIdx.x * blockDim.x + threadIdx.x;
  if (idx >= 2 * NH * 28 * 28 * 32) return;
  int lane = idx & 31, r = idx >> 5;
  int ks = r % 28; r /= 28; int tile = r % 28; r /= 28; int h = r % NH; int mat = r / NH;
  int g = lane >> 2, tq = lane & 3;
  float v[8];
  for (int i = 0; i < 8; i++) {
    int row = tile * 16 + g + ((i >> 1) & 1) * 8;
    int col = ks * 16 + tq * 2 + (i & 1) + (i >> 2) * 8;
    float acc = 0.f;
    if (mat == 0) { for (int e = 0; e < 256; e++) acc += b2f(Wq[(row * NH + h) * 256 + e]) * b2f(Wk[(col * NH + h) * 256 + e]); acc *= 0.0625f; }
    else { for (int e = 0; e < 256; e++) acc += b2f(Wo[(h * 256 + e) * DM + row]) * b2f(Wv[(col * NH + h) * 256 + e]); }
    v[i] = acc;
  }
  g_WF[idx] = make_uint4(pack_bf16(v[0], v[1]), pack_bf16(v[2], v[3]), pack_bf16(v[4], v[5]), pack_bf16(v[6], v[7]));
}
__device__ __forceinline__ float wf_elem(int mat, int h, int row, int col) {
  int tile = row >> 4, ks = col >> 4, rr = row & 15, cc = col & 15;
  int lane = (rr & 7) * 4 + ((cc & 7) >> 1);
  int reg = (rr >> 3) + (cc >> 3) * 2;
  uint32_t w = ((const uint32_t*)g_WF)[((((mat * NH + h) * 28 + tile) * 28 + ks) * 32 + lane) * 4 + reg];
  return (cc & 1) ? bf_hi(w) : bf_lo(w);
}
__device__ __forceinline__ void mma16816(float* d, uint32_t a0, uint32_t a1, uint32_t a2, uint32_t a3, uint32_t b0, uint32_t b1) {
  asm volatile("mma.sync.aligned.m16n8k16.row.col.f32.bf16.bf16.f32 {%0,%1,%2,%3}, {%4,%5,%6,%7}, {%8,%9}, {%0,%1,%2,%3};"
    : "+f"(d[0]), "+f"(d[1]), "+f"(d[2]), "+f"(d[3]) : "r"(a0), "r"(a1), "r"(a2), "r"(a3), "r"(b0), "r"(b1));
}
__device__ __forceinline__ void mma1688(float* d, uint32_t a0, uint32_t a1, uint32_t b0) {
  asm volatile("mma.sync.aligned.m16n8k8.row.col.f32.bf16.bf16.f32 {%0,%1,%2,%3}, {%4,%5}, {%6}, {%0,%1,%2,%3};"
    : "+f"(d[0]), "+f"(d[1]), "+f"(d[2]), "+f"(d[3]) : "r"(a0), "r"(a1), "r"(b0));
}
__device__ __forceinline__ uint32_t movm(uint32_t a) { uint32_t d; asm volatile("movmatrix.sync.aligned.m8n8.trans.b16 %0, %1;" : "=r"(d) : "r"(a)); return d; }

__global__ void n_xgemm(const bf16* x) {
  int wid = (blockIdx.x * blockDim.x + threadIdx.x) >> 5, lane = threadIdx.x & 31;
  int seg = wid % NSEG; int r = wid / NSEG;
  int tile = r % 28; r /= 28; int h = r % NH; int mat = r / NH;
  if (mat >= 2) return;
  int g = lane >> 2, tq = lane & 3;
  float d[4][4] = {};
  const uint4* wf = g_WF + (((mat * NH + h) * 28 + tile) * 28) * 32 + lane;
  for (int ks = 0; ks < 28; ks++) {
    uint4 a = wf[ks * 32];
    for (int kg = 0; kg < 4; kg++) {
      const uint32_t* xr = (const uint32_t*)(x + (seg * 32 + kg * 8 + g) * DM + ks * 16 + tq * 2);
      mma16816(d[kg], a.x, a.y, a.z, a.w, xr[0], xr[4]);
    }
  }
  if (mat == 0) {
    for (int kg = 0; kg < 4; kg++) {
      uint32_t b0 = movm(pack_bf16(d[kg][0], d[kg][1])), b1 = movm(pack_bf16(d[kg][2], d[kg][3]));
      int jj = tile / 7, i = tile % 7;
      uint32_t* dst = (uint32_t*)&g_KF[((((seg * NH + h) * 4 + kg) * 4 + jj) * 4 + (i >> 1)) * 32 + lane];
      if (i == 6) { dst[0] = b0; dst[1] = b1; } else { dst[i & 1] = b0; dst[2 + (i & 1)] = b1; }
    }
  } else {
    g_VF[((seg * NH + h) * 56 + tile * 2) * 32 + lane] = make_uint4(pack_bf16(d[0][0], d[0][1]), pack_bf16(d[1][0], d[1][1]), pack_bf16(d[2][0], d[2][1]), pack_bf16(d[3][0], d[3][1]));
    g_VF[((seg * NH + h) * 56 + tile * 2 + 1) * 32 + lane] = make_uint4(pack_bf16(d[0][2], d[0][3]), pack_bf16(d[1][2], d[1][3]), pack_bf16(d[2][2], d[2][3]), pack_bf16(d[3][2], d[3][3]));
  }
}
__global__ void n_zero() {
  int i = blockIdx.x * blockDim.x + threadIdx.x;
  if (i < (NSEG + 2) * 16 * 32) g_ACC16[i] = make_uint4(0, 0, 0, 0);
  if (i < NSEG) g_xmax[i] = 0.f;
  if (i == 0) g_bmax = 0.f;
  if (i < NH * 56 * 29) g_kv[i] = 0.f;
}
__global__ void n_qkv(const bf16* x, const bf16* w) {
  int i = blockIdx.x * blockDim.x + threadIdx.x;
  if (i >= S_LEN * 1344) return;
  int n = i % 1344, t = i / 1344;
  float acc = 0.f;
  for (int k = 0; k < DM; k++) acc += b2f(x[t * DM + k]) * b2f(w[k * 1344 + n]);
  g_qkv[i] = acc;
}
__global__ void n_phi(const bf16* wphi) {
  int i = blockIdx.x * blockDim.x + threadIdx.x;
  if (i >= S_LEN * 2 * NH) return;
  int h = i % NH, which = (i / NH) % 2, t = i / (2 * NH);
  float p[28]; float mx = -1e30f, mn = 1e30f;
  for (int f = 0; f < 28; f++) {
    float acc = 0.f;
    for (int d = 0; d < 28; d++) acc += g_qkv[t * 1344 + which * 448 + h * 28 + d] * b2f(wphi[(h * 28 + d) * 28 + f]);
    p[f] = acc; mx = fmaxf(mx, acc); mn = fminf(mn, acc);
  }
  float s1 = 0.f, s2 = 0.f;
  for (int f = 0; f < 28; f++) { s1 += __expf(p[f] - mx); s2 += __expf(mn - p[f]); }
  float* o = (which ? g_phik : g_phiq) + (t * NH + h) * 56;
  for (int f = 0; f < 28; f++) { o[f] = __expf(p[f] - mx) / s1; o[28 + f] = __expf(mn - p[f]) / s2; }
}
__global__ void n_kv() {
  int i = blockIdx.x * blockDim.x + threadIdx.x;
  if (i >= 32 * NH * 56 * 29) return;
  int d = i % 29, f = (i / 29) % 56, h = (i / (29 * 56)) % NH, ch = i / (29 * 56 * NH);
  float acc = 0.f;
  for (int t = ch * 64; t < ch * 64 + 64; t++) acc += g_phik[(t * NH + h) * 56 + f] * (d < 28 ? g_qkv[t * 1344 + 896 + h * 28 + d] : 1.f);
  atomicAdd(&g_kv[(h * 56 + f) * 29 + d], acc);
}
__global__ void n_oa() {
  int i = blockIdx.x * blockDim.x + threadIdx.x;
  if (i >= S_LEN * DM) return;
  int c = i % DM, t = i / DM, h = c / 28, d = c % 28;
  float num = 0.f, den = 0.f;
  for (int f = 0; f < 56; f++) { float p = g_phiq[(t * NH + h) * 56 + f]; num += p * g_kv[(h * 56 + f) * 29 + d]; den += p * g_kv[(h * 56 + f) * 29 + 28]; }
  g_oa[i] = num / (den + 1e-6f);
}

__global__ void __launch_bounds__(512) n_x3(const bf16* x, const bf16* wo, const bf16* gate_w, bf16* out) {
  __shared__ uint32_t sP[NH][2][32][10];
  __shared__ float sG[32];
  int seg = blockIdx.x, w = threadIdx.x >> 5, lane = threadIdx.x & 31, g = lane >> 2, tq = lane & 3;
  for (int r = w; r < 32; r += 16) {
    float acc = 0.f;
    for (int k = lane; k < DM; k += 32) acc += b2f(x[(seg * 32 + r) * DM + k]) * b2f(gate_w[k]);
    for (int o = 16; o; o >>= 1) acc += __shfl_xor_sync(0xffffffffu, acc, o);
    if (lane == 0) sG[r] = 1.f / (1.f + __expf(-acc));
  }
  {
    int h = w;
    float s[2][5][4] = {};
    for (int ct = 0; ct < 28; ct++) {
      uint32_t a[2][4];
      for (int m = 0; m < 2; m++) {
        const uint32_t* r0 = (const uint32_t*)(x + (seg * 32 + m * 16 + g) * DM + ct * 16 + tq * 2);
        const uint32_t* r1 = (const uint32_t*)(x + (seg * 32 + m * 16 + g + 8) * DM + ct * 16 + tq * 2);
        a[m][0] = r0[0]; a[m][1] = r1[0]; a[m][2] = r0[4]; a[m][3] = r1[4];
      }
      int j = ct / 7, i = ct % 7;
      for (int kg = 0; kg < 4; kg++) {
        const uint32_t* src = (const uint32_t*)&g_KF[((((seg * NH + h) * 4 + kg) * 4 + j) * 4 + (i >> 1)) * 32 + lane];
        uint2 b = i == 6 ? make_uint2(src[0], src[1]) : make_uint2(src[i & 1], src[2 + (i & 1)]);
        for (int m = 0; m < 2; m++) mma16816(s[m][1 + kg], a[m][0], a[m][1], a[m][2], a[m][3], b.x, b.y);
      }
    }
    for (int m = 0; m < 2; m++) for (int j = 0; j < 4; j++) {
      float4 t = g_SXM[(((seg * NH + h) * 4 + j) * 2 + m) * 32 + lane];
      s[m][0][0] += t.x; s[m][0][1] += t.y; s[m][0][2] += t.z; s[m][0][3] += t.w;
    }
    for (int m = 0; m < 2; m++) for (int hf = 0; hf < 2; hf++) {
      int t = m * 16 + hf * 8 + g;
      float v[10]; float mx = -1e30f;
      for (int n = 0; n < 5; n++) for (int e = 0; e < 2; e++) {
        float val = s[m][n][hf * 2 + e];
        if (n > 0 && (n - 1) * 8 + tq * 2 + e > t) val = -1e30f;
        v[n * 2 + e] = val; mx = fmaxf(mx, val);
      }
      mx = fmaxf(mx, __shfl_xor_sync(0xffffffffu, mx, 1)); mx = fmaxf(mx, __shfl_xor_sync(0xffffffffu, mx, 2));
      float z = 0.f;
      for (int i = 0; i < 10; i++) { v[i] = __expf(v[i] - mx); z += v[i]; }
      z += __shfl_xor_sync(0xffffffffu, z, 1); z += __shfl_xor_sync(0xffffffffu, z, 2);
      float iz = 1.f / z;
      sP[h][m][lane][hf] = pack_bf16(v[0] * iz, v[1] * iz);
      sP[h][m][lane][2 + hf] = pack_bf16(v[2] * iz, v[3] * iz);
      sP[h][m][lane][4 + hf] = pack_bf16(v[4] * iz, v[5] * iz);
      sP[h][m][lane][6 + hf] = pack_bf16(v[6] * iz, v[7] * iz);
      sP[h][m][lane][8 + hf] = pack_bf16(v[8] * iz, v[9] * iz);
    }
  }
  __syncthreads();
  if (w < 14) {
    float o[2][4][4] = {};
    for (int h = 0; h < NH; h++) {
      for (int n = 0; n < 4; n++) {
        int nt = w * 4 + n;
        uint4 v = g_VF[((seg * NH + h) * 56 + nt) * 32 + lane];
        uint32_t u = g_UF[((seg * NH + h) * 56 + nt) * 32 + lane];
        for (int m = 0; m < 2; m++) {
          const uint32_t* p = sP[h][m][lane];
          mma1688(o[m][n], p[0], p[1], u);
          mma16816(o[m][n], p[2], p[3], p[4], p[5], v.x, v.y);
          mma16816(o[m][n], p[6], p[7], p[8], p[9], v.z, v.w);
        }
      }
    }
    for (int m = 0; m < 2; m++) for (int n = 0; n < 4; n++) for (int i = 0; i < 4; i++) {
      int r = m * 16 + (i >> 1) * 8 + g, c = (w * 4 + n) * 8 + tq * 2 + (i & 1);
      int t = seg * 32 + r;
      float a = 0.f;
      for (int k = 0; k < DM; k++) a += g_oa[t * DM + k] * b2f(wo[k * DM + c]);
      float gt = sG[r];
      out[t * DM + c] = __float2bfloat16(gt * a + (1.f - gt) * o[m][n][i]);
    }
  }
}

__device__ __forceinline__ uint32_t smem_u32(const void* p) { return (uint32_t)__cvta_generic_to_shared(p); }
__device__ __forceinline__ uint32_t mapa(uint32_t a, uint32_t r) { uint32_t o; asm volatile("mapa.shared::cluster.u32 %0, %1, %2;" : "=r"(o) : "r"(a), "r"(r)); return o; }
__device__ __forceinline__ bool try_wait(uint32_t bar, uint32_t parity) {
  uint32_t ok; asm volatile("{\n.reg .pred p;\nmbarrier.try_wait.parity.shared::cta.b64 p, [%1], %2;\nselp.u32 %0, 1, 0, p;\n}" : "=r"(ok) : "r"(bar), "r"(parity) : "memory"); return ok; }
__device__ __forceinline__ void wait_bar(uint32_t bar, uint32_t parity) {
  int n = 0; while (!try_wait(bar, parity)) { if (++n > SPIN_LIMIT) { g_err = 1; break; } } }
__device__ __forceinline__ void arm_bar(uint32_t bar, uint32_t bytes) { asm volatile("mbarrier.arrive.expect_tx.shared::cta.b64 _, [%0], %1;" :: "r"(bar), "r"(bytes) : "memory"); }
__device__ __forceinline__ float4 ld_relaxed4(const void* p) { float4 v; asm volatile("ld.relaxed.gpu.global.v4.f32 {%0,%1,%2,%3}, [%4];" : "=f"(v.x), "=f"(v.y), "=f"(v.z), "=f"(v.w) : "l"(p) : "memory"); return v; }
__device__ __forceinline__ void red4(void* p, float a, float b, float c, float d) { asm volatile("red.relaxed.gpu.global.add.v4.f32 [%0], {%1,%2,%3,%4};" :: "l"(p), "f"(a), "f"(b), "f"(c), "f"(d) : "memory"); }
__device__ __forceinline__ void st_async2(uint32_t dst, float a, float b, uint32_t bar) { asm volatile("st.async.shared::cluster.mbarrier::complete_tx::bytes.v2.f32 [%0], {%1,%2}, [%3];" :: "r"(dst), "f"(a), "f"(b), "r"(bar) : "memory"); }
__device__ __forceinline__ void bulk_g2s(uint32_t dst, const void* src, uint32_t bytes, uint32_t bar) {
  asm volatile("cp.async.bulk.shared::cluster.global.mbarrier::complete_tx::bytes [%0], [%1], %2, [%3];" :: "r"(dst), "l"(src), "r"(bytes), "r"(bar) : "memory"); }
__device__ __forceinline__ unsigned clk() { unsigned c; asm volatile("mov.u32 %0, %%clock;" : "=r"(c) :: "memory"); return c; }
__device__ __forceinline__ float ex2(float x) { float y; asm("ex2.approx.ftz.f32 %0, %1;" : "=f"(y) : "f"(x)); return y; }

#define NST 4
struct QBlk {
  uint4 memF[4][32];
  uint4 wA[7][32], wB[7][32];
  uint4 kf[NST][4][32];
  float4 xred[2][32];
  float4 red[32];
  uint4 uQ[4][32];
  uint4 kq[2][4][32];
};
#define QB ((uint32_t)sizeof(QBlk))
#define QOFF(f) ((uint32_t)offsetof(QBlk, f))
struct RSmem {
  QBlk qb[4];
  uint4 vf[NST][14][32];
  uint4 xf[NST][14][32];
  float4 sx[2][32];
  float4 sm[2][32];
  uint32_t smax[4];
  float xmax[NSEG];
  float sinv[4];
  unsigned long long bar_ld[NST], bar_sx, bar_sm;
  unsigned ts[64 * 64];
};
#define LD_BYTES (8192 + 7168 + 7168)
#define POLL_DELAY 300
#define STAMP(i)
__device__ __forceinline__ void wait_slow(uint32_t bar, uint32_t parity) {
#pragma unroll 1
  for (int n = 0; n < SPIN_LIMIT; n++) if (try_wait(bar, parity)) return;
  g_err = 1;
}
__device__ __forceinline__ void wait_bar1(uint32_t bar, uint32_t parity) { if (!try_wait(bar, parity)) wait_slow(bar, parity); }
__device__ __forceinline__ uint4 ld_relaxed_u4(const void* p) { uint4 v; asm volatile("ld.relaxed.gpu.global.v4.u32 {%0,%1,%2,%3}, [%4];" : "=r"(v.x), "=r"(v.y), "=r"(v.z), "=r"(v.w) : "l"(p) : "memory"); return v; }
__device__ __forceinline__ void red_h8(void* p, uint32_t a, uint32_t b, uint32_t c, uint32_t d) { asm volatile("red.relaxed.gpu.global.add.noftz.v4.f16x2 [%0], {%1,%2,%3,%4};" :: "l"(p), "r"(a), "r"(b), "r"(c), "r"(d) : "memory"); }
__device__ __forceinline__ uint32_t pack_f16(float lo, float hi) { uint32_t r; asm("cvt.rn.f16x2.f32 %0, %1, %2;" : "=r"(r) : "f"(hi), "f"(lo)); return r; }
__device__ __forceinline__ uint32_t h2_to_bf2(uint32_t v) {
  float lo, hi; asm("{.reg .f16 l, h; mov.b32 {l, h}, %2; cvt.f32.f16 %0, l; cvt.f32.f16 %1, h;}" : "=f"(lo), "=f"(hi) : "r"(v)); return pack_bf16(lo, hi); }
__device__ __forceinline__ uint2 lds64(uint32_t a) { uint2 v; asm volatile("ld.shared.v2.u32 {%0,%1}, [%2];" : "=r"(v.x), "=r"(v.y) : "r"(a) : "memory"); return v; }
__device__ __forceinline__ float2 lds64f(uint32_t a) { float2 v; asm volatile("ld.shared.v2.f32 {%0,%1}, [%2];" : "=f"(v.x), "=f"(v.y) : "r"(a) : "memory"); return v; }
__device__ __forceinline__ uint4 lds128(uint32_t a) { uint4 v; asm volatile("ld.shared.v4.u32 {%0,%1,%2,%3}, [%4];" : "=r"(v.x), "=r"(v.y), "=r"(v.z), "=r"(v.w) : "r"(a) : "memory"); return v; }
__device__ __forceinline__ uint4 lds128v(uint32_t a) { uint4 v; asm volatile("ld.volatile.shared.v4.u32 {%0,%1,%2,%3}, [%4];" : "=r"(v.x), "=r"(v.y), "=r"(v.z), "=r"(v.w) : "r"(a) : "memory"); return v; }
__device__ __forceinline__ uint32_t lds32(uint32_t a) { uint32_t v; asm volatile("ld.shared.u32 %0, [%1];" : "=r"(v) : "r"(a) : "memory"); return v; }
__device__ __forceinline__ void sts64(uint32_t a, uint32_t x, uint32_t y) { asm volatile("st.shared.v2.u32 [%0], {%1,%2};" :: "r"(a), "r"(x), "r"(y) : "memory"); }
__device__ __forceinline__ void sts64f(uint32_t a, float x, float y) { asm volatile("st.shared.v2.f32 [%0], {%1,%2};" :: "r"(a), "f"(x), "f"(y) : "memory"); }
__device__ __forceinline__ void sts32(uint32_t a, uint32_t x) { asm volatile("st.shared.u32 [%0], %1;" :: "r"(a), "r"(x) : "memory"); }
__device__ __forceinline__ void mma_z(float* d, uint32_t a0, uint32_t a1, uint32_t a2, uint32_t a3, uint32_t b0, uint32_t b1) {
  asm volatile("mma.sync.aligned.m16n8k16.row.col.f32.bf16.bf16.f32 {%0,%1,%2,%3}, {%4,%5,%6,%7}, {%8,%9}, {%10,%10,%10,%10};"
    : "=f"(d[0]), "=f"(d[1]), "=f"(d[2]), "=f"(d[3]) : "r"(a0), "r"(a1), "r"(a2), "r"(a3), "r"(b0), "r"(b1), "f"(0.f));
}
__device__ __forceinline__ void mma8_z(float* d, uint32_t a0, uint32_t a1, uint32_t b0) {
  asm volatile("mma.sync.aligned.m16n8k8.row.col.f32.bf16.bf16.f32 {%0,%1,%2,%3}, {%4,%5}, {%6}, {%7,%7,%7,%7};"
    : "=f"(d[0]), "=f"(d[1]), "=f"(d[2]), "=f"(d[3]) : "r"(a0), "r"(a1), "r"(b0), "f"(0.f));
}
#define OFF(f) ((uint32_t)offsetof(RSmem, f))
#define BAR_SYNC(id, n) asm volatile("bar.sync %0, %1;" :: "n"(id), "n"(n) : "memory")
#define BAR_ARRIVE(id, n) asm volatile("bar.arrive %0, %1;" :: "n"(id), "n"(n) : "memory")

__device__ __forceinline__ void sts128(uint32_t a, uint32_t x, uint32_t y, uint32_t z, uint32_t w) { asm volatile("st.shared.v4.u32 [%0], {%1,%2,%3,%4};" :: "r"(a), "r"(x), "r"(y), "r"(z), "r"(w) : "memory"); }
template <int K>
__device__ __forceinline__ void kstep(const uint4 (&W)[42], float (&acc)[7][4], uint32_t b0, uint32_t b1, uint4& w6, uint32_t ws) {
#pragma unroll
  for (int t = 0; t < 6; t++) {
    const uint4& w = W[K * 6 + t];
    if (K == 0) mma_z(acc[t], w.x, w.y, w.z, w.w, b0, b1); else mma16816(acc[t], w.x, w.y, w.z, w.w, b0, b1);
  }
  if (K == 0) mma_z(acc[6], w6.x, w6.y, w6.z, w6.w, b0, b1); else mma16816(acc[6], w6.x, w6.y, w6.z, w6.w, b0, b1);
  if (K < 6) w6 = lds128(ws + (K + 1) * 512);
}
__device__ __forceinline__ uint4* acc_ptr(int step, int vec, int lane) { return g_ACC16 + (((step >> 1) * 16 + vec) * 2 + (step & 1)) * 32 + lane; }

__device__ __forceinline__ bool elect1() { uint32_t p; asm volatile("{.reg .pred p; elect.sync _|p, 0xffffffff; selp.u32 %0, 1, 0, p;}" : "=r"(p)); return p; }
__device__ __forceinline__ float4 lds128f(uint32_t a) { float4 v; asm volatile("ld.shared.v4.f32 {%0,%1,%2,%3}, [%4];" : "=f"(v.x), "=f"(v.y), "=f"(v.z), "=f"(v.w) : "r"(a) : "memory"); return v; }
__device__ __forceinline__ uint32_t amax2(uint32_t m, uint32_t x, uint32_t y) { return __vmaxu2(m, __vmaxu2(x & 0x7fff7fffu, y & 0x7fff7fffu)); }

#define FENCE(n) do { if (__builtin_expect((poll_delay >> (16 + (n))) & 1, 0)) { _Pragma("unroll 1") for (int i_ = poll_delay & 7; i_ > 0; i_--) asm volatile("nanosleep.u32 %0;" :: "n"(n) : "memory"); } } while (0)
#define BAR_SYNC_R(id, n) asm volatile("bar.sync %0, %1;" :: "r"(id), "n"(n) : "memory")
#define BAR_ARRIVE_R(id, n) asm volatile("bar.arrive %0, %1;" :: "r"(id), "n"(n) : "memory")
#define MMW(A, WW, B0, B1, first) do { if (first) mma_z(A, WW.x, WW.y, WW.z, WW.w, B0, B1); else mma16816(A, WW.x, WW.y, WW.z, WW.w, B0, B1); } while (0)
__device__ __forceinline__ void issue_loads(uint32_t sb, int s, int h, int j) {
  const int st = s & (NST - 1), s0 = s;
  const uint32_t bar = sb + OFF(bar_ld) + 8 * st;
  arm_bar(bar, LD_BYTES);
#pragma unroll
  for (int qq = 0; qq < 4; qq++) bulk_g2s(sb + qq * QB + QOFF(kf) + st * 2048, g_KF + ((s * NH + h) * 4 + j) * 512 + qq * 128, 2048, bar);
  bulk_g2s(sb + OFF(vf) + st * 7168, g_VF + ((s * NH + h) * 56 + 14 * j) * 32, 7168, bar);
  bulk_g2s(sb + OFF(xf) + st * 7168, g_XF + (s * 4 + j) * 448, 7168, bar);
  asm volatile("prefetch.global.L2 [%0];" :: "l"(acc_ptr(s0, h, j * 8)));
}
__device__ __forceinline__ int opaque_lane() { return __shfl_sync(0xffffffffu, threadIdx.x & 31, threadIdx.x & 31); }

__global__ void __cluster_dims__(4, 1, 1) __launch_bounds__(384, 1) r_kernel(const bf16* mem0, int poll_delay) {
  extern __shared__ __align__(128) unsigned char smem_raw[];
  RSmem& sm = *reinterpret_cast<RSmem*>(smem_raw);
  const int h = blockIdx.x >> 2, j = blockIdx.x & 3;
  const int w = __shfl_sync(0xffffffffu, threadIdx.x >> 5, 0), q = w & 3, role = w >> 2;
  const uint32_t sb = smem_u32(smem_raw);
  const uint32_t bar_ld = sb + OFF(bar_ld), bar_sx = sb + OFF(bar_sx), bar_sm = sb + OFF(bar_sm);
  if (threadIdx.x == 0) {
    for (int i = 0; i < NST; i++) asm volatile("mbarrier.init.shared::cta.b64 [%0], 1;" :: "r"(bar_ld + 8 * i));
    asm volatile("mbarrier.init.shared::cta.b64 [%0], 1;" :: "r"(bar_sx));
    asm volatile("mbarrier.init.shared::cta.b64 [%0], 1;" :: "r"(bar_sm));
    asm volatile("fence.mbarrier_init.release.cluster;" ::: "memory");
    arm_bar(bar_sx, 1024); arm_bar(bar_sm, 1024);
    for (int s = 0; s < NST; s++) issue_loads(sb, s, h, j);
    sm.sinv[0] = g_inv0;
  }
  if (threadIdx.x < NSEG) sm.xmax[threadIdx.x] = g_xmax[threadIdx.x];
  if (role < 2) {
    const int lane = threadIdx.x & 31;
    const uint4* wf = g_WF + (((role * NH + h) * 28 + 7 * j) * 28 + 7 * q) * 32 + lane;
#pragma unroll
    for (int e = 0; e < 7; e++) (role ? sm.qb[q].wB : sm.qb[q].wA)[e][lane] = wf[e * 28 * 32];
  }
  asm volatile("barrier.cluster.arrive.release.aligned;\nbarrier.cluster.wait.acquire.aligned;" ::: "memory");
  const float LOG2E = 1.4426950408889634f;

  if (role == 0) {
    asm volatile("setmaxnreg.inc.sync.aligned.u32 224;");
    const int lane = opaque_lane();
    const uint32_t l16 = sb + lane * 16;
    uint4 W[42];
    {
      const uint4* wf = g_WF + ((h * 28 + 7 * j) * 28 + 7 * q) * 32 + lane;
#pragma unroll
      for (int k = 1; k < 7; k++)
#pragma unroll
        for (int t = 0; t < 7; t++) W[(k - 1) * 7 + t] = wf[(t * 28 + k) * 32];
    }
    const uint32_t lq = l16 + q * QB, mj = l16 + j * QB;
#define ws (lq + QOFF(wA))
#define mq lq
    const uint32_t dst_sm = mapa(l16 + OFF(sm) + (j >> 1) * 512 + (j & 1) * 8, q), dst_bar = mapa(bar_sm, q);
    const uint4* p = acc_ptr(0, q * 4, lane);
#define TM(t, k) do { if ((k) == 0) mma_z(acc[t], f[t].x, f[t].y, f[t].z, f[t].w, b[0], b[1]); else { const uint4& w_ = W[((k) - 1) * 7 + (t)]; mma16816(acc[t], w_.x, w_.y, w_.z, w_.w, b[2 * (k)], b[2 * (k) + 1]); } } while (0)
#define T3(k) do { TM(0, k); TM(1, k); TM(2, k); } while (0)
#define T4(k) do { TM(3, k); TM(4, k); TM(5, k); TM(6, k); } while (0)
#define TR(t) do { kl[t] = movm(pack_bf16(acc[t][0], acc[t][1])); kh[t] = movm(pack_bf16(acc[t][2], acc[t][3])); } while (0)
    wait_bar1(bar_ld, 0);
#pragma unroll 1
    for (int s = 0; s < NSEG; s++) {
      STAMP(0);
      uint4 v0 = ld_relaxed_u4(p), v1 = ld_relaxed_u4(p + 64), v2 = ld_relaxed_u4(p + 128), v3 = ld_relaxed_u4(p + 192);
      const uint32_t kb = lq + QOFF(kf) + (s & (NST - 1)) * 2048;
      uint4 k0 = lds128(kb), k1 = lds128(kb + 512), k2 = lds128(kb + 1024); uint2 k3 = lds64(kb + 1536);
      uint4 f[7];
      f[0] = lds128v(ws); f[1] = lds128v(ws + 512); f[2] = lds128v(ws + 1024);
      if (!__all_sync(0xffffffffu, __byte_perm(v0.w, v1.w, 0x7632) == 0x4C004C00u && __byte_perm(v2.w, v3.w, 0x7632) == 0x4C004C00u)) {
#pragma unroll 1
        for (int n = 0; n < SPIN_LIMIT; n++) {
          v0 = ld_relaxed_u4(p); v1 = ld_relaxed_u4(p + 64); v2 = ld_relaxed_u4(p + 128); v3 = ld_relaxed_u4(p + 192);
          if (__all_sync(0xffffffffu, __byte_perm(v0.w, v1.w, 0x7632) == 0x4C004C00u && __byte_perm(v2.w, v3.w, 0x7632) == 0x4C004C00u)) break;
        }
      }
      STAMP(1);
      uint32_t b[14];
      float dl[4], dh[4], el[4], eh[4];
      b[0] = h2_to_bf2(v0.x); b[1] = h2_to_bf2(v0.y); b[2] = h2_to_bf2(v0.z); b[3] = h2_to_bf2(v1.x);
      mma_z(dl, b[0], b[1], b[2], b[3], k0.x, k0.y); mma_z(dh, b[0], b[1], b[2], b[3], k0.z, k0.w);
      b[4] = h2_to_bf2(v1.y); b[5] = h2_to_bf2(v1.z);
      b[6] = h2_to_bf2(__byte_perm(v0.w, v1.w, 0x5410)); b[7] = h2_to_bf2(__byte_perm(v2.w, v3.w, 0x5410));
      mma_z(el, b[4], b[5], b[6], b[7], k1.x, k1.y); mma_z(eh, b[4], b[5], b[6], b[7], k1.z, k1.w);
      b[8] = h2_to_bf2(v2.x); b[9] = h2_to_bf2(v2.y); b[10] = h2_to_bf2(v2.z); b[11] = h2_to_bf2(v3.x);
      mma16816(dl, b[8], b[9], b[10], b[11], k2.x, k2.y); mma16816(dh, b[8], b[9], b[10], b[11], k2.z, k2.w);
      b[12] = h2_to_bf2(v3.y); b[13] = h2_to_bf2(v3.z);
      mma1688(el, b[12], b[13], k3.x); mma1688(eh, b[12], b[13], k3.y);
      float acc[7][4];
      T3(0); T3(1);
      sts64f(lq + QOFF(red) + 8, (dl[0] + dh[2]) + (el[0] + eh[2]), (dl[1] + dh[3]) + (el[1] + eh[3]));
      BAR_ARRIVE(14, 256);
      f[3] = lds128(ws + 1536); f[4] = lds128(ws + 2048); f[5] = lds128(ws + 2560); f[6] = lds128(ws + 3072);
      sts128(mq, b[0], b[1], b[2], b[3]); sts128(mq + 512, b[4], b[5], b[6], b[7]); sts128(mq + 1024, b[8], b[9], b[10], b[11]); sts64(mq + 1536, b[12], b[13]);
      BAR_ARRIVE_R(5 + q, 64);
      T3(2);
      FENCE(2);
      T3(3); T4(0); T3(4); T4(1); T3(5); T4(2); T3(6); T4(3);
      FENCE(4);
      BAR_SYNC(1, 128);
      uint4 a0 = lds128(mj), a1 = lds128(mj + 512), a2 = lds128(mj + 1024); uint2 a3 = lds64(mj + 1536);
      uint32_t kl[7], kh[7];
      T4(4); TR(0); TR(1); T4(5); TR(2); T4(6);
      mma_z(dl, a0.x, a0.y, a0.z, a0.w, kl[0], kl[1]); mma_z(dh, a0.x, a0.y, a0.z, a0.w, kh[0], kh[1]);
      BAR_ARRIVE_R(10 + q, 64);
      FENCE(5);
      STAMP(3);
      TR(3); TR(4); TR(5); TR(6);
      mma_z(el, a1.x, a1.y, a1.z, a1.w, kl[2], kl[3]); mma_z(eh, a1.x, a1.y, a1.z, a1.w, kh[2], kh[3]);
      mma16816(dl, a2.x, a2.y, a2.z, a2.w, kl[4], kl[5]); mma16816(dh, a2.x, a2.y, a2.z, a2.w, kh[4], kh[5]);
      float gl[4], gh[4];
      mma8_z(gl, a3.x, a3.y, kl[6]); mma8_z(gh, a3.x, a3.y, kh[6]);
      dl[0] += el[0]; dh[2] += eh[2]; dl[1] += el[1]; dh[3] += eh[3]; el[0] = gl[0]; el[1] = gl[1]; eh[2] = gh[2]; eh[3] = gh[3];
      sts64f(lq + QOFF(red), (dl[0] + dh[2]) + (el[0] + eh[2]), (dl[1] + dh[3]) + (el[1] + eh[3]));
      BAR_SYNC(2, 128);
      {
        float2 t0 = lds64f(l16 + QOFF(red)), t1 = lds64f(l16 + QOFF(red) + QB), t2 = lds64f(l16 + QOFF(red) + 2 * QB), t3 = lds64f(l16 + QOFF(red) + 3 * QB);
        st_async2(dst_sm, (t0.x + t1.x) + (t2.x + t3.x), (t0.y + t1.y) + (t2.y + t3.y), dst_bar);
      }
      STAMP(4);
      { const uint32_t kqa = lq + QOFF(kq) + (s & 1) * 2048;
      sts128(kqa, kl[0], kl[1], kh[0], kh[1]); sts128(kqa + 512, kl[2], kl[3], kh[2], kh[3]);
      sts128(kqa + 1024, kl[4], kl[5], kh[4], kh[5]); sts64(kqa + 1536, kl[6], kh[6]); }
      p += (s & 1) ? (1024 - 32) : 32;
      if (q == 1 && s >= 2 && s + 2 < NSEG) { if (elect1()) issue_loads(sb, s + 2, h, j); __syncwarp(); }
      if (s + 1 < NSEG) wait_bar1(bar_ld + 8 * ((s + 1) & (NST - 1)), ((s + 1) / NST) & 1);
      BAR_SYNC(4, 384);
      unsigned tred = clk();
      if (q == 0) { if (elect1()) { arm_bar(bar_sx, 1024); arm_bar(bar_sm, 1024); } __syncwarp(); }
      while (clk() - tred < (unsigned)(poll_delay & 0xffff)) {}
    }
  } else if (role == 1) {
    asm volatile("setmaxnreg.inc.sync.aligned.u32 216;");
    const int lane = opaque_lane();
    const uint32_t l16 = sb + lane * 16;
    uint4 W[42];
    {
      const uint4* wf = g_WF + (((NH + h) * 28 + 7 * j) * 28 + 7 * q) * 32 + lane;
#pragma unroll
      for (int k = 1; k < 7; k++)
#pragma unroll
        for (int t = 0; t < 7; t++) W[(k - 1) * 7 + t] = wf[(t * 28 + k) * 32];
    }
#undef ws
#define ws (lq + QOFF(wB))
    const uint32_t lq = l16 + q * QB;
#define uq (lq + QOFF(uQ))
#pragma unroll 1
    for (int s = 0; s < NSEG; s++) {
      const int st = s & (NST - 1);
      uint4 f[7];
#pragma unroll
      for (int t = 0; t < 7; t++) f[t] = lds128(ws + t * 512);
      BAR_SYNC_R(5 + q, 64);
      uint4 p0 = lds128(mq), p1 = lds128(mq + 512), p2 = lds128(mq + 1024); uint2 p3 = lds64(mq + 1536);
      {
        uint32_t m = amax2(amax2(amax2(amax2(0u, p0.x, p0.y), p0.z, p0.w), p1.x, p1.y), p1.z, p1.w);
        m = amax2(amax2(amax2(m, p2.x, p2.y), p2.z, p2.w), p3.x, p3.y);
        m = max(m & 0xffffu, m >> 16);
        m = __reduce_max_sync(0xffffffffu, m);
        sts32(sb + OFF(smax) + q * 4, m);
      }
      BAR_ARRIVE(9, 256);
      BAR_SYNC_R(10 + q, 64);
      FENCE(7);
      STAMP(10);
      const uint32_t b[14] = {p0.x, p0.y, p0.z, p0.w, p1.x, p1.y, p1.z, p1.w, p2.x, p2.y, p2.z, p2.w, p3.x, p3.y};
      float acc[7][4];
      T3(0); T3(1); T3(2); T3(3); T3(4); T3(5); T3(6);
      FENCE(8);
#define UP(nt) pack_bf16(acc[(nt) >> 1][((nt) & 1) * 2], acc[(nt) >> 1][((nt) & 1) * 2 + 1])
      T4(0); T4(1); T4(2); T4(3); T4(4); T4(5); T4(6);
      { uint32_t u6 = UP(6), u7 = UP(7);
        sts128(uq, UP(0), UP(1), UP(2), u6); sts128(uq + 512, UP(3), UP(4), UP(5), u6);
        sts128(uq + 1024, UP(8), UP(9), UP(10), u7); sts128(uq + 1536, UP(11), UP(12), UP(13), u7); }
      BAR_ARRIVE(3, 256);
      STAMP(11);
      const float inv = __uint_as_float(lds32(sb + OFF(sinv) + (s & 1) * 4));
      BAR_SYNC(4, 384);
      {
        const int nt0 = q < 2 ? q * 3 : 8 + (q - 2) * 3, nts = 6 + (q >> 1);
        uint32_t ub = l16 + QOFF(uQ) + q * 512; asm volatile("" : "+r"(ub));
        uint4 u0 = lds128(ub), u1 = lds128(ub + QB), u2 = lds128(ub + 2 * QB), u3 = lds128(ub + 3 * QB);
        auto us = [&](uint32_t a, uint32_t b, uint32_t c, uint32_t d) { return pack_bf16(((bf_lo(a) + bf_lo(b)) + (bf_lo(c) + bf_lo(d))) * inv, ((bf_hi(a) + bf_hi(b)) + (bf_hi(c) + bf_hi(d))) * inv); };
        uint32_t* uf = (uint32_t*)((char*)(g_UF + ((s * NH + h) * 56 + 14 * j) * 32) + ((l16 - sb) >> 2));
        { uf[(nt0 + 0) * 32] = us(u0.x, u1.x, u2.x, u3.x); uf[(nt0 + 1) * 32] = us(u0.y, u1.y, u2.y, u3.y); uf[(nt0 + 2) * 32] = us(u0.z, u1.z, u2.z, u3.z);
        if ((q & 1) == 0) uf[nts * 32] = us(u0.w, u1.w, u2.w, u3.w); }
      }
      {
        const uint32_t xb = l16 + OFF(xf) + st * 7168;
        const uint32_t kqa = lq + QOFF(kq) + (s & 1) * 2048;
        uint4 k0 = lds128(kqa), k1 = lds128(kqa + 512), k2 = lds128(kqa + 1024); uint2 k3 = lds64(kqa + 1536);
        const uint32_t kk[14] = {k0.x, k0.y, k0.z, k0.w, k1.x, k1.y, k1.z, k1.w, k2.x, k2.y, k2.z, k2.w, k3.x, k3.y};
        float y[2][4];
#pragma unroll
        for (int f = 0; f < 7; f++)
#pragma unroll
          for (int m = 0; m < 2; m++) {
            uint4 xa = lds128(xb + (f * 2 + m) * 512);
            MMW(y[m], xa, kk[2 * f], kk[2 * f + 1], f == 0);
          }
        sts128(lq + QOFF(xred), __float_as_uint(y[0][0]), __float_as_uint(y[0][1]), __float_as_uint(y[0][2]), __float_as_uint(y[0][3]));
        sts128(lq + QOFF(xred) + 512, __float_as_uint(y[1][0]), __float_as_uint(y[1][1]), __float_as_uint(y[1][2]), __float_as_uint(y[1][3]));
        BAR_SYNC(15, 128);
        if (q < 2) {
          uint32_t xr = l16 + QOFF(xred) + q * 512; asm volatile("" : "+r"(xr));
          float4 t0 = lds128f(xr), t1 = lds128f(xr + QB), t2 = lds128f(xr + 2 * QB), t3 = lds128f(xr + 3 * QB);
          *(float4*)((char*)(g_SXM + ((((s * NH + h) * 4 + j) * 2 + q) * 32)) + (l16 - sb)) = make_float4(((t0.x + t1.x) + (t2.x + t3.x)) * inv, ((t0.y + t1.y) + (t2.y + t3.y)) * inv, ((t0.z + t1.z) + (t2.z + t3.z)) * inv, ((t0.w + t1.w) + (t2.w + t3.w)) * inv);
        }
      }
    }
  } else {
    asm volatile("setmaxnreg.dec.sync.aligned.u32 64;");
    const int lane = opaque_lane();
    const uint32_t l16 = sb + lane * 16;
    const int nt0 = q < 2 ? q * 3 : 8 + (q - 2) * 3, nts = 6 + (q >> 1);
    const float bmax = g_bmax;
    float inv = g_inv0;
    uint32_t sc_bf; { uint32_t t = (0x7f000000u - __float_as_uint(inv)) >> 16; sc_bf = t | (t << 16); }
    uint4* redp = acc_ptr(1, j * 4 + q, lane);
    const uint32_t dst_sx = mapa(l16 + OFF(sx) + (j >> 1) * 512 + (j & 1) * 8, q), dst_bar = mapa(bar_sx, q);
#pragma unroll 1
    for (int s = 0; s < NSEG; s++) {
      const int st = s & (NST - 1);
      float ox[8];
      float mx, nsc;
      const float c1 = LOG2E * inv;
      {
        const uint32_t vb = l16 + OFF(vf) + st * 7168;
        wait_bar1(bar_ld + 8 * st, (s / NST) & 1);
        uint4 v0 = lds128(vb + nt0 * 512), v1 = lds128(vb + nt0 * 512 + 512), v2 = lds128(vb + nt0 * 512 + 1024), v3 = lds128(vb + nts * 512);
        BAR_SYNC(14, 256);
        STAMP(2);
        {
          float2 t0 = lds64f(l16 + QOFF(red) + 8), t1 = lds64f(l16 + QOFF(red) + 8 + QB), t2 = lds64f(l16 + QOFF(red) + 8 + 2 * QB), t3 = lds64f(l16 + QOFF(red) + 8 + 3 * QB);
          st_async2(dst_sx, (t0.x + t1.x) + (t2.x + t3.x), (t0.y + t1.y) + (t2.y + t3.y), dst_bar);
        }
        STAMP(9);
        wait_bar1(bar_sx, s & 1);
        STAMP(12);
        float4 x0 = lds128f(l16 + OFF(sx)), x1 = lds128f(l16 + OFF(sx) + 512);
        float sx[8] = {x0.x, x0.y, x0.z, x0.w, x1.x, x1.y, x1.z, x1.w};
        mx = fmaxf(fmaxf(fmaxf(sx[0], sx[1]), fmaxf(sx[2], sx[3])), fmaxf(fmaxf(sx[4], sx[5]), fmaxf(sx[6], sx[7])));
        mx = fmaxf(mx, __shfl_xor_sync(0xffffffffu, mx, 1)); mx = fmaxf(mx, __shfl_xor_sync(0xffffffffu, mx, 2));
        mx *= c1;
#pragma unroll
        for (int i = 0; i < 8; i++) sx[i] = ex2(fmaf(sx[i], c1, -mx));
        uint32_t p0 = pack_bf16(sx[0], sx[1]), p1 = pack_bf16(sx[2], sx[3]), p2 = pack_bf16(sx[4], sx[5]), p3 = pack_bf16(sx[6], sx[7]);
        float o[4], r[4];
        mma_z(o, p0, p2, p1, p3, v0.x, v0.y); mma_z(r, p0, p2, p1, p3, v0.z, v0.w); ox[0] = o[0] + r[2]; ox[1] = o[1] + r[3];
        mma_z(o, p0, p2, p1, p3, v1.x, v1.y); mma_z(r, p0, p2, p1, p3, v1.z, v1.w); ox[2] = o[0] + r[2]; ox[3] = o[1] + r[3];
        mma_z(o, p0, p2, p1, p3, v2.x, v2.y); mma_z(r, p0, p2, p1, p3, v2.z, v2.w); ox[4] = o[0] + r[2]; ox[5] = o[1] + r[3];
        mma_z(o, p0, p2, p1, p3, v3.x, v3.y); mma_z(r, p0, p2, p1, p3, v3.z, v3.w); ox[6] = (q & 1) ? o[1] + r[3] : o[0] + r[2];
        mma_z(o, p0, p2, p1, p3, 0x3f803f80u, 0x3f803f80u); ox[7] = o[0] + o[2];
      }
      STAMP(5);
      FENCE(9);
        BAR_SYNC(9, 256);
        {
          uint4 m4 = lds128(sb + OFF(smax));
          uint32_t mb = max(max(m4.x, m4.y), max(m4.z, m4.w));
          float mh = fmaxf(__uint_as_float(mb << 16) * inv, __uint_as_float(lds32(sb + OFF(xmax) + s * 4)));
          float bound = mh * bmax;
          int e = (int)(__float_as_uint(bound) >> 23) - 127 + 10;
          int se = min(max(15 - e, -100), 100);
          nsc = __uint_as_float((uint32_t)(127 + se) << 23);
        }
      wait_bar1(bar_sm, s & 1);
      STAMP(7);
      uint4 u0, u1, u2, u3;
      {
        float4 t0 = lds128f(l16 + OFF(sm)), t1 = lds128f(l16 + OFF(sm) + 512);
        float s0 = ((t0.x + t0.z) + (t1.x + t1.z)) * inv * c1, s1 = ((t0.y + t0.w) + (t1.y + t1.w)) * inv * c1;
        float m = fmaxf(fmaxf(s0, s1), mx);
        m = fmaxf(m, __shfl_xor_sync(0xffffffffu, m, 1)); m = fmaxf(m, __shfl_xor_sync(0xffffffffu, m, 2));
        FENCE(10);
        BAR_SYNC(3, 256);
        const uint32_t ub = l16 + QOFF(uQ) + q * 512;
        u0 = lds128(ub); u1 = lds128(ub + QB); u2 = lds128(ub + 2 * QB); u3 = lds128(ub + 3 * QB);
        STAMP(6);
        float e0 = ex2(s0 - m), e1 = ex2(s1 - m), al = ex2(mx - m);
        uint32_t pm = pack_bf16(e0 * inv, e1 * inv);
        float z[4], ya[4], yb[4], yc[4], yd[4];
        mma_z(z, pm, 0u, 0u, pm, sc_bf, sc_bf);
        mma_z(ya, pm, 0u, 0u, pm, u0.x, u0.y); mma_z(yb, pm, 0u, 0u, pm, u0.z, u0.w);
        mma_z(yc, pm, 0u, 0u, pm, u1.x, u1.y); mma_z(yd, pm, 0u, 0u, pm, u1.z, u1.w);
        mma16816(ya, pm, 0u, 0u, pm, u2.x, u2.y); mma16816(yb, pm, 0u, 0u, pm, u2.z, u2.w);
        mma16816(yc, pm, 0u, 0u, pm, u3.x, u3.y); mma16816(yd, pm, 0u, 0u, pm, u3.z, u3.w);
        float iz; asm("rcp.approx.ftz.f32 %0, %1;" : "=f"(iz) : "f"(fmaf(ox[7], al, z[0])));
        iz *= nsc;
#pragma unroll
        for (int i = 0; i < 7; i++) ox[i] *= al;
        const float y6 = (q & 1) ? yb[3] + yd[3] : yb[2] + yd[2];
        red_h8(redp, pack_f16(((ya[0] + ox[0]) + yc[0]) * iz, ((ya[1] + ox[1]) + yc[1]) * iz), pack_f16(((ya[2] + ox[2]) + yc[2]) * iz, ((ya[3] + ox[3]) + yc[3]) * iz),
               pack_f16(((yb[0] + ox[4]) + yd[0]) * iz, ((yb[1] + ox[5]) + yd[1]) * iz), pack_f16((y6 + ox[6]) * iz, 1.f));
      }
      const float ninv = __uint_as_float(0x7f000000u - __float_as_uint(nsc));
      BAR_ARRIVE(4, 384);
      STAMP(8);
      if (q == 0) sts32(sb + OFF(sinv) + ((s + 1) & 1) * 4, __float_as_uint(ninv));
      redp += (s & 1) ? 32 : (1024 - 32);
      inv = ninv; { uint32_t t = __float_as_uint(nsc) >> 16; sc_bf = t | (t << 16); }
    }
  }
  asm volatile("barrier.cluster.arrive.release.aligned;\nbarrier.cluster.wait.acquire.aligned;" ::: "memory");
}

__global__ void n_xf(const bf16* x) {
  int i = blockIdx.x * blockDim.x + threadIdx.x;
  if (i >= NSEG * 4 * 14 * 32) return;
  int lane = i & 31, r = i >> 5, m = r & 1; r >>= 1; int f = r % 7; r /= 7; int j = r & 3, seg = r >> 2;
  int c0 = f == 6 ? 96 : (f & ~1) * 16 + (f & 1) * 8, c1 = f == 6 ? 104 : (f | 1) * 16 + (f & 1) * 8;
  const bf16* r0 = x + (seg * 32 + m * 16 + (lane >> 2)) * DM + j * 112 + (lane & 3) * 2;
  const bf16* r1 = r0 + 8 * DM;
  g_XF[i] = make_uint4(*(const uint32_t*)(r0 + c0), *(const uint32_t*)(r1 + c0), *(const uint32_t*)(r0 + c1), *(const uint32_t*)(r1 + c1));
}

__global__ void n_seed(const bf16* mem0) {
  __shared__ unsigned smx;
  if (threadIdx.x == 0) smx = 0;
  __syncthreads();
  float m = 0.f;
  for (int i = threadIdx.x; i < 8 * DM; i += 512) m = fmaxf(m, fabsf(b2f(mem0[i])));
  atomicMax(&smx, __float_as_uint(m));
  __syncthreads();
  int e = (int)(smx >> 23) - 127 + 1;
  int se = min(max(15 - e, -100), 100);
  float sc = __uint_as_float((uint32_t)(127 + se) << 23);
  if (threadIdx.x == 0) g_inv0 = __uint_as_float((uint32_t)(127 - se) << 23);
  int vec = threadIdx.x >> 5, lane = threadIdx.x & 31, j = vec >> 2, q = vec & 3;
  int nt0 = q < 2 ? q * 3 : 8 + (q - 2) * 3, nts = 6 + (q >> 1);
  const bf16* r = mem0 + (lane >> 2) * DM + j * 112 + (lane & 3) * 2;
  auto val = [&](int nt, int e2) { return b2f(r[nt * 8 + e2]) * sc; };
  *acc_ptr(0, vec, lane) = make_uint4(pack_f16(val(nt0, 0), val(nt0, 1)), pack_f16(val(nt0 + 1, 0), val(nt0 + 1, 1)), pack_f16(val(nt0 + 2, 0), val(nt0 + 2, 1)), pack_f16(val(nts, q & 1), 16.f));
}

__global__ void n_stats(const bf16* x) {
  if (blockIdx.x < 64) {
    float m = 0.f;
    for (int i = threadIdx.x; i < 32 * DM; i += 256) m = fmaxf(m, fabsf(b2f(x[blockIdx.x * 32 * DM + i])));
    atomicMax((unsigned*)&g_xmax[blockIdx.x], __float_as_uint(m));
  } else {
    int r = (blockIdx.x - 64) * 256 + threadIdx.x;
    if (r < NH * DM) { float a = 0.f; for (int k = 0; k < DM; k++) { float v = wf_elem(1, r / DM, r % DM, k); a += v * v; } atomicMax((unsigned*)&g_bmax, __float_as_uint(sqrtf(a))); }
  }
}

int g_poll_delay = POLL_DELAY;
extern "C" void kernel_launch(void* const* d_in, const int* in_sizes, int n_in, void* d_out, int out_size) {
  const bf16* x = (const bf16*)d_in[0];
  const bf16* wqkv = (const bf16*)d_in[1];
  const bf16* wphi = (const bf16*)d_in[2];
  const bf16* wo_a = (const bf16*)d_in[3];
  const bf16* mem0 = (const bf16*)d_in[5];
  const bf16* Wq = (const bf16*)d_in[6];
  const bf16* Wk = (const bf16*)d_in[7];
  const bf16* Wv = (const bf16*)d_in[8];
  const bf16* Wo = (const bf16*)d_in[9];
  const bf16* gate_w = (const bf16*)d_in[11];
  bf16* out = (bf16*)d_out;
  cudaFuncSetAttribute(r_kernel, cudaFuncAttributeMaxDynamicSharedMemorySize, (int)sizeof(RSmem));
  n_zero<<<(NSEG * 40 * 32 + 255) / 256, 256>>>();
  n_prep<<<(2 * NH * 28 * 28 * 32 + 255) / 256, 256>>>(Wq, Wk, Wv, Wo);
  n_stats<<<64 + 28, 256>>>(x);
  n_seed<<<1, 512>>>(mem0);
  n_xf<<<NSEG * 4 * 14 * 32 / 256, 256>>>(x);
  n_xgemm<<<2 * NH * 28 * NSEG * 32 / 256, 256>>>(x);
  r_kernel<<<64, 384, sizeof(RSmem)>>>(mem0, g_poll_delay);
  n_qkv<<<(S_LEN * 1344 + 255) / 256, 256>>>(x, wqkv);
  n_phi<<<(S_LEN * 2 * NH + 255) / 256, 256>>>(wphi);
  n_kv<<<(32 * NH * 56 * 29 + 255) / 256, 256>>>();
  n_oa<<<(S_LEN * DM + 255) / 256, 256>>>();
  n_x3<<<NSEG, 512>>>(x, wo_a, gate_w, out);
}
```

```cpp
#include <cuda_runtime.h>
#include <cuda_bf16.h>
#include <stdint.h>
#include <stddef.h>

typedef __nv_bfloat16 bf16;
#define S_LEN 2048
#define DM 448
#define NH 16
#define NSEG 64
#define SPIN_LIMIT (1 << 22)

__device__ uint4 g_WF[2 * NH * 28 * 28 * 32];
__device__ uint4 g_KF[NSEG * NH * 4 * 4 * 4 * 32];
__device__ uint4 g_VF[NSEG * NH * 56 * 32];
__device__ float4 g_SXM[NSEG * NH * 4 * 2 * 32];
__device__ uint4 g_XF[NSEG * 4 * 14 * 32];
__device__ uint32_t g_UF[NSEG * NH * 56 * 32];
__device__ uint4 g_ACC16[(NSEG + 2) * 16 * 32];
__device__ float g_xmax[NSEG];
__device__ float g_bmax;
__device__ float g_inv0;
__device__ float g_qkv[S_LEN * 1344];
__device__ float g_phiq[S_LEN * NH * 56];
__device__ float g_phik[S_LEN * NH * 56];
__device__ float g_kv[NH * 56 * 29];
__device__ float g_oa[S_LEN * DM];
__device__ int g_err;
__device__ unsigned g_ts[64 * 64 * 64];

__device__ __forceinline__ uint32_t pack_bf16(float lo, float hi) {
  uint32_t r; asm("cvt.rn.bf16x2.f32 %0, %1, %2;" : "=r"(r) : "f"(hi), "f"(lo)); return r;
}
__device__ __forceinline__ float bf_lo(uint32_t v) { return __uint_as_float(v << 16); }
__device__ __forceinline__ float bf_hi(uint32_t v) { return __uint_as_float(v & 0xffff0000u); }
__device__ __forceinline__ float b2f(bf16 v) { return __bfloat162float(v); }

__global__ void n_prep(const bf16* Wq, const bf16* Wk, const bf16* Wv, const bf16* Wo) {
  int idx = blockIdx.x * blockDim.x + threadIdx.x;
  if (idx >= 2 * NH * 28 * 28 * 32) return;
  int lane = idx & 31, r = idx >> 5;
  int ks = r % 28; r /= 28; int tile = r % 28; r /= 28; int h = r % NH; int mat = r / NH;
  int g = lane >> 2, tq = lane & 3;
  float v[8];
  for (int i = 0; i < 8; i++) {
    int row = tile * 16 + g + ((i >> 1) & 1) * 8;
    int col = ks * 16 + tq * 2 + (i & 1) + (i >> 2) * 8;
    float acc = 0.f;
    if (mat == 0) { for (int e = 0; e < 256; e++) acc += b2f(Wq[(row * NH + h) * 256 + e]) * b2f(Wk[(col * NH + h) * 256 + e]); acc *= 0.0625f; }
    else { for (int e = 0; e < 256; e++) acc += b2f(Wo[(h * 256 + e) * DM + row]) * b2f(Wv[(col * NH + h) * 256 + e]); }
    v[i] = acc;
  }
  g_WF[idx] = make_uint4(pack_bf16(v[0], v[1]), pack_bf16(v[2], v[3]), pack_bf16(v[4], v[5]), pack_bf16(v[6], v[7]));
}
__device__ __forceinline__ float wf_elem(int mat, int h, int row, int col) {
  int tile = row >> 4, ks = col >> 4, rr = row & 15, cc = col & 15;
  int lane = (rr & 7) * 4 + ((cc & 7) >> 1);
  int reg = (rr >> 3) + (cc >> 3) * 2;
  uint32_t w = ((const uint32_t*)g_WF)[((((mat * NH + h) * 28 + tile) * 28 + ks) * 32 + lane) * 4 + reg];
  return (cc & 1) ? bf_hi(w) : bf_lo(w);
}
__device__ __forceinline__ void mma16816(float* d, uint32_t a0, uint32_t a1, uint32_t a2, uint32_t a3, uint32_t b0, uint32_t b1) {
  asm volatile("mma.sync.aligned.m16n8k16.row.col.f32.bf16.bf16.f32 {%0,%1,%2,%3}, {%4,%5,%6,%7}, {%8,%9}, {%0,%1,%2,%3};"
    : "+f"(d[0]), "+f"(d[1]), "+f"(d[2]), "+f"(d[3]) : "r"(a0), "r"(a1), "r"(a2), "r"(a3), "r"(b0), "r"(b1));
}
__device__ __forceinline__ void mma1688(float* d, uint32_t a0, uint32_t a1, uint32_t b0) {
  asm volatile("mma.sync.aligned.m16n8k8.row.col.f32.bf16.bf16.f32 {%0,%1,%2,%3}, {%4,%5}, {%6}, {%0,%1,%2,%3};"
    : "+f"(d[0]), "+f"(d[1]), "+f"(d[2]), "+f"(d[3]) : "r"(a0), "r"(a1), "r"(b0));
}
__device__ __forceinline__ uint32_t movm(uint32_t a) { uint32_t d; asm volatile("movmatrix.sync.aligned.m8n8.trans.b16 %0, %1;" : "=r"(d) : "r"(a)); return d; }

__global__ void n_xgemm(const bf16* x) {
  int wid = (blockIdx.x * blockDim.x + threadIdx.x) >> 5, lane = threadIdx.x & 31;
  int seg = wid % NSEG; int r = wid / NSEG;
  int tile = r % 28; r /= 28; int h = r % NH; int mat = r / NH;
  if (mat >= 2) return;
  int g = lane >> 2, tq = lane & 3;
  float d[4][4] = {};
  const uint4* wf = g_WF + (((mat * NH + h) * 28 + tile) * 28) * 32 + lane;
  for (int ks = 0; ks < 28; ks++) {
    uint4 a = wf[ks * 32];
    for (int kg = 0; kg < 4; kg++) {
      const uint32_t* xr = (const uint32_t*)(x + (seg * 32 + kg * 8 + g) * DM + ks * 16 + tq * 2);
      mma16816(d[kg], a.x, a.y, a.z, a.w, xr[0], xr[4]);
    }
  }
  if (mat == 0) {
    for (int kg = 0; kg < 4; kg++) {
      uint32_t b0 = movm(pack_bf16(d[kg][0], d[kg][1])), b1 = movm(pack_bf16(d[kg][2], d[kg][3]));
      int jj = tile / 7, i = tile % 7;
      uint32_t* dst = (uint32_t*)&g_KF[((((seg * NH + h) * 4 + kg) * 4 + jj) * 4 + (i >> 1)) * 32 + lane];
      if (i == 6) { dst[0] = b0; dst[1] = b1; } else { dst[i & 1] = b0; dst[2 + (i & 1)] = b1; }
    }
  } else {
    g_VF[((seg * NH + h) * 56 + tile * 2) * 32 + lane] = make_uint4(pack_bf16(d[0][0], d[0][1]), pack_bf16(d[1][0], d[1][1]), pack_bf16(d[2][0], d[2][1]), pack_bf16(d[3][0], d[3][1]));
    g_VF[((seg * NH + h) * 56 + tile * 2 + 1) * 32 + lane] = make_uint4(pack_bf16(d[0][2], d[0][3]), pack_bf16(d[1][2], d[1][3]), pack_bf16(d[2][2], d[2][3]), pack_bf16(d[3][2], d[3][3]));
  }
}
__global__ void n_zero() {
  int i = blockIdx.x * blockDim.x + threadIdx.x;
  if (i < (NSEG + 2) * 16 * 32) g_ACC16[i] = make_uint4(0, 0, 0, 0);
  if (i < NSEG) g_xmax[i] = 0.f;
  if (i == 0) g_bmax = 0.f;
  if (i < NH * 56 * 29) g_kv[i] = 0.f;
}
__global__ void n_qkv(const bf16* x, const bf16* w) {
  int i = blockIdx.x * blockDim.x + threadIdx.x;
  if (i >= S_LEN * 1344) return;
  int n = i % 1344, t = i / 1344;
  float acc = 0.f;
  for (int k = 0; k < DM; k++) acc += b2f(x[t * DM + k]) * b2f(w[k * 1344 + n]);
  g_qkv[i] = acc;
}
__global__ void n_phi(const bf16* wphi) {
  int i = blockIdx.x * blockDim.x + threadIdx.x;
  if (i >= S_LEN * 2 * NH) return;
  int h = i % NH, which = (i / NH) % 2, t = i / (2 * NH);
  float p[28]; float mx = -1e30f, mn = 1e30f;
  for (int f = 0; f < 28; f++) {
    float acc = 0.f;
    for (int d = 0; d < 28; d++) acc += g_qkv[t * 1344 + which * 448 + h * 28 + d] * b2f(wphi[(h * 28 + d) * 28 + f]);
    p[f] = acc; mx = fmaxf(mx, acc); mn = fminf(mn, acc);
  }
  float s1 = 0.f, s2 = 0.f;
  for (int f = 0; f < 28; f++) { s1 += __expf(p[f] - mx); s2 += __expf(mn - p[f]); }
  float* o = (which ? g_phik : g_phiq) + (t * NH + h) * 56;
  for (int f = 0; f < 28; f++) { o[f] = __expf(p[f] - mx) / s1; o[28 + f] = __expf(mn - p[f]) / s2; }
}
__global__ void n_kv() {
  int i = blockIdx.x * blockDim.x + threadIdx.x;
  if (i >= 32 * NH * 56 * 29) return;
  int d = i % 29, f = (i / 29) % 56, h = (i / (29 * 56)) % NH, ch = i / (29 * 56 * NH);
  float acc = 0.f;
  for (int t = ch * 64; t < ch * 64 + 64; t++) acc += g_phik[(t * NH + h) * 56 + f] * (d < 28 ? g_qkv[t * 1344 + 896 + h * 28 + d] : 1.f);
  atomicAdd(&g_kv[(h * 56 + f) * 29 + d], acc);
}
__global__ void n_oa() {
  int i = blockIdx.x * blockDim.x + threadIdx.x;
  if (i >= S_LEN * DM) return;
  int c = i % DM, t = i / DM, h = c / 28, d = c % 28;
  float num = 0.f, den = 0.f;
  for (int f = 0; f < 56; f++) { float p = g_phiq[(t * NH + h) * 56 + f]; num += p * g_kv[(h * 56 + f) * 29 + d]; den += p * g_kv[(h * 56 + f) * 29 + 28]; }
  g_oa[i] = num / (den + 1e-6f);
}

__global__ void __launch_bounds__(512) n_x3(const bf16* x, const bf16* wo, const bf16* gate_w, bf16* out) {
  __shared__ uint32_t sP[NH][2][32][10];
  __shared__ float sG[32];
  int seg = blockIdx.x, w = threadIdx.x >> 5, lane = threadIdx.x & 31, g = lane >> 2, tq = lane & 3;
  for (int r = w; r < 32; r += 16) {
    float acc = 0.f;
    for (int k = lane; k < DM; k += 32) acc += b2f(x[(seg * 32 + r) * DM + k]) * b2f(gate_w[k]);
    for (int o = 16; o; o >>= 1) acc += __shfl_xor_sync(0xffffffffu, acc, o);
    if (lane == 0) sG[r] = 1.f / (1.f + __expf(-acc));
  }
  {
    int h = w;
    float s[2][5][4] = {};
    for (int ct = 0; ct < 28; ct++) {
      uint32_t a[2][4];
      for (int m = 0; m < 2; m++) {
        const uint32_t* r0 = (const uint32_t*)(x + (seg * 32 + m * 16 + g) * DM + ct * 16 + tq * 2);
        const uint32_t* r1 = (const uint32_t*)(x + (seg * 32 + m * 16 + g + 8) * DM + ct * 16 + tq * 2);
        a[m][0] = r0[0]; a[m][1] = r1[0]; a[m][2] = r0[4]; a[m][3] = r1[4];
      }
      int j = ct / 7, i = ct % 7;
      for (int kg = 0; kg < 4; kg++) {
        const uint32_t* src = (const uint32_t*)&g_KF[((((seg * NH + h) * 4 + kg) * 4 + j) * 4 + (i >> 1)) * 32 + lane];
        uint2 b = i == 6 ? make_uint2(src[0], src[1]) : make_uint2(src[i & 1], src[2 + (i & 1)]);
        for (int m = 0; m < 2; m++) mma16816(s[m][1 + kg], a[m][0], a[m][1], a[m][2], a[m][3], b.x, b.y);
      }
    }
    for (int m = 0; m < 2; m++) for (int j = 0; j < 4; j++) {
      float4 t = g_SXM[(((seg * NH + h) * 4 + j) * 2 + m) * 32 + lane];
      s[m][0][0] += t.x; s[m][0][1] += t.y; s[m][0][2] += t.z; s[m][0][3] += t.w;
    }
    for (int m = 0; m < 2; m++) for (int hf = 0; hf < 2; hf++) {
      int t = m * 16 + hf * 8 + g;
      float v[10]; float mx = -1e30f;
      for (int n = 0; n < 5; n++) for (int e = 0; e < 2; e++) {
        float val = s[m][n][hf * 2 + e];
        if (n > 0 && (n - 1) * 8 + tq * 2 + e > t) val = -1e30f;
        v[n * 2 + e] = val; mx = fmaxf(mx, val);
      }
      mx = fmaxf(mx, __shfl_xor_sync(0xffffffffu, mx, 1)); mx = fmaxf(mx, __shfl_xor_sync(0xffffffffu, mx, 2));
      float z = 0.f;
      for (int i = 0; i < 10; i++) { v[i] = __expf(v[i] - mx); z += v[i]; }
      z += __shfl_xor_sync(0xffffffffu, z, 1); z += __shfl_xor_sync(0xffffffffu, z, 2);
      float iz = 1.f / z;
      sP[h][m][lane][hf] = pack_bf16(v[0] * iz, v[1] * iz);
      sP[h][m][lane][2 + hf] = pack_bf16(v[2] * iz, v[3] * iz);
      sP[h][m][lane][4 + hf] = pack_bf16(v[4] * iz, v[5] * iz);
      sP[h][m][lane][6 + hf] = pack_bf16(v[6] * iz, v[7] * iz);
      sP[h][m][lane][8 + hf] = pack_bf16(v[8] * iz, v[9] * iz);
    }
  }
  __syncthreads();
  if (w < 14) {
    float o[2][4][4] = {};
    for (int h = 0; h < NH; h++) {
      for (int n = 0; n < 4; n++) {
        int nt = w * 4 + n;
        uint4 v = g_VF[((seg * NH + h) * 56 + nt) * 32 + lane];
        uint32_t u = g_UF[((seg * NH + h) * 56 + nt) * 32 + lane];
        for (int m = 0; m < 2; m++) {
          const uint32_t* p = sP[h][m][lane];
          mma1688(o[m][n], p[0], p[1], u);
          mma16816(o[m][n], p[2], p[3], p[4], p[5], v.x, v.y);
          mma16816(o[m][n], p[6], p[7], p[8], p[9], v.z, v.w);
        }
      }
    }
    for (int m = 0; m < 2; m++) for (int n = 0; n < 4; n++) for (int i = 0; i < 4; i++) {
      int r = m * 16 + (i >> 1) * 8 + g, c = (w * 4 + n) * 8 + tq * 2 + (i & 1);
      int t = seg * 32 + r;
      float a = 0.f;
      for (int k = 0; k < DM; k++) a += g_oa[t * DM + k] * b2f(wo[k * DM + c]);
      float gt = sG[r];
      out[t * DM + c] = __float2bfloat16(gt * a + (1.f - gt) * o[m][n][i]);
    }
  }
}

__device__ __forceinline__ uint32_t smem_u32(const void* p) { return (uint32_t)__cvta_generic_to_shared(p); }
__device__ __forceinline__ uint32_t mapa(uint32_t a, uint32_t r) { uint32_t o; asm volatile("mapa.shared::cluster.u32 %0, %1, %2;" : "=r"(o) : "r"(a), "r"(r)); return o; }
__device__ __forceinline__ bool try_wait(uint32_t bar, uint32_t parity) {
  uint32_t ok; asm volatile("{\n.reg .pred p;\nmbarrier.try_wait.parity.shared::cta.b64 p, [%1], %2;\nselp.u32 %0, 1, 0, p;\n}" : "=r"(ok) : "r"(bar), "r"(parity) : "memory"); return ok; }
__device__ __forceinline__ void wait_bar(uint32_t bar, uint32_t parity) {
  int n = 0; while (!try_wait(bar, parity)) { if (++n > SPIN_LIMIT) { g_err = 1; break; } } }
__device__ __forceinline__ void arm_bar(uint32_t bar, uint32_t bytes) { asm volatile("mbarrier.arrive.expect_tx.shared::cta.b64 _, [%0], %1;" :: "r"(bar), "r"(bytes) : "memory"); }
__device__ __forceinline__ float4 ld_relaxed4(const void* p) { float4 v; asm volatile("ld.relaxed.gpu.global.v4.f32 {%0,%1,%2,%3}, [%4];" : "=f"(v.x), "=f"(v.y), "=f"(v.z), "=f"(v.w) : "l"(p) : "memory"); return v; }
__device__ __forceinline__ void red4(void* p, float a, float b, float c, float d) { asm volatile("red.relaxed.gpu.global.add.v4.f32 [%0], {%1,%2,%3,%4};" :: "l"(p), "f"(a), "f"(b), "f"(c), "f"(d) : "memory"); }
__device__ __forceinline__ void st_async2(uint32_t dst, float a, float b, uint32_t bar) { asm volatile("st.async.shared::cluster.mbarrier::complete_tx::bytes.v2.f32 [%0], {%1,%2}, [%3];" :: "r"(dst), "f"(a), "f"(b), "r"(bar) : "memory"); }
__device__ __forceinline__ void bulk_g2s(uint32_t dst, const void* src, uint32_t bytes, uint32_t bar) {
  asm volatile("cp.async.bulk.shared::cluster.global.mbarrier::complete_tx::bytes [%0], [%1], %2, [%3];" :: "r"(dst), "l"(src), "r"(bytes), "r"(bar) : "memory"); }
__device__ __forceinline__ unsigned clk() { unsigned c; asm volatile("mov.u32 %0, %%clock;" : "=r"(c) :: "memory"); return c; }
__device__ __forceinline__ float ex2(float x) { float y; asm("ex2.approx.ftz.f32 %0, %1;" : "=f"(y) : "f"(x)); return y; }

#define NST 4
struct QBlk {
  uint4 memF[4][32];
  uint4 wA[7][32], wB[7][32];
  uint4 kf[NST][4][32];
  float4 xred[2][32];
  float4 red[32];
  uint4 uQ[4][32];
  uint4 kq[2][4][32];
};
#define QB ((uint32_t)sizeof(QBlk))
#define QOFF(f) ((uint32_t)offsetof(QBlk, f))
struct RSmem {
  QBlk qb[4];
  uint4 vf[NST][14][32];
  uint4 xf[NST][14][32];
  float4 sx[2][32];
  float4 sm[2][32];
  uint32_t smax[4];
  float xmax[NSEG];
  float sinv[4];
  unsigned long long bar_ld[NST], bar_sx, bar_sm;
  unsigned ts[64 * 64];
};
#define LD_BYTES (8192 + 7168 + 7168)
#define POLL_DELAY 300
#define STAMP(i)
__device__ __forceinline__ void wait_slow(uint32_t bar, uint32_t parity) {
#pragma unroll 1
  for (int n = 0; n < SPIN_LIMIT; n++) if (try_wait(bar, parity)) return;
  g_err = 1;
}
__device__ __forceinline__ void wait_bar1(uint32_t bar, uint32_t parity) { if (!try_wait(bar, parity)) wait_slow(bar, parity); }
__device__ __forceinline__ uint4 ld_relaxed_u4(const void* p) { uint4 v; asm volatile("ld.relaxed.gpu.global.v4.u32 {%0,%1,%2,%3}, [%4];" : "=r"(v.x), "=r"(v.y), "=r"(v.z), "=r"(v.w) : "l"(p) : "memory"); return v; }
__device__ __forceinline__ void red_h8(void* p, uint32_t a, uint32_t b, uint32_t c, uint32_t d) { asm volatile("red.relaxed.gpu.global.add.noftz.v4.f16x2 [%0], {%1,%2,%3,%4};" :: "l"(p), "r"(a), "r"(b), "r"(c), "r"(d) : "memory"); }
__device__ __forceinline__ uint32_t pack_f16(float lo, float hi) { uint32_t r; asm("cvt.rn.f16x2.f32 %0, %1, %2;" : "=r"(r) : "f"(hi), "f"(lo)); return r; }
__device__ __forceinline__ uint32_t h2_to_bf2(uint32_t v) {
  float lo, hi; asm("{.reg .f16 l, h; mov.b32 {l, h}, %2; cvt.f32.f16 %0, l; cvt.f32.f16 %1, h;}" : "=f"(lo), "=f"(hi) : "r"(v)); return pack_bf16(lo, hi); }
__device__ __forceinline__ uint2 lds64(uint32_t a) { uint2 v; asm volatile("ld.shared.v2.u32 {%0,%1}, [%2];" : "=r"(v.x), "=r"(v.y) : "r"(a) : "memory"); return v; }
__device__ __forceinline__ float2 lds64f(uint32_t a) { float2 v; asm volatile("ld.shared.v2.f32 {%0,%1}, [%2];" : "=f"(v.x), "=f"(v.y) : "r"(a) : "memory"); return v; }
__device__ __forceinline__ uint4 lds128(uint32_t a) { uint4 v; asm volatile("ld.shared.v4.u32 {%0,%1,%2,%3}, [%4];" : "=r"(v.x), "=r"(v.y), "=r"(v.z), "=r"(v.w) : "r"(a) : "memory"); return v; }
__device__ __forceinline__ uint4 lds128v(uint32_t a) { uint4 v; asm volatile("ld.volatile.shared.v4.u32 {%0,%1,%2,%3}, [%4];" : "=r"(v.x), "=r"(v.y), "=r"(v.z), "=r"(v.w) : "r"(a) : "memory"); return v; }
__device__ __forceinline__ uint32_t lds32(uint32_t a) { uint32_t v; asm volatile("ld.shared.u32 %0, [%1];" : "=r"(v) : "r"(a) : "memory"); return v; }
__device__ __forceinline__ void sts64(uint32_t a, uint32_t x, uint32_t y) { asm volatile("st.shared.v2.u32 [%0], {%1,%2};" :: "r"(a), "r"(x), "r"(y) : "memory"); }
__device__ __forceinline__ void sts64f(uint32_t a, float x, float y) { asm volatile("st.shared.v2.f32 [%0], {%1,%2};" :: "r"(a), "f"(x), "f"(y) : "memory"); }
__device__ __forceinline__ void sts32(uint32_t a, uint32_t x) { asm volatile("st.shared.u32 [%0], %1;" :: "r"(a), "r"(x) : "memory"); }
__device__ __forceinline__ void mma_z(float* d, uint32_t a0, uint32_t a1, uint32_t a2, uint32_t a3, uint32_t b0, uint32_t b1) {
  asm volatile("mma.sync.aligned.m16n8k16.row.col.f32.bf16.bf16.f32 {%0,%1,%2,%3}, {%4,%5,%6,%7}, {%8,%9}, {%10,%10,%10,%10};"
    : "=f"(d[0]), "=f"(d[1]), "=f"(d[2]), "=f"(d[3]) : "r"(a0), "r"(a1), "r"(a2), "r"(a3), "r"(b0), "r"(b1), "f"(0.f));
}
__device__ __forceinline__ void mma8_z(float* d, uint32_t a0, uint32_t a1, uint32_t b0) {
  asm volatile("mma.sync.aligned.m16n8k8.row.col.f32.bf16.bf16.f32 {%0,%1,%2,%3}, {%4,%5}, {%6}, {%7,%7,%7,%7};"
    : "=f"(d[0]), "=f"(d[1]), "=f"(d[2]), "=f"(d[3]) : "r"(a0), "r"(a1), "r"(b0), "f"(0.f));
}
#define OFF(f) ((uint32_t)offsetof(RSmem, f))
#define BAR_SYNC(id, n) asm volatile("bar.sync %0, %1;" :: "n"(id), "n"(n) : "memory")
#define BAR_ARRIVE(id, n) asm volatile("bar.arrive %0, %1;" :: "n"(id), "n"(n) : "memory")

__device__ __forceinline__ void sts128(uint32_t a, uint32_t x, uint32_t y, uint32_t z, uint32_t w) { asm volatile("st.shared.v4.u32 [%0], {%1,%2,%3,%4};" :: "r"(a), "r"(x), "r"(y), "r"(z), "r"(w) : "memory"); }
template <int K>
__device__ __forceinline__ void kstep(const uint4 (&W)[42], float (&acc)[7][4], uint32_t b0, uint32_t b1, uint4& w6, uint32_t ws) {
#pragma unroll
  for (int t = 0; t < 6; t++) {
    const uint4& w = W[K * 6 + t];
    if (K == 0) mma_z(acc[t], w.x, w.y, w.z, w.w, b0, b1); else mma16816(acc[t], w.x, w.y, w.z, w.w, b0, b1);
  }
  if (K == 0) mma_z(acc[6], w6.x, w6.y, w6.z, w6.w, b0, b1); else mma16816(acc[6], w6.x, w6.y, w6.z, w6.w, b0, b1);
  if (K < 6) w6 = lds128(ws + (K + 1) * 512);
}
__device__ __forceinline__ uint4* acc_ptr(int step, int vec, int lane) { return g_ACC16 + (((step >> 1) * 16 + vec) * 2 + (step & 1)) * 32 + lane; }

__device__ __forceinline__ bool elect1() { uint32_t p; asm volatile("{.reg .pred p; elect.sync _|p, 0xffffffff; selp.u32 %0, 1, 0, p;}" : "=r"(p)); return p; }
__device__ __forceinline__ float4 lds128f(uint32_t a) { float4 v; asm volatile("ld.shared.v4.f32 {%0,%1,%2,%3}, [%4];" : "=f"(v.x), "=f"(v.y), "=f"(v.z), "=f"(v.w) : "r"(a) : "memory"); return v; }
__device__ __forceinline__ float ex2v(float x) { float y; asm volatile("ex2.approx.ftz.f32 %0, %1;" : "=f"(y) : "f"(x)); return y; }
__device__ __forceinline__ uint32_t hadd_bf2(uint32_t a, uint32_t b) { uint32_t d; asm("add.rn.bf16x2 %0, %1, %2;" : "=r"(d) : "r"(a), "r"(b)); return d; }
__device__ __forceinline__ uint32_t amax2(uint32_t m, uint32_t x, uint32_t y) { return __vmaxu2(m, __vmaxu2(x & 0x7fff7fffu, y & 0x7fff7fffu)); }

#define FENCE(n) do { if (__builtin_expect((poll_delay >> (16 + (n))) & 1, 0)) { _Pragma("unroll 1") for (int i_ = poll_delay & 7; i_ > 0; i_--) asm volatile("nanosleep.u32 %0;" :: "n"(n) : "memory"); } } while (0)
#define BAR_SYNC_R(id, n) asm volatile("bar.sync %0, %1;" :: "r"(id), "n"(n) : "memory")
#define BAR_ARRIVE_R(id, n) asm volatile("bar.arrive %0, %1;" :: "r"(id), "n"(n) : "memory")
#define MMW(A, WW, B0, B1, first) do { if (first) mma_z(A, WW.x, WW.y, WW.z, WW.w, B0, B1); else mma16816(A, WW.x, WW.y, WW.z, WW.w, B0, B1); } while (0)
__device__ __forceinline__ void issue_loads(uint32_t sb, int s, int h, int j) {
  const int st = s & (NST - 1), s0 = s;
  const uint32_t bar = sb + OFF(bar_ld) + 8 * st;
  arm_bar(bar, LD_BYTES);
#pragma unroll
  for (int qq = 0; qq < 4; qq++) bulk_g2s(sb + qq * QB + QOFF(kf) + st * 2048, g_KF + ((s * NH + h) * 4 + j) * 512 + qq * 128, 2048, bar);
  bulk_g2s(sb + OFF(vf) + st * 7168, g_VF + ((s * NH + h) * 56 + 14 * j) * 32, 7168, bar);
  bulk_g2s(sb + OFF(xf) + st * 7168, g_XF + (s * 4 + j) * 448, 7168, bar);
  asm volatile("prefetch.global.L2 [%0];" :: "l"(acc_ptr(s0, h, j * 8)));
}
__device__ __forceinline__ int opaque_lane() { return __shfl_sync(0xffffffffu, threadIdx.x & 31, threadIdx.x & 31); }

__global__ void __cluster_dims__(4, 1, 1) __launch_bounds__(384, 1) r_kernel(const bf16* mem0, int poll_delay) {
  extern __shared__ __align__(128) unsigned char smem_raw[];
  RSmem& sm = *reinterpret_cast<RSmem*>(smem_raw);
  const int h = blockIdx.x >> 2, j = blockIdx.x & 3;
  const int w = __shfl_sync(0xffffffffu, threadIdx.x >> 5, 0), q = w & 3, role = w >> 2;
  const uint32_t sb = smem_u32(smem_raw);
  const uint32_t bar_ld = sb + OFF(bar_ld), bar_sx = sb + OFF(bar_sx), bar_sm = sb + OFF(bar_sm);
  if (threadIdx.x == 0) {
    for (int i = 0; i < NST; i++) asm volatile("mbarrier.init.shared::cta.b64 [%0], 1;" :: "r"(bar_ld + 8 * i));
    asm volatile("mbarrier.init.shared::cta.b64 [%0], 1;" :: "r"(bar_sx));
    asm volatile("mbarrier.init.shared::cta.b64 [%0], 1;" :: "r"(bar_sm));
    asm volatile("fence.mbarrier_init.release.cluster;" ::: "memory");
    arm_bar(bar_sx, 1024); arm_bar(bar_sm, 1024);
    for (int s = 0; s < NST; s++) issue_loads(sb, s, h, j);
    sm.sinv[0] = g_inv0;
  }
  if (threadIdx.x < NSEG) sm.xmax[threadIdx.x] = g_xmax[threadIdx.x];
  if (role < 2) {
    const int lane = threadIdx.x & 31;
    const uint4* wf = g_WF + (((role * NH + h) * 28 + 7 * j) * 28 + 7 * q) * 32 + lane;
#pragma unroll
    for (int e = 0; e < 7; e++) (role ? sm.qb[q].wB : sm.qb[q].wA)[e][lane] = wf[e * 28 * 32];
  }
  asm volatile("barrier.cluster.arrive.release.aligned;\nbarrier.cluster.wait.acquire.aligned;" ::: "memory");
  const float LOG2E = 1.4426950408889634f;

  if (role == 0) {
    asm volatile("setmaxnreg.inc.sync.aligned.u32 224;");
    const int lane = opaque_lane();
    const uint32_t l16 = sb + lane * 16;
    uint4 W[42];
    {
      const uint4* wf = g_WF + ((h * 28 + 7 * j) * 28 + 7 * q) * 32 + lane;
#pragma unroll
      for (int k = 1; k < 7; k++)
#pragma unroll
        for (int t = 0; t < 7; t++) W[(k - 1) * 7 + t] = wf[(t * 28 + k) * 32];
    }
    const uint32_t lq = l16 + q * QB, mj = l16 + j * QB;
#define ws (lq + QOFF(wA))
#define mq lq
    const uint32_t dst_sm = mapa(l16 + OFF(sm) + (j >> 1) * 512 + (j & 1) * 8, q), dst_bar = mapa(bar_sm, q);
    const uint4* p = acc_ptr(0, q * 4, lane);
#define TM(t, k) do { if ((k) == 0) mma_z(acc[t], f[t].x, f[t].y, f[t].z, f[t].w, b[0], b[1]); else { const uint4& w_ = W[((k) - 1) * 7 + (t)]; mma16816(acc[t], w_.x, w_.y, w_.z, w_.w, b[2 * (k)], b[2 * (k) + 1]); } } while (0)
#define T3(k) do { TM(0, k); TM(1, k); TM(2, k); } while (0)
#define T4(k) do { TM(3, k); TM(4, k); TM(5, k); TM(6, k); } while (0)
#define TR(t) do { kl[t] = movm(pack_bf16(acc[t][0], acc[t][1])); kh[t] = movm(pack_bf16(acc[t][2], acc[t][3])); } while (0)
    wait_bar1(bar_ld, 0);
#pragma unroll 1
    for (int s = 0; s < NSEG; s++) {
      STAMP(0);
      uint4 v0 = ld_relaxed_u4(p), v1 = ld_relaxed_u4(p + 64), v2 = ld_relaxed_u4(p + 128), v3 = ld_relaxed_u4(p + 192);
      const uint32_t kb = lq + QOFF(kf) + (s & (NST - 1)) * 2048;
      uint4 k0 = lds128(kb), k1 = lds128(kb + 512), k2 = lds128(kb + 1024); uint2 k3 = lds64(kb + 1536);
      uint4 f[7];
      f[0] = lds128v(ws); f[1] = lds128v(ws + 512); f[2] = lds128v(ws + 1024);
      if (!__all_sync(0xffffffffu, __byte_perm(v0.w, v1.w, 0x7632) == 0x4C004C00u && __byte_perm(v2.w, v3.w, 0x7632) == 0x4C004C00u)) {
#pragma unroll 1
        for (int n = 0; n < SPIN_LIMIT; n++) {
          v0 = ld_relaxed_u4(p); v1 = ld_relaxed_u4(p + 64); v2 = ld_relaxed_u4(p + 128); v3 = ld_relaxed_u4(p + 192);
          if (__all_sync(0xffffffffu, __byte_perm(v0.w, v1.w, 0x7632) == 0x4C004C00u && __byte_perm(v2.w, v3.w, 0x7632) == 0x4C004C00u)) break;
        }
      }
      STAMP(1);
      uint32_t b[14];
      float dl[4], dh[4], el[4], eh[4];
      b[0] = h2_to_bf2(v0.x); b[1] = h2_to_bf2(v0.y); b[2] = h2_to_bf2(v0.z); b[3] = h2_to_bf2(v1.x);
      mma_z(dl, b[0], b[1], b[2], b[3], k0.x, k0.y); mma_z(dh, b[0], b[1], b[2], b[3], k0.z, k0.w);
      b[4] = h2_to_bf2(v1.y); b[5] = h2_to_bf2(v1.z);
      b[6] = h2_to_bf2(__byte_perm(v0.w, v1.w, 0x5410)); b[7] = h2_to_bf2(__byte_perm(v2.w, v3.w, 0x5410));
      mma_z(el, b[4], b[5], b[6], b[7], k1.x, k1.y); mma_z(eh, b[4], b[5], b[6], b[7], k1.z, k1.w);
      b[8] = h2_to_bf2(v2.x); b[9] = h2_to_bf2(v2.y); b[10] = h2_to_bf2(v2.z); b[11] = h2_to_bf2(v3.x);
      mma16816(dl, b[8], b[9], b[10], b[11], k2.x, k2.y); mma16816(dh, b[8], b[9], b[10], b[11], k2.z, k2.w);
      b[12] = h2_to_bf2(v3.y); b[13] = h2_to_bf2(v3.z);
      mma1688(el, b[12], b[13], k3.x); mma1688(eh, b[12], b[13], k3.y);
      float acc[7][4];
      T3(0); T3(1);
      sts64f(lq + QOFF(red) + 8, (dl[0] + dh[2]) + (el[0] + eh[2]), (dl[1] + dh[3]) + (el[1] + eh[3]));
      BAR_ARRIVE(14, 256);
      f[3] = lds128(ws + 1536); f[4] = lds128(ws + 2048); f[5] = lds128(ws + 2560); f[6] = lds128(ws + 3072);
      sts128(mq, b[0], b[1], b[2], b[3]); sts128(mq + 512, b[4], b[5], b[6], b[7]); sts128(mq + 1024, b[8], b[9], b[10], b[11]); sts64(mq + 1536, b[12], b[13]);
      BAR_ARRIVE_R(5 + q, 64);
      T3(2);
      FENCE(2);
      T3(3); T4(0); T3(4); T4(1); T3(5); T4(2); T3(6); T4(3);
      FENCE(4);
      BAR_SYNC(1, 128);
      uint4 a0 = lds128(mj), a1 = lds128(mj + 512), a2 = lds128(mj + 1024); uint2 a3 = lds64(mj + 1536);
      uint32_t kl[7], kh[7];
      T4(4); TR(0); TR(1); T4(5); TR(2); T4(6);
      mma_z(dl, a0.x, a0.y, a0.z, a0.w, kl[0], kl[1]); mma_z(dh, a0.x, a0.y, a0.z, a0.w, kh[0], kh[1]);
      BAR_ARRIVE_R(10 + q, 64);
      FENCE(5);
      STAMP(3);
      TR(3); TR(4); TR(5); TR(6);
      mma_z(el, a1.x, a1.y, a1.z, a1.w, kl[2], kl[3]); mma_z(eh, a1.x, a1.y, a1.z, a1.w, kh[2], kh[3]);
      mma16816(dl, a2.x, a2.y, a2.z, a2.w, kl[4], kl[5]); mma16816(dh, a2.x, a2.y, a2.z, a2.w, kh[4], kh[5]);
      float gl[4], gh[4];
      mma8_z(gl, a3.x, a3.y, kl[6]); mma8_z(gh, a3.x, a3.y, kh[6]);
      dl[0] += el[0]; dh[2] += eh[2]; dl[1] += el[1]; dh[3] += eh[3]; el[0] = gl[0]; el[1] = gl[1]; eh[2] = gh[2]; eh[3] = gh[3];
      sts64f(lq + QOFF(red), (dl[0] + dh[2]) + (el[0] + eh[2]), (dl[1] + dh[3]) + (el[1] + eh[3]));
      BAR_SYNC(2, 128);
      {
        float2 t0 = lds64f(l16 + QOFF(red)), t1 = lds64f(l16 + QOFF(red) + QB), t2 = lds64f(l16 + QOFF(red) + 2 * QB), t3 = lds64f(l16 + QOFF(red) + 3 * QB);
        st_async2(dst_sm, (t0.x + t1.x) + (t2.x + t3.x), (t0.y + t1.y) + (t2.y + t3.y), dst_bar);
      }
      STAMP(4);
      { const uint32_t kqa = lq + QOFF(kq) + (s & 1) * 2048;
      sts128(kqa, kl[0], kl[1], kh[0], kh[1]); sts128(kqa + 512, kl[2], kl[3], kh[2], kh[3]);
      sts128(kqa + 1024, kl[4], kl[5], kh[4], kh[5]); sts64(kqa + 1536, kl[6], kh[6]); }
      p += (s & 1) ? (1024 - 32) : 32;
      if (q == 1 && s >= 2 && s + 2 < NSEG) { if (elect1()) issue_loads(sb, s + 2, h, j); __syncwarp(); }
      if (s + 1 < NSEG) wait_bar1(bar_ld + 8 * ((s + 1) & (NST - 1)), ((s + 1) / NST) & 1);
      BAR_SYNC(4, 384);
      unsigned tred = clk();
      if (q == 0) { if (elect1()) { arm_bar(bar_sx, 1024); arm_bar(bar_sm, 1024); } __syncwarp(); }
      while (clk() - tred < (unsigned)(poll_delay & 0xffff)) {}
    }
  } else if (role == 1) {
    asm volatile("setmaxnreg.inc.sync.aligned.u32 216;");
    const int lane = opaque_lane();
    const uint32_t l16 = sb + lane * 16;
    uint4 W[42];
    {
      const uint4* wf = g_WF + (((NH + h) * 28 + 7 * j) * 28 + 7 * q) * 32 + lane;
#pragma unroll
      for (int k = 1; k < 7; k++)
#pragma unroll
        for (int t = 0; t < 7; t++) W[(k - 1) * 7 + t] = wf[(t * 28 + k) * 32];
    }
#undef ws
#define ws (lq + QOFF(wB))
    const uint32_t lq = l16 + q * QB;
#define uq (lq + QOFF(uQ))
#pragma unroll 1
    for (int s = 0; s < NSEG; s++) {
      const int st = s & (NST - 1);
      uint4 f[7];
#pragma unroll
      for (int t = 0; t < 7; t++) f[t] = lds128(ws + t * 512);
      BAR_SYNC_R(5 + q, 64);
      uint4 p0 = lds128(mq), p1 = lds128(mq + 512), p2 = lds128(mq + 1024); uint2 p3 = lds64(mq + 1536);
      {
        uint32_t m = amax2(amax2(amax2(amax2(0u, p0.x, p0.y), p0.z, p0.w), p1.x, p1.y), p1.z, p1.w);
        m = amax2(amax2(amax2(m, p2.x, p2.y), p2.z, p2.w), p3.x, p3.y);
        m = max(m & 0xffffu, m >> 16);
        m = __reduce_max_sync(0xffffffffu, m);
        sts32(sb + OFF(smax) + q * 4, m);
      }
      BAR_ARRIVE(9, 256);
      BAR_SYNC_R(10 + q, 64);
      FENCE(7);
      STAMP(10);
      const uint32_t b[14] = {p0.x, p0.y, p0.z, p0.w, p1.x, p1.y, p1.z, p1.w, p2.x, p2.y, p2.z, p2.w, p3.x, p3.y};
      float acc[7][4];
      T3(0); T3(1); T3(2); T3(3); T3(4); T3(5); T3(6);
      FENCE(8);
#define UP(nt) pack_bf16(acc[(nt) >> 1][((nt) & 1) * 2], acc[(nt) >> 1][((nt) & 1) * 2 + 1])
      T4(0); T4(1); T4(2); T4(3); T4(4); T4(5); T4(6);
      { uint32_t u6 = UP(6), u7 = UP(7);
        sts128(uq, UP(0), UP(1), UP(2), u6); sts128(uq + 512, UP(3), UP(4), UP(5), u6);
        sts128(uq + 1024, UP(8), UP(9), UP(10), u7); sts128(uq + 1536, UP(11), UP(12), UP(13), u7); }
      BAR_ARRIVE(3, 256);
      STAMP(11);
      const float inv = __uint_as_float(lds32(sb + OFF(sinv) + (s & 1) * 4));
      BAR_SYNC(4, 384);
      {
        const int nt0 = q < 2 ? q * 3 : 8 + (q - 2) * 3, nts = 6 + (q >> 1);
        uint32_t ub = l16 + QOFF(uQ) + q * 512; asm volatile("" : "+r"(ub));
        uint4 u0 = lds128(ub), u1 = lds128(ub + QB), u2 = lds128(ub + 2 * QB), u3 = lds128(ub + 3 * QB);
        auto us = [&](uint32_t a, uint32_t b, uint32_t c, uint32_t d) { return pack_bf16(((bf_lo(a) + bf_lo(b)) + (bf_lo(c) + bf_lo(d))) * inv, ((bf_hi(a) + bf_hi(b)) + (bf_hi(c) + bf_hi(d))) * inv); };
        uint32_t* uf = (uint32_t*)((char*)(g_UF + ((s * NH + h) * 56 + 14 * j) * 32) + ((l16 - sb) >> 2));
        { uf[(nt0 + 0) * 32] = us(u0.x, u1.x, u2.x, u3.x); uf[(nt0 + 1) * 32] = us(u0.y, u1.y, u2.y, u3.y); uf[(nt0 + 2) * 32] = us(u0.z, u1.z, u2.z, u3.z);
        if ((q & 1) == 0) uf[nts * 32] = us(u0.w, u1.w, u2.w, u3.w); }
      }
      {
        const uint32_t xb = l16 + OFF(xf) + st * 7168;
        const uint32_t kqa = lq + QOFF(kq) + (s & 1) * 2048;
        uint4 k0 = lds128(kqa), k1 = lds128(kqa + 512), k2 = lds128(kqa + 1024); uint2 k3 = lds64(kqa + 1536);
        const uint32_t kk[14] = {k0.x, k0.y, k0.z, k0.w, k1.x, k1.y, k1.z, k1.w, k2.x, k2.y, k2.z, k2.w, k3.x, k3.y};
        float y[2][4];
#pragma unroll
        for (int f = 0; f < 7; f++)
#pragma unroll
          for (int m = 0; m < 2; m++) {
            uint4 xa = lds128(xb + (f * 2 + m) * 512);
            MMW(y[m], xa, kk[2 * f], kk[2 * f + 1], f == 0);
          }
        sts128(lq + QOFF(xred), __float_as_uint(y[0][0]), __float_as_uint(y[0][1]), __float_as_uint(y[0][2]), __float_as_uint(y[0][3]));
        sts128(lq + QOFF(xred) + 512, __float_as_uint(y[1][0]), __float_as_uint(y[1][1]), __float_as_uint(y[1][2]), __float_as_uint(y[1][3]));
        BAR_SYNC(15, 128);
        if (q < 2) {
          uint32_t xr = l16 + QOFF(xred) + q * 512; asm volatile("" : "+r"(xr));
          float4 t0 = lds128f(xr), t1 = lds128f(xr + QB), t2 = lds128f(xr + 2 * QB), t3 = lds128f(xr + 3 * QB);
          *(float4*)((char*)(g_SXM + ((((s * NH + h) * 4 + j) * 2 + q) * 32)) + (l16 - sb)) = make_float4(((t0.x + t1.x) + (t2.x + t3.x)) * inv, ((t0.y + t1.y) + (t2.y + t3.y)) * inv, ((t0.z + t1.z) + (t2.z + t3.z)) * inv, ((t0.w + t1.w) + (t2.w + t3.w)) * inv);
        }
      }
    }
  } else {
    asm volatile("setmaxnreg.dec.sync.aligned.u32 64;");
    const int lane = opaque_lane();
    const uint32_t l16 = sb + lane * 16;
    const int nt0 = q < 2 ? q * 3 : 8 + (q - 2) * 3, nts = 6 + (q >> 1);
    const float bmax = g_bmax;
    int se = (int)(127 - (__float_as_uint(g_inv0) >> 23));
    uint4* redp = acc_ptr(1, j * 4 + q, lane);
    const uint32_t dst_sx = mapa(l16 + OFF(sx) + (j >> 1) * 512 + (j & 1) * 8, q), dst_bar = mapa(bar_sx, q);
#pragma unroll 1
    for (int s = 0; s < NSEG; s++) {
      const int st = s & (NST - 1);
      float ya[4], yb[4], z[4];
      float mx;
      int nse;
      const float inv = __uint_as_float((uint32_t)(127 - se) << 23);
      const float c1 = LOG2E * inv;
      {
        const uint32_t vb = l16 + OFF(vf) + st * 7168;
        wait_bar1(bar_ld + 8 * st, (s / NST) & 1);
        uint4 v0 = lds128(vb + nt0 * 512), v1 = lds128(vb + nt0 * 512 + 512), v2 = lds128(vb + nt0 * 512 + 1024), v3 = lds128(vb + nts * 512);
        BAR_SYNC(14, 256);
        STAMP(2);
        {
          float2 t0 = lds64f(l16 + QOFF(red) + 8), t1 = lds64f(l16 + QOFF(red) + 8 + QB), t2 = lds64f(l16 + QOFF(red) + 8 + 2 * QB), t3 = lds64f(l16 + QOFF(red) + 8 + 3 * QB);
          st_async2(dst_sx, (t0.x + t1.x) + (t2.x + t3.x), (t0.y + t1.y) + (t2.y + t3.y), dst_bar);
        }
        STAMP(9);
        BAR_SYNC(9, 256);
        {
          uint4 m4 = lds128(sb + OFF(smax));
          uint32_t mb = max(max(m4.x, m4.y), max(m4.z, m4.w));
          float mh = fmaxf(__uint_as_float(mb << 16) * inv, __uint_as_float(lds32(sb + OFF(xmax) + s * 4)));
          float bound = mh * bmax;
          int e = (int)(__float_as_uint(bound) >> 23) - 127 + 10;
          nse = min(max(15 - e, -60), 60);
        }
        const uint32_t one_n = (uint32_t)(127 - nse) * 0x00800080u;
        wait_bar1(bar_sx, s & 1);
        STAMP(12);
        float4 x0 = lds128f(l16 + OFF(sx)), x1 = lds128f(l16 + OFF(sx) + 512);
        float sx[8] = {x0.x, x0.y, x0.z, x0.w, x1.x, x1.y, x1.z, x1.w};
        mx = fmaxf(fmaxf(fmaxf(sx[0], sx[1]), fmaxf(sx[2], sx[3])), fmaxf(fmaxf(sx[4], sx[5]), fmaxf(sx[6], sx[7])));
        mx = fmaxf(mx, __shfl_xor_sync(0xffffffffu, mx, 1)); mx = fmaxf(mx, __shfl_xor_sync(0xffffffffu, mx, 2));
        mx *= c1;
#pragma unroll
        for (int i = 0; i < 8; i++) sx[i] = ex2(fmaf(sx[i], c1, -mx));
        uint32_t p0 = pack_bf16(sx[0], sx[1]), p1 = pack_bf16(sx[2], sx[3]), p2 = pack_bf16(sx[4], sx[5]), p3 = pack_bf16(sx[6], sx[7]);
        float o[4], r[4];
        mma_z(o, p0, p2, p1, p3, v0.x, v0.y); mma_z(r, p0, p2, p1, p3, v0.z, v0.w); ya[0] = o[0] + r[2]; ya[1] = o[1] + r[3];
        mma_z(o, p0, p2, p1, p3, v1.x, v1.y); mma_z(r, p0, p2, p1, p3, v1.z, v1.w); ya[2] = o[0] + r[2]; ya[3] = o[1] + r[3];
        mma_z(o, p0, p2, p1, p3, v2.x, v2.y); mma_z(r, p0, p2, p1, p3, v2.z, v2.w); yb[0] = o[0] + r[2]; yb[1] = o[1] + r[3];
        mma_z(o, p0, p2, p1, p3, v3.x, v3.y); mma_z(r, p0, p2, p1, p3, v3.z, v3.w); yb[2] = o[0] + r[2]; yb[3] = o[1] + r[3];
        mma_z(z, p0, p2, p1, p3, one_n, one_n); z[0] += z[2];
      }
      asm volatile("" : "+f"(ya[0]), "+f"(ya[1]), "+f"(ya[2]), "+f"(ya[3]), "+f"(yb[0]), "+f"(yb[1]), "+f"(yb[2]), "+f"(yb[3]), "+f"(z[0]));
      STAMP(5);
      FENCE(9);
      BAR_SYNC(3, 256);
      uint32_t u[4];
      {
        const uint32_t ub = l16 + QOFF(uQ) + q * 512;
        uint4 u0 = lds128(ub), u1 = lds128(ub + QB), u2 = lds128(ub + 2 * QB), u3 = lds128(ub + 3 * QB);
        u[0] = hadd_bf2(hadd_bf2(u0.x, u1.x), hadd_bf2(u2.x, u3.x)); u[1] = hadd_bf2(hadd_bf2(u0.y, u1.y), hadd_bf2(u2.y, u3.y));
        u[2] = hadd_bf2(hadd_bf2(u0.z, u1.z), hadd_bf2(u2.z, u3.z)); u[3] = hadd_bf2(hadd_bf2(u0.w, u1.w), hadd_bf2(u2.w, u3.w));
      }
      const uint32_t zb = (uint32_t)(127 + se - nse) * 0x00800080u;
      const float c2 = c1 * inv;
      float off = -mx - (float)se;
      const float lim = 32.f - (float)se;
      STAMP(6);
      wait_bar1(bar_sm, s & 1);
      STAMP(7);
      {
        float4 t0 = lds128f(l16 + OFF(sm)), t1 = lds128f(l16 + OFF(sm) + 512);
        const float r0 = (t0.x + t0.z) + (t1.x + t1.z), r1 = (t0.y + t0.w) + (t1.y + t1.w);
        float a0 = fmaf(r0, c2, off), a1 = fmaf(r1, c2, off);
        uint32_t pm = pack_bf16(ex2v(a0), ex2v(a1));
        if (__any_sync(0xffffffffu, !(fmaxf(a0, a1) <= lim))) {
          float m = fmaxf(fmaxf(r0, r1) * c2, mx);
          m = fmaxf(m, __shfl_xor_sync(0xffffffffu, m, 1)); m = fmaxf(m, __shfl_xor_sync(0xffffffffu, m, 2));
          const float al = ex2(mx - m);
#pragma unroll
          for (int i = 0; i < 4; i++) { ya[i] *= al; yb[i] *= al; }
          z[0] *= al;
          off = -m - (float)se;
          pm = pack_bf16(ex2(fmaf(r0, c2, off)), ex2(fmaf(r1, c2, off)));
        }
        mma16816(z, pm, 0u, 0u, pm, zb, zb);
        mma16816(ya, pm, 0u, 0u, pm, u[0], u[1]); mma16816(yb, pm, 0u, 0u, pm, u[2], u[3]);
        float iz; asm("rcp.approx.ftz.f32 %0, %1;" : "=f"(iz) : "f"(z[0]));
        red_h8(redp, pack_f16(ya[0] * iz, ya[1] * iz), pack_f16(ya[2] * iz, ya[3] * iz), pack_f16(yb[0] * iz, yb[1] * iz), pack_f16(((q & 1) ? yb[3] : yb[2]) * iz, 1.f));
      }
      BAR_ARRIVE(4, 384);
      STAMP(8);
      if (q == 0) sts32(sb + OFF(sinv) + ((s + 1) & 1) * 4, (uint32_t)(127 - nse) << 23);
      redp += (s & 1) ? 32 : (1024 - 32);
      se = nse;
    }
  }
  asm volatile("barrier.cluster.arrive.release.aligned;\nbarrier.cluster.wait.acquire.aligned;" ::: "memory");
}

__global__ void n_xf(const bf16* x) {
  int i = blockIdx.x * blockDim.x + threadIdx.x;
  if (i >= NSEG * 4 * 14 * 32) return;
  int lane = i & 31, r = i >> 5, m = r & 1; r >>= 1; int f = r % 7; r /= 7; int j = r & 3, seg = r >> 2;
  int c0 = f == 6 ? 96 : (f & ~1) * 16 + (f & 1) * 8, c1 = f == 6 ? 104 : (f | 1) * 16 + (f & 1) * 8;
  const bf16* r0 = x + (seg * 32 + m * 16 + (lane >> 2)) * DM + j * 112 + (lane & 3) * 2;
  const bf16* r1 = r0 + 8 * DM;
  g_XF[i] = make_uint4(*(const uint32_t*)(r0 + c0), *(const uint32_t*)(r1 + c0), *(const uint32_t*)(r0 + c1), *(const uint32_t*)(r1 + c1));
}

__global__ void n_seed(const bf16* mem0) {
  __shared__ unsigned smx;
  if (threadIdx.x == 0) smx = 0;
  __syncthreads();
  float m = 0.f;
  for (int i = threadIdx.x; i < 8 * DM; i += 512) m = fmaxf(m, fabsf(b2f(mem0[i])));
  atomicMax(&smx, __float_as_uint(m));
  __syncthreads();
  int e = (int)(smx >> 23) - 127 + 1;
  int se = min(max(15 - e, -60), 60);
  float sc = __uint_as_float((uint32_t)(127 + se) << 23);
  if (threadIdx.x == 0) g_inv0 = __uint_as_float((uint32_t)(127 - se) << 23);
  int vec = threadIdx.x >> 5, lane = threadIdx.x & 31, j = vec >> 2, q = vec & 3;
  int nt0 = q < 2 ? q * 3 : 8 + (q - 2) * 3, nts = 6 + (q >> 1);
  const bf16* r = mem0 + (lane >> 2) * DM + j * 112 + (lane & 3) * 2;
  auto val = [&](int nt, int e2) { return b2f(r[nt * 8 + e2]) * sc; };
  *acc_ptr(0, vec, lane) = make_uint4(pack_f16(val(nt0, 0), val(nt0, 1)), pack_f16(val(nt0 + 1, 0), val(nt0 + 1, 1)), pack_f16(val(nt0 + 2, 0), val(nt0 + 2, 1)), pack_f16(val(nts, q & 1), 16.f));
}

__global__ void n_stats(const bf16* x) {
  if (blockIdx.x < 64) {
    float m = 0.f;
    for (int i = threadIdx.x; i < 32 * DM; i += 256) m = fmaxf(m, fabsf(b2f(x[blockIdx.x * 32 * DM + i])));
    atomicMax((unsigned*)&g_xmax[blockIdx.x], __float_as_uint(m));
  } else {
    int r = (blockIdx.x - 64) * 256 + threadIdx.x;
    if (r < NH * DM) { float a = 0.f; for (int k = 0; k < DM; k++) { float v = wf_elem(1, r / DM, r % DM, k); a += v * v; } atomicMax((unsigned*)&g_bmax, __float_as_uint(sqrtf(a))); }
  }
}

int g_poll_delay = POLL_DELAY;
extern "C" void kernel_launch(void* const* d_in, const int* in_sizes, int n_in, void* d_out, int out_size) {
  const bf16* x = (const bf16*)d_in[0];
  const bf16* wqkv = (const bf16*)d_in[1];
  const bf16* wphi = (const bf16*)d_in[2];
  const bf16* wo_a = (const bf16*)d_in[3];
  const bf16* mem0 = (const bf16*)d_in[5];
  const bf16* Wq = (const bf16*)d_in[6];
  const bf16* Wk = (const bf16*)d_in[7];
  const bf16* Wv = (const bf16*)d_in[8];
  const bf16* Wo = (const bf16*)d_in[9];
  const bf16* gate_w = (const bf16*)d_in[11];
  bf16* out = (bf16*)d_out;
  cudaFuncSetAttribute(r_kernel, cudaFuncAttributeMaxDynamicSharedMemorySize, (int)sizeof(RSmem));
  n_zero<<<(NSEG * 40 * 32 + 255) / 256, 256>>>();
  n_prep<<<(2 * NH * 28 * 28 * 32 + 255) / 256, 256>>>(Wq, Wk, Wv, Wo);
  n_stats<<<64 + 28, 256>>>(x);
  n_seed<<<1, 512>>>(mem0);
  n_xf<<<NSEG * 4 * 14 * 32 / 256, 256>>>(x);
  n_xgemm<<<2 * NH * 28 * NSEG * 32 / 256, 256>>>(x);
  r_kernel<<<64, 384, sizeof(RSmem)>>>(mem0, g_poll_delay);
  n_qkv<<<(S_LEN * 1344 + 255) / 256, 256>>>(x, wqkv);
  n_phi<<<(S_LEN * 2 * NH + 255) / 256, 256>>>(wphi);
  n_kv<<<(32 * NH * 56 * 29 + 255) / 256, 256>>>();
  n_oa<<<(S_LEN * DM + 255) / 256, 256>>>();
  n_x3<<<NSEG, 512>>>(x, wo_a, gate_w, out);
}
```

```cpp
#include <cuda_runtime.h>
#include <cuda_bf16.h>
#include <stdint.h>
#include <stddef.h>

typedef __nv_bfloat16 bf16;
#define S_LEN 2048
#define DM 448
#define NH 16
#define NSEG 64
#define SPIN_LIMIT (1 << 22)

__device__ uint4 g_WF[2 * NH * 28 * 28 * 32];
__device__ uint4 g_KF[NSEG * NH * 4 * 4 * 4 * 32];
__device__ uint4 g_VF[NSEG * NH * 56 * 32];
__device__ float4 g_SXM[NSEG * NH * 4 * 2 * 32];
__device__ uint4 g_XF[NSEG * 4 * 14 * 32];
__device__ uint32_t g_UF[NSEG * NH * 56 * 32];
__device__ uint4 g_ACC16[(NSEG + 2) * 16 * 32];
__device__ float g_xmax[NSEG];
__device__ float g_bmax;
__device__ float g_inv0;
__device__ float g_qkv[S_LEN * 1344];
__device__ float g_phiq[S_LEN * NH * 56];
__device__ float g_phik[S_LEN * NH * 56];
__device__ float g_kv[NH * 56 * 29];
__device__ float g_oa[S_LEN * DM];
__device__ int g_err;
__device__ unsigned g_ts[64 * 64 * 64];

__device__ __forceinline__ uint32_t pack_bf16(float lo, float hi) {
  uint32_t r; asm("cvt.rn.bf16x2.f32 %0, %1, %2;" : "=r"(r) : "f"(hi), "f"(lo)); return r;
}
__device__ __forceinline__ float bf_lo(uint32_t v) { return __uint_as_float(v << 16); }
__device__ __forceinline__ float bf_hi(uint32_t v) { return __uint_as_float(v & 0xffff0000u); }
__device__ __forceinline__ float b2f(bf16 v) { return __bfloat162float(v); }

__global__ void n_prep(const bf16* Wq, const bf16* Wk, const bf16* Wv, const bf16* Wo) {
  int idx = blockIdx.x * blockDim.x + threadIdx.x;
  if (idx >= 2 * NH * 28 * 28 * 32) return;
  int lane = idx & 31, r = idx >> 5;
  int ks = r % 28; r /= 28; int tile = r % 28; r /= 28; int h = r % NH; int mat = r / NH;
  int g = lane >> 2, tq = lane & 3;
  float v[8];
  for (int i = 0; i < 8; i++) {
    int row = tile * 16 + g + ((i >> 1) & 1) * 8;
    int col = ks * 16 + tq * 2 + (i & 1) + (i >> 2) * 8;
    float acc = 0.f;
    if (mat == 0) { for (int e = 0; e < 256; e++) acc += b2f(Wq[(row * NH + h) * 256 + e]) * b2f(Wk[(col * NH + h) * 256 + e]); acc *= 0.0625f; }
    else { for (int e = 0; e < 256; e++) acc += b2f(Wo[(h * 256 + e) * DM + row]) * b2f(Wv[(col * NH + h) * 256 + e]); }
    v[i] = acc;
  }
  g_WF[idx] = make_uint4(pack_bf16(v[0], v[1]), pack_bf16(v[2], v[3]), pack_bf16(v[4], v[5]), pack_bf16(v[6], v[7]));
}
__device__ __forceinline__ float wf_elem(int mat, int h, int row, int col) {
  int tile = row >> 4, ks = col >> 4, rr = row & 15, cc = col & 15;
  int lane = (rr & 7) * 4 + ((cc & 7) >> 1);
  int reg = (rr >> 3) + (cc >> 3) * 2;
  uint32_t w = ((const uint32_t*)g_WF)[((((mat * NH + h) * 28 + tile) * 28 + ks) * 32 + lane) * 4 + reg];
  return (cc & 1) ? bf_hi(w) : bf_lo(w);
}
__device__ __forceinline__ void mma16816(float* d, uint32_t a0, uint32_t a1, uint32_t a2, uint32_t a3, uint32_t b0, uint32_t b1) {
  asm volatile("mma.sync.aligned.m16n8k16.row.col.f32.bf16.bf16.f32 {%0,%1,%2,%3}, {%4,%5,%6,%7}, {%8,%9}, {%0,%1,%2,%3};"
    : "+f"(d[0]), "+f"(d[1]), "+f"(d[2]), "+f"(d[3]) : "r"(a0), "r"(a1), "r"(a2), "r"(a3), "r"(b0), "r"(b1));
}
__device__ __forceinline__ void mma1688(float* d, uint32_t a0, uint32_t a1, uint32_t b0) {
  asm volatile("mma.sync.aligned.m16n8k8.row.col.f32.bf16.bf16.f32 {%0,%1,%2,%3}, {%4,%5}, {%6}, {%0,%1,%2,%3};"
    : "+f"(d[0]), "+f"(d[1]), "+f"(d[2]), "+f"(d[3]) : "r"(a0), "r"(a1), "r"(b0));
}
__device__ __forceinline__ uint32_t movm(uint32_t a) { uint32_t d; asm volatile("movmatrix.sync.aligned.m8n8.trans.b16 %0, %1;" : "=r"(d) : "r"(a)); return d; }

__global__ void n_xgemm(const bf16* x) {
  int wid = (blockIdx.x * blockDim.x + threadIdx.x) >> 5, lane = threadIdx.x & 31;
  int seg = wid % NSEG; int r = wid / NSEG;
  int tile = r % 28; r /= 28; int h = r % NH; int mat = r / NH;
  if (mat >= 2) return;
  int g = lane >> 2, tq = lane & 3;
  float d[4][4] = {};
  const uint4* wf = g_WF + (((mat * NH + h) * 28 + tile) * 28) * 32 + lane;
  for (int ks = 0; ks < 28; ks++) {
    uint4 a = wf[ks * 32];
    for (int kg = 0; kg < 4; kg++) {
      const uint32_t* xr = (const uint32_t*)(x + (seg * 32 + kg * 8 + g) * DM + ks * 16 + tq * 2);
      mma16816(d[kg], a.x, a.y, a.z, a.w, xr[0], xr[4]);
    }
  }
  if (mat == 0) {
    for (int kg = 0; kg < 4; kg++) {
      uint32_t b0 = movm(pack_bf16(d[kg][0], d[kg][1])), b1 = movm(pack_bf16(d[kg][2], d[kg][3]));
      int jj = tile / 7, i = tile % 7;
      uint32_t* dst = (uint32_t*)&g_KF[((((seg * NH + h) * 4 + kg) * 4 + jj) * 4 + (i >> 1)) * 32 + lane];
      if (i == 6) { dst[0] = b0; dst[1] = b1; } else { dst[i & 1] = b0; dst[2 + (i & 1)] = b1; }
    }
  } else {
    g_VF[((seg * NH + h) * 56 + tile * 2) * 32 + lane] = make_uint4(pack_bf16(d[0][0], d[0][1]), pack_bf16(d[1][0], d[1][1]), pack_bf16(d[2][0], d[2][1]), pack_bf16(d[3][0], d[3][1]));
    g_VF[((seg * NH + h) * 56 + tile * 2 + 1) * 32 + lane] = make_uint4(pack_bf16(d[0][2], d[0][3]), pack_bf16(d[1][2], d[1][3]), pack_bf16(d[2][2], d[2][3]), pack_bf16(d[3][2], d[3][3]));
  }
}
__global__ void n_zero() {
  int i = blockIdx.x * blockDim.x + threadIdx.x;
  if (i < (NSEG + 2) * 16 * 32) g_ACC16[i] = make_uint4(0, 0, 0, 0);
  if (i < NSEG) g_xmax[i] = 0.f;
  if (i == 0) g_bmax = 0.f;
  if (i < NH * 56 * 29) g_kv[i] = 0.f;
}
__global__ void n_qkv(const bf16* x, const bf16* w) {
  int i = blockIdx.x * blockDim.x + threadIdx.x;
  if (i >= S_LEN * 1344) return;
  int n = i % 1344, t = i / 1344;
  float acc = 0.f;
  for (int k = 0; k < DM; k++) acc += b2f(x[t * DM + k]) * b2f(w[k * 1344 + n]);
  g_qkv[i] = acc;
}
__global__ void n_phi(const bf16* wphi) {
  int i = blockIdx.x * blockDim.x + threadIdx.x;
  if (i >= S_LEN * 2 * NH) return;
  int h = i % NH, which = (i / NH) % 2, t = i / (2 * NH);
  float p[28]; float mx = -1e30f, mn = 1e30f;
  for (int f = 0; f < 28; f++) {
    float acc = 0.f;
    for (int d = 0; d < 28; d++) acc += g_qkv[t * 1344 + which * 448 + h * 28 + d] * b2f(wphi[(h * 28 + d) * 28 + f]);
    p[f] = acc; mx = fmaxf(mx, acc); mn = fminf(mn, acc);
  }
  float s1 = 0.f, s2 = 0.f;
  for (int f = 0; f < 28; f++) { s1 += __expf(p[f] - mx); s2 += __expf(mn - p[f]); }
  float* o = (which ? g_phik : g_phiq) + (t * NH + h) * 56;
  for (int f = 0; f < 28; f++) { o[f] = __expf(p[f] - mx) / s1; o[28 + f] = __expf(mn - p[f]) / s2; }
}
__global__ void n_kv() {
  int i = blockIdx.x * blockDim.x + threadIdx.x;
  if (i >= 32 * NH * 56 * 29) return;
  int d = i % 29, f = (i / 29) % 56, h = (i / (29 * 56)) % NH, ch = i / (29 * 56 * NH);
  float acc = 0.f;
  for (int t = ch * 64; t < ch * 64 + 64; t++) acc += g_phik[(t * NH + h) * 56 + f] * (d < 28 ? g_qkv[t * 1344 + 896 + h * 28 + d] : 1.f);
  atomicAdd(&g_kv[(h * 56 + f) * 29 + d], acc);
}
__global__ void n_oa() {
  int i = blockIdx.x * blockDim.x + threadIdx.x;
  if (i >= S_LEN * DM) return;
  int c = i % DM, t = i / DM, h = c / 28, d = c % 28;
  float num = 0.f, den = 0.f;
  for (int f = 0; f < 56; f++) { float p = g_phiq[(t * NH + h) * 56 + f]; num += p * g_kv[(h * 56 + f) * 29 + d]; den += p * g_kv[(h * 56 + f) * 29 + 28]; }
  g_oa[i] = num / (den + 1e-6f);
}

__global__ void __launch_bounds__(512) n_x3(const bf16* x, const bf16* wo, const bf16* gate_w, bf16* out) {
  __shared__ uint32_t sP[NH][2][32][10];
  __shared__ float sG[32];
  int seg = blockIdx.x, w = threadIdx.x >> 5, lane = threadIdx.x & 31, g = lane >> 2, tq = lane & 3;
  for (int r = w; r < 32; r += 16) {
    float acc = 0.f;
    for (int k = lane; k < DM; k += 32) acc += b2f(x[(seg * 32 + r) * DM + k]) * b2f(gate_w[k]);
    for (int o = 16; o; o >>= 1) acc += __shfl_xor_sync(0xffffffffu, acc, o);
    if (lane == 0) sG[r] = 1.f / (1.f + __expf(-acc));
  }
  {
    int h = w;
    float s[2][5][4] = {};
    for (int ct = 0; ct < 28; ct++) {
      uint32_t a[2][4];
      for (int m = 0; m < 2; m++) {
        const uint32_t* r0 = (const uint32_t*)(x + (seg * 32 + m * 16 + g) * DM + ct * 16 + tq * 2);
        const uint32_t* r1 = (const uint32_t*)(x + (seg * 32 + m * 16 + g + 8) * DM + ct * 16 + tq * 2);
        a[m][0] = r0[0]; a[m][1] = r1[0]; a[m][2] = r0[4]; a[m][3] = r1[4];
      }
      int j = ct / 7, i = ct % 7;
      for (int kg = 0; kg < 4; kg++) {
        const uint32_t* src = (const uint32_t*)&g_KF[((((seg * NH + h) * 4 + kg) * 4 + j) * 4 + (i >> 1)) * 32 + lane];
        uint2 b = i == 6 ? make_uint2(src[0], src[1]) : make_uint2(src[i & 1], src[2 + (i & 1)]);
        for (int m = 0; m < 2; m++) mma16816(s[m][1 + kg], a[m][0], a[m][1], a[m][2], a[m][3], b.x, b.y);
      }
    }
    for (int m = 0; m < 2; m++) for (int j = 0; j < 4; j++) {
      float4 t = g_SXM[(((seg * NH + h) * 4 + j) * 2 + m) * 32 + lane];
      s[m][0][0] += t.x; s[m][0][1] += t.y; s[m][0][2] += t.z; s[m][0][3] += t.w;
    }
    for (int m = 0; m < 2; m++) for (int hf = 0; hf < 2; hf++) {
      int t = m * 16 + hf * 8 + g;
      float v[10]; float mx = -1e30f;
      for (int n = 0; n < 5; n++) for (int e = 0; e < 2; e++) {
        float val = s[m][n][hf * 2 + e];
        if (n > 0 && (n - 1) * 8 + tq * 2 + e > t) val = -1e30f;
        v[n * 2 + e] = val; mx = fmaxf(mx, val);
      }
      mx = fmaxf(mx, __shfl_xor_sync(0xffffffffu, mx, 1)); mx = fmaxf(mx, __shfl_xor_sync(0xffffffffu, mx, 2));
      float z = 0.f;
      for (int i = 0; i < 10; i++) { v[i] = __expf(v[i] - mx); z += v[i]; }
      z += __shfl_xor_sync(0xffffffffu, z, 1); z += __shfl_xor_sync(0xffffffffu, z, 2);
      float iz = 1.f / z;
      sP[h][m][lane][hf] = pack_bf16(v[0] * iz, v[1] * iz);
      sP[h][m][lane][2 + hf] = pack_bf16(v[2] * iz, v[3] * iz);
      sP[h][m][lane][4 + hf] = pack_bf16(v[4] * iz, v[5] * iz);
      sP[h][m][lane][6 + hf] = pack_bf16(v[6] * iz, v[7] * iz);
      sP[h][m][lane][8 + hf] = pack_bf16(v[8] * iz, v[9] * iz);
    }
  }
  __syncthreads();
  if (w < 14) {
    float o[2][4][4] = {};
    for (int h = 0; h < NH; h++) {
      for (int n = 0; n < 4; n++) {
        int nt = w * 4 + n;
        uint4 v = g_VF[((seg * NH + h) * 56 + nt) * 32 + lane];
        uint32_t u = g_UF[((seg * NH + h) * 56 + nt) * 32 + lane];
        for (int m = 0; m < 2; m++) {
          const uint32_t* p = sP[h][m][lane];
          mma1688(o[m][n], p[0], p[1], u);
          mma16816(o[m][n], p[2], p[3], p[4], p[5], v.x, v.y);
          mma16816(o[m][n], p[6], p[7], p[8], p[9], v.z, v.w);
        }
      }
    }
    for (int m = 0; m < 2; m++) for (int n = 0; n < 4; n++) for (int i = 0; i < 4; i++) {
      int r = m * 16 + (i >> 1) * 8 + g, c = (w * 4 + n) * 8 + tq * 2 + (i & 1);
      int t = seg * 32 + r;
      float a = 0.f;
      for (int k = 0; k < DM; k++) a += g_oa[t * DM + k] * b2f(wo[k * DM + c]);
      float gt = sG[r];
      out[t * DM + c] = __float2bfloat16(gt * a + (1.f - gt) * o[m][n][i]);
    }
  }
}

__device__ __forceinline__ uint32_t smem_u32(const void* p) { return (uint32_t)__cvta_generic_to_shared(p); }
__device__ __forceinline__ uint32_t mapa(uint32_t a, uint32_t r) { uint32_t o; asm volatile("mapa.shared::cluster.u32 %0, %1, %2;" : "=r"(o) : "r"(a), "r"(r)); return o; }
__device__ __forceinline__ bool try_wait(uint32_t bar, uint32_t parity) {
  uint32_t ok; asm volatile("{\n.reg .pred p;\nmbarrier.try_wait.parity.shared::cta.b64 p, [%1], %2;\nselp.u32 %0, 1, 0, p;\n}" : "=r"(ok) : "r"(bar), "r"(parity) : "memory"); return ok; }
__device__ __forceinline__ void wait_bar(uint32_t bar, uint32_t parity) {
  int n = 0; while (!try_wait(bar, parity)) { if (++n > SPIN_LIMIT) { g_err = 1; break; } } }
__device__ __forceinline__ void arm_bar(uint32_t bar, uint32_t bytes) { asm volatile("mbarrier.arrive.expect_tx.shared::cta.b64 _, [%0], %1;" :: "r"(bar), "r"(bytes) : "memory"); }
__device__ __forceinline__ float4 ld_relaxed4(const void* p) { float4 v; asm volatile("ld.relaxed.gpu.global.v4.f32 {%0,%1,%2,%3}, [%4];" : "=f"(v.x), "=f"(v.y), "=f"(v.z), "=f"(v.w) : "l"(p) : "memory"); return v; }
__device__ __forceinline__ void red4(void* p, float a, float b, float c, float d) { asm volatile("red.relaxed.gpu.global.add.v4.f32 [%0], {%1,%2,%3,%4};" :: "l"(p), "f"(a), "f"(b), "f"(c), "f"(d) : "memory"); }
__device__ __forceinline__ void st_async2(uint32_t dst, float a, float b, uint32_t bar) { asm volatile("st.async.shared::cluster.mbarrier::complete_tx::bytes.v2.f32 [%0], {%1,%2}, [%3];" :: "r"(dst), "f"(a), "f"(b), "r"(bar) : "memory"); }
__device__ __forceinline__ void bulk_g2s(uint32_t dst, const void* src, uint32_t bytes, uint32_t bar) {
  asm volatile("cp.async.bulk.shared::cluster.global.mbarrier::complete_tx::bytes [%0], [%1], %2, [%3];" :: "r"(dst), "l"(src), "r"(bytes), "r"(bar) : "memory"); }
__device__ __forceinline__ unsigned clk() { unsigned c; asm volatile("mov.u32 %0, %%clock;" : "=r"(c) :: "memory"); return c; }
__device__ __forceinline__ float ex2(float x) { float y; asm("ex2.approx.ftz.f32 %0, %1;" : "=f"(y) : "f"(x)); return y; }

#define NST 4
struct QBlk {
  uint4 memF[4][32];
  uint4 wA[7][32], wB[7][32];
  uint4 kf[NST][4][32];
  float4 xred[2][32];
  float4 red[32];
  uint4 uQ[4][32];
  uint4 kq[2][4][32];
};
#define QB ((uint32_t)sizeof(QBlk))
#define QOFF(f) ((uint32_t)offsetof(QBlk, f))
struct RSmem {
  QBlk qb[4];
  uint4 vf[NST][14][32];
  uint4 xf[NST][14][32];
  float4 sx[2][32];
  float4 sm[2][32];
  uint32_t smax[4];
  float xmax[NSEG];
  float sinv[4];
  unsigned long long bar_ld[NST], bar_sx, bar_sm;
  unsigned ts[64 * 64];
};
#define LD_BYTES (8192 + 7168 + 7168)
#define POLL_DELAY 300
#define STAMP(i)
__device__ __forceinline__ void wait_slow(uint32_t bar, uint32_t parity) {
#pragma unroll 1
  for (int n = 0; n < SPIN_LIMIT; n++) if (try_wait(bar, parity)) return;
  g_err = 1;
}
__device__ __forceinline__ void wait_bar1(uint32_t bar, uint32_t parity) { if (!try_wait(bar, parity)) wait_slow(bar, parity); }
__device__ __forceinline__ uint4 ld_relaxed_u4(const void* p) { uint4 v; asm volatile("ld.relaxed.gpu.global.v4.u32 {%0,%1,%2,%3}, [%4];" : "=r"(v.x), "=r"(v.y), "=r"(v.z), "=r"(v.w) : "l"(p) : "memory"); return v; }
__device__ __forceinline__ void red_h8(void* p, uint32_t a, uint32_t b, uint32_t c, uint32_t d) { asm volatile("red.relaxed.gpu.global.add.noftz.v4.f16x2 [%0], {%1,%2,%3,%4};" :: "l"(p), "r"(a), "r"(b), "r"(c), "r"(d) : "memory"); }
__device__ __forceinline__ uint32_t pack_f16(float lo, float hi) { uint32_t r; asm("cvt.rn.f16x2.f32 %0, %1, %2;" : "=r"(r) : "f"(hi), "f"(lo)); return r; }
__device__ __forceinline__ uint32_t h2_to_bf2(uint32_t v) {
  float lo, hi; asm("{.reg .f16 l, h; mov.b32 {l, h}, %2; cvt.f32.f16 %0, l; cvt.f32.f16 %1, h;}" : "=f"(lo), "=f"(hi) : "r"(v)); return pack_bf16(lo, hi); }
__device__ __forceinline__ uint2 lds64(uint32_t a) { uint2 v; asm volatile("ld.shared.v2.u32 {%0,%1}, [%2];" : "=r"(v.x), "=r"(v.y) : "r"(a) : "memory"); return v; }
__device__ __forceinline__ float2 lds64f(uint32_t a) { float2 v; asm volatile("ld.shared.v2.f32 {%0,%1}, [%2];" : "=f"(v.x), "=f"(v.y) : "r"(a) : "memory"); return v; }
__device__ __forceinline__ uint4 lds128(uint32_t a) { uint4 v; asm volatile("ld.shared.v4.u32 {%0,%1,%2,%3}, [%4];" : "=r"(v.x), "=r"(v.y), "=r"(v.z), "=r"(v.w) : "r"(a) : "memory"); return v; }
__device__ __forceinline__ uint4 lds128v(uint32_t a) { uint4 v; asm volatile("ld.volatile.shared.v4.u32 {%0,%1,%2,%3}, [%4];" : "=r"(v.x), "=r"(v.y), "=r"(v.z), "=r"(v.w) : "r"(a) : "memory"); return v; }
__device__ __forceinline__ uint32_t lds32(uint32_t a) { uint32_t v; asm volatile("ld.shared.u32 %0, [%1];" : "=r"(v) : "r"(a) : "memory"); return v; }
__device__ __forceinline__ void sts64(uint32_t a, uint32_t x, uint32_t y) { asm volatile("st.shared.v2.u32 [%0], {%1,%2};" :: "r"(a), "r"(x), "r"(y) : "memory"); }
__device__ __forceinline__ void sts64f(uint32_t a, float x, float y) { asm volatile("st.shared.v2.f32 [%0], {%1,%2};" :: "r"(a), "f"(x), "f"(y) : "memory"); }
__device__ __forceinline__ void sts32(uint32_t a, uint32_t x) { asm volatile("st.shared.u32 [%0], %1;" :: "r"(a), "r"(x) : "memory"); }
__device__ __forceinline__ void mma_z(float* d, uint32_t a0, uint32_t a1, uint32_t a2, uint32_t a3, uint32_t b0, uint32_t b1) {
  asm volatile("mma.sync.aligned.m16n8k16.row.col.f32.bf16.bf16.f32 {%0,%1,%2,%3}, {%4,%5,%6,%7}, {%8,%9}, {%10,%10,%10,%10};"
    : "=f"(d[0]), "=f"(d[1]), "=f"(d[2]), "=f"(d[3]) : "r"(a0), "r"(a1), "r"(a2), "r"(a3), "r"(b0), "r"(b1), "f"(0.f));
}
__device__ __forceinline__ void mma8_z(float* d, uint32_t a0, uint32_t a1, uint32_t b0) {
  asm volatile("mma.sync.aligned.m16n8k8.row.col.f32.bf16.bf16.f32 {%0,%1,%2,%3}, {%4,%5}, {%6}, {%7,%7,%7,%7};"
    : "=f"(d[0]), "=f"(d[1]), "=f"(d[2]), "=f"(d[3]) : "r"(a0), "r"(a1), "r"(b0), "f"(0.f));
}
#define OFF(f) ((uint32_t)offsetof(RSmem, f))
#define BAR_SYNC(id, n) asm volatile("bar.sync %0, %1;" :: "n"(id), "n"(n) : "memory")
#define BAR_ARRIVE(id, n) asm volatile("bar.arrive %0, %1;" :: "n"(id), "n"(n) : "memory")

__device__ __forceinline__ void sts128(uint32_t a, uint32_t x, uint32_t y, uint32_t z, uint32_t w) { asm volatile("st.shared.v4.u32 [%0], {%1,%2,%3,%4};" :: "r"(a), "r"(x), "r"(y), "r"(z), "r"(w) : "memory"); }
template <int K>
__device__ __forceinline__ void kstep(const uint4 (&W)[42], float (&acc)[7][4], uint32_t b0, uint32_t b1, uint4& w6, uint32_t ws) {
#pragma unroll
  for (int t = 0; t < 6; t++) {
    const uint4& w = W[K * 6 + t];
    if (K == 0) mma_z(acc[t], w.x, w.y, w.z, w.w, b0, b1); else mma16816(acc[t], w.x, w.y, w.z, w.w, b0, b1);
  }
  if (K == 0) mma_z(acc[6], w6.x, w6.y, w6.z, w6.w, b0, b1); else mma16816(acc[6], w6.x, w6.y, w6.z, w6.w, b0, b1);
  if (K < 6) w6 = lds128(ws + (K + 1) * 512);
}
__device__ __forceinline__ uint4* acc_ptr(int step, int vec, int lane) { return g_ACC16 + (((step >> 1) * 16 + vec) * 2 + (step & 1)) * 32 + lane; }

__device__ __forceinline__ bool elect1() { uint32_t p; asm volatile("{.reg .pred p; elect.sync _|p, 0xffffffff; selp.u32 %0, 1, 0, p;}" : "=r"(p)); return p; }
__device__ __forceinline__ float4 lds128f(uint32_t a) { float4 v; asm volatile("ld.shared.v4.f32 {%0,%1,%2,%3}, [%4];" : "=f"(v.x), "=f"(v.y), "=f"(v.z), "=f"(v.w) : "r"(a) : "memory"); return v; }
__device__ __forceinline__ float ex2v(float x) { float y; asm volatile("ex2.approx.ftz.f32 %0, %1;" : "=f"(y) : "f"(x)); return y; }
__device__ __forceinline__ uint32_t hadd_bf2(uint32_t a, uint32_t b) { uint32_t d; asm("add.rn.bf16x2 %0, %1, %2;" : "=r"(d) : "r"(a), "r"(b)); return d; }
__device__ __forceinline__ uint32_t amax2(uint32_t m, uint32_t x, uint32_t y) { return __vmaxu2(m, __vmaxu2(x & 0x7fff7fffu, y & 0x7fff7fffu)); }

#define FENCE(n) do { if (__builtin_expect((poll_delay >> (16 + (n))) & 1, 0)) { _Pragma("unroll 1") for (int i_ = poll_delay & 7; i_ > 0; i_--) asm volatile("nanosleep.u32 %0;" :: "n"(n) : "memory"); } } while (0)
#define BAR_SYNC_R(id, n) asm volatile("bar.sync %0, %1;" :: "r"(id), "n"(n) : "memory")
#define BAR_ARRIVE_R(id, n) asm volatile("bar.arrive %0, %1;" :: "r"(id), "n"(n) : "memory")
#define MMW(A, WW, B0, B1, first) do { if (first) mma_z(A, WW.x, WW.y, WW.z, WW.w, B0, B1); else mma16816(A, WW.x, WW.y, WW.z, WW.w, B0, B1); } while (0)
__device__ __forceinline__ void issue_loads(uint32_t sb, int s, int h, int j) {
  const int st = s & (NST - 1), s0 = s;
  const uint32_t bar = sb + OFF(bar_ld) + 8 * st;
  arm_bar(bar, LD_BYTES);
#pragma unroll
  for (int qq = 0; qq < 4; qq++) bulk_g2s(sb + qq * QB + QOFF(kf) + st * 2048, g_KF + ((s * NH + h) * 4 + j) * 512 + qq * 128, 2048, bar);
  bulk_g2s(sb + OFF(vf) + st * 7168, g_VF + ((s * NH + h) * 56 + 14 * j) * 32, 7168, bar);
  bulk_g2s(sb + OFF(xf) + st * 7168, g_XF + (s * 4 + j) * 448, 7168, bar);
  asm volatile("prefetch.global.L2 [%0];" :: "l"(acc_ptr(s0, h, j * 8)));
}
__device__ __forceinline__ int opaque_lane() { return __shfl_sync(0xffffffffu, threadIdx.x & 31, threadIdx.x & 31); }

__global__ void __cluster_dims__(4, 1, 1) __launch_bounds__(384, 1) r_kernel(const bf16* mem0, int poll_delay) {
  extern __shared__ __align__(128) unsigned char smem_raw[];
  RSmem& sm = *reinterpret_cast<RSmem*>(smem_raw);
  const int h = blockIdx.x >> 2, j = blockIdx.x & 3;
  const int w = __shfl_sync(0xffffffffu, threadIdx.x >> 5, 0), q = w & 3, role = w >> 2;
  const uint32_t sb = smem_u32(smem_raw);
  const uint32_t bar_ld = sb + OFF(bar_ld), bar_sx = sb + OFF(bar_sx), bar_sm = sb + OFF(bar_sm);
  if (threadIdx.x == 0) {
    for (int i = 0; i < NST; i++) asm volatile("mbarrier.init.shared::cta.b64 [%0], 1;" :: "r"(bar_ld + 8 * i));
    asm volatile("mbarrier.init.shared::cta.b64 [%0], 1;" :: "r"(bar_sx));
    asm volatile("mbarrier.init.shared::cta.b64 [%0], 1;" :: "r"(bar_sm));
    asm volatile("fence.mbarrier_init.release.cluster;" ::: "memory");
    arm_bar(bar_sx, 1024); arm_bar(bar_sm, 1024);
    for (int s = 0; s < NST; s++) issue_loads(sb, s, h, j);
    sm.sinv[0] = g_inv0; sm.sinv[2] = g_bmax;
  }
  if (threadIdx.x < NSEG) sm.xmax[threadIdx.x] = g_xmax[threadIdx.x];
  if (role < 2) {
    const int lane = threadIdx.x & 31;
    const uint4* wf = g_WF + (((role * NH + h) * 28 + 7 * j) * 28 + 7 * q) * 32 + lane;
#pragma unroll
    for (int e = 0; e < 7; e++) (role ? sm.qb[q].wB : sm.qb[q].wA)[e][lane] = wf[e * 28 * 32];
  }
  asm volatile("barrier.cluster.arrive.release.aligned;\nbarrier.cluster.wait.acquire.aligned;" ::: "memory");
  const float LOG2E = 1.4426950408889634f;

  if (role == 0) {
    asm volatile("setmaxnreg.inc.sync.aligned.u32 224;");
    const int lane = opaque_lane();
    const uint32_t l16 = sb + lane * 16;
    uint4 W[42];
    {
      const uint4* wf = g_WF + ((h * 28 + 7 * j) * 28 + 7 * q) * 32 + lane;
#pragma unroll
      for (int k = 1; k < 7; k++)
#pragma unroll
        for (int t = 0; t < 7; t++) W[(k - 1) * 7 + t] = wf[(t * 28 + k) * 32];
    }
    const uint32_t lq = l16 + q * QB, mj = l16 + j * QB;
#define ws (lq + QOFF(wA))
#define mq lq
    const uint32_t dst_sm = mapa(l16 + OFF(sm) + (j >> 1) * 512 + (j & 1) * 8, q), dst_bar = mapa(bar_sm, q);
    const uint4* p = acc_ptr(0, q * 4, lane);
#define TM(t, k) do { if ((k) == 0) mma_z(acc[t], f[t].x, f[t].y, f[t].z, f[t].w, b[0], b[1]); else { const uint4& w_ = W[((k) - 1) * 7 + (t)]; mma16816(acc[t], w_.x, w_.y, w_.z, w_.w, b[2 * (k)], b[2 * (k) + 1]); } } while (0)
#define T3(k) do { TM(0, k); TM(1, k); TM(2, k); } while (0)
#define T4(k) do { TM(3, k); TM(4, k); TM(5, k); TM(6, k); } while (0)
#define TR(t) do { kl[t] = movm(pack_bf16(acc[t][0], acc[t][1])); kh[t] = movm(pack_bf16(acc[t][2], acc[t][3])); } while (0)
    wait_bar1(bar_ld, 0);
#pragma unroll 1
    for (int s = 0; s < NSEG; s++) {
      STAMP(0);
      uint4 v0 = ld_relaxed_u4(p), v1 = ld_relaxed_u4(p + 64), v2 = ld_relaxed_u4(p + 128), v3 = ld_relaxed_u4(p + 192);
      const uint32_t kb = lq + QOFF(kf) + (s & (NST - 1)) * 2048;
      uint4 k0 = lds128(kb), k1 = lds128(kb + 512), k2 = lds128(kb + 1024); uint2 k3 = lds64(kb + 1536);
      uint4 f[7];
      f[0] = lds128v(ws); f[1] = lds128v(ws + 512); f[2] = lds128v(ws + 1024);
      if (!__all_sync(0xffffffffu, __byte_perm(v0.w, v1.w, 0x7632) == 0x4C004C00u && __byte_perm(v2.w, v3.w, 0x7632) == 0x4C004C00u)) {
#pragma unroll 1
        for (int n = 0; n < SPIN_LIMIT; n++) {
          v0 = ld_relaxed_u4(p); v1 = ld_relaxed_u4(p + 64); v2 = ld_relaxed_u4(p + 128); v3 = ld_relaxed_u4(p + 192);
          if (__all_sync(0xffffffffu, __byte_perm(v0.w, v1.w, 0x7632) == 0x4C004C00u && __byte_perm(v2.w, v3.w, 0x7632) == 0x4C004C00u)) break;
        }
      }
      STAMP(1);
      uint32_t b[14];
      float dl[4], dh[4], el[4], eh[4];
      b[0] = h2_to_bf2(v0.x); b[1] = h2_to_bf2(v0.y); b[2] = h2_to_bf2(v0.z); b[3] = h2_to_bf2(v1.x);
      mma_z(dl, b[0], b[1], b[2], b[3], k0.x, k0.y); mma_z(dh, b[0], b[1], b[2], b[3], k0.z, k0.w);
      b[4] = h2_to_bf2(v1.y); b[5] = h2_to_bf2(v1.z);
      b[6] = h2_to_bf2(__byte_perm(v0.w, v1.w, 0x5410)); b[7] = h2_to_bf2(__byte_perm(v2.w, v3.w, 0x5410));
      mma_z(el, b[4], b[5], b[6], b[7], k1.x, k1.y); mma_z(eh, b[4], b[5], b[6], b[7], k1.z, k1.w);
      b[8] = h2_to_bf2(v2.x); b[9] = h2_to_bf2(v2.y); b[10] = h2_to_bf2(v2.z); b[11] = h2_to_bf2(v3.x);
      mma16816(dl, b[8], b[9], b[10], b[11], k2.x, k2.y); mma16816(dh, b[8], b[9], b[10], b[11], k2.z, k2.w);
      b[12] = h2_to_bf2(v3.y); b[13] = h2_to_bf2(v3.z);
      mma1688(el, b[12], b[13], k3.x); mma1688(eh, b[12], b[13], k3.y);
      float acc[7][4];
      T3(0); T3(1);
      sts64f(lq + QOFF(red) + 8, (dl[0] + dh[2]) + (el[0] + eh[2]), (dl[1] + dh[3]) + (el[1] + eh[3]));
      BAR_ARRIVE(14, 256);
      f[3] = lds128(ws + 1536); f[4] = lds128(ws + 2048); f[5] = lds128(ws + 2560); f[6] = lds128(ws + 3072);
      sts128(mq, b[0], b[1], b[2], b[3]); sts128(mq + 512, b[4], b[5], b[6], b[7]); sts128(mq + 1024, b[8], b[9], b[10], b[11]); sts64(mq + 1536, b[12], b[13]);
      BAR_ARRIVE_R(5 + q, 64);
      T3(2);
      FENCE(2);
      T3(3); T4(0); T3(4); T4(1); T3(5); T4(2); T3(6); T4(3);
      FENCE(4);
      BAR_SYNC(1, 128);
      uint4 a0 = lds128(mj), a1 = lds128(mj + 512), a2 = lds128(mj + 1024); uint2 a3 = lds64(mj + 1536);
      uint32_t kl[7], kh[7];
      T4(4); TR(0); TR(1); T4(5); TR(2); T4(6);
      mma_z(dl, a0.x, a0.y, a0.z, a0.w, kl[0], kl[1]); mma_z(dh, a0.x, a0.y, a0.z, a0.w, kh[0], kh[1]);
      BAR_ARRIVE_R(10 + q, 64);
      FENCE(5);
      STAMP(3);
      TR(3); TR(4); TR(5); TR(6);
      mma_z(el, a1.x, a1.y, a1.z, a1.w, kl[2], kl[3]); mma_z(eh, a1.x, a1.y, a1.z, a1.w, kh[2], kh[3]);
      mma16816(dl, a2.x, a2.y, a2.z, a2.w, kl[4], kl[5]); mma16816(dh, a2.x, a2.y, a2.z, a2.w, kh[4], kh[5]);
      float gl[4], gh[4];
      mma8_z(gl, a3.x, a3.y, kl[6]); mma8_z(gh, a3.x, a3.y, kh[6]);
      dl[0] += el[0]; dh[2] += eh[2]; dl[1] += el[1]; dh[3] += eh[3]; el[0] = gl[0]; el[1] = gl[1]; eh[2] = gh[2]; eh[3] = gh[3];
      sts64f(lq + QOFF(red), (dl[0] + dh[2]) + (el[0] + eh[2]), (dl[1] + dh[3]) + (el[1] + eh[3]));
      BAR_SYNC(2, 128);
      {
        float2 t0 = lds64f(l16 + QOFF(red)), t1 = lds64f(l16 + QOFF(red) + QB), t2 = lds64f(l16 + QOFF(red) + 2 * QB), t3 = lds64f(l16 + QOFF(red) + 3 * QB);
        st_async2(dst_sm, (t0.x + t1.x) + (t2.x + t3.x), (t0.y + t1.y) + (t2.y + t3.y), dst_bar);
      }
      STAMP(4);
      { const uint32_t kqa = lq + QOFF(kq) + (s & 1) * 2048;
      sts128(kqa, kl[0], kl[1], kh[0], kh[1]); sts128(kqa + 512, kl[2], kl[3], kh[2], kh[3]);
      sts128(kqa + 1024, kl[4], kl[5], kh[4], kh[5]); sts64(kqa + 1536, kl[6], kh[6]); }
      p += (s & 1) ? (1024 - 32) : 32;
      if (q == 1 && s >= 2 && s + 2 < NSEG) { if (elect1()) issue_loads(sb, s + 2, h, j); __syncwarp(); }
      if (s + 1 < NSEG) wait_bar1(bar_ld + 8 * ((s + 1) & (NST - 1)), ((s + 1) / NST) & 1);
      BAR_SYNC(4, 384);
      unsigned tred = clk();
      if (q == 0) { if (elect1()) { arm_bar(bar_sx, 1024); arm_bar(bar_sm, 1024); } __syncwarp(); }
      while (clk() - tred < (unsigned)(poll_delay & 0xffff)) {}
    }
  } else if (role == 1) {
    asm volatile("setmaxnreg.inc.sync.aligned.u32 216;");
    const int lane = opaque_lane();
    const uint32_t l16 = sb + lane * 16;
    uint4 W[42];
    {
      const uint4* wf = g_WF + (((NH + h) * 28 + 7 * j) * 28 + 7 * q) * 32 + lane;
#pragma unroll
      for (int k = 1; k < 7; k++)
#pragma unroll
        for (int t = 0; t < 7; t++) W[(k - 1) * 7 + t] = wf[(t * 28 + k) * 32];
    }
#undef ws
#define ws (lq + QOFF(wB))
    const uint32_t lq = l16 + q * QB;
#define uq (lq + QOFF(uQ))
#pragma unroll 1
    for (int s = 0; s < NSEG; s++) {
      const int st = s & (NST - 1);
      BAR_SYNC_R(5 + q, 64);
      uint4 p0 = lds128(mq), p1 = lds128(mq + 512), p2 = lds128(mq + 1024); uint2 p3 = lds64(mq + 1536);
      {
        uint32_t m = amax2(amax2(amax2(amax2(0u, p0.x, p0.y), p0.z, p0.w), p1.x, p1.y), p1.z, p1.w);
        m = amax2(amax2(amax2(m, p2.x, p2.y), p2.z, p2.w), p3.x, p3.y);
        m = max(m & 0xffffu, m >> 16);
        m = __reduce_max_sync(0xffffffffu, m);
        sts32(sb + OFF(smax) + q * 4, m);
      }
      BAR_SYNC(9, 128);
      if (q == 0) {
        uint4 m4 = lds128(sb + OFF(smax));
        uint32_t mb = max(max(m4.x, m4.y), max(m4.z, m4.w));
        float mh = fmaxf(__uint_as_float(mb << 16) * __uint_as_float(lds32(sb + OFF(sinv) + (s & 1) * 4)), __uint_as_float(lds32(sb + OFF(xmax) + s * 4)));
        float bound = mh * __uint_as_float(lds32(sb + OFF(sinv) + 8));
        int e = (int)(__float_as_uint(bound) >> 23) - 127 + 10;
        sts32(sb + OFF(sinv) + ((s + 1) & 1) * 4, (uint32_t)(127 - min(max(15 - e, -60), 60)) << 23);
      }
      uint4 f[7];
#pragma unroll
      for (int t = 0; t < 7; t++) f[t] = lds128(ws + t * 512);
      BAR_SYNC_R(10 + q, 64);
      FENCE(7);
      STAMP(10);
      const uint32_t b[14] = {p0.x, p0.y, p0.z, p0.w, p1.x, p1.y, p1.z, p1.w, p2.x, p2.y, p2.z, p2.w, p3.x, p3.y};
      float acc[7][4];
      T3(0); T3(1); T3(2); T3(3); T3(4); T3(5); T3(6);
      FENCE(8);
#define UP(nt) pack_bf16(acc[(nt) >> 1][((nt) & 1) * 2], acc[(nt) >> 1][((nt) & 1) * 2 + 1])
      T4(0); T4(1); T4(2); T4(3); T4(4); T4(5); T4(6);
      { uint32_t u6 = UP(6), u7 = UP(7);
        sts128(uq, UP(0), UP(1), UP(2), u6); sts128(uq + 512, UP(3), UP(4), UP(5), u6);
        sts128(uq + 1024, UP(8), UP(9), UP(10), u7); sts128(uq + 1536, UP(11), UP(12), UP(13), u7); }
      BAR_ARRIVE(3, 256);
      STAMP(11);
      const float inv = __uint_as_float(lds32(sb + OFF(sinv) + (s & 1) * 4));
      BAR_SYNC(4, 384);
      {
        const int nt0 = q < 2 ? q * 3 : 8 + (q - 2) * 3, nts = 6 + (q >> 1);
        uint32_t ub = l16 + QOFF(uQ) + q * 512; asm volatile("" : "+r"(ub));
        uint4 u0 = lds128(ub), u1 = lds128(ub + QB), u2 = lds128(ub + 2 * QB), u3 = lds128(ub + 3 * QB);
        auto us = [&](uint32_t a, uint32_t b, uint32_t c, uint32_t d) { return pack_bf16(((bf_lo(a) + bf_lo(b)) + (bf_lo(c) + bf_lo(d))) * inv, ((bf_hi(a) + bf_hi(b)) + (bf_hi(c) + bf_hi(d))) * inv); };
        uint32_t* uf = (uint32_t*)((char*)(g_UF + ((s * NH + h) * 56 + 14 * j) * 32) + ((l16 - sb) >> 2));
        { uf[(nt0 + 0) * 32] = us(u0.x, u1.x, u2.x, u3.x); uf[(nt0 + 1) * 32] = us(u0.y, u1.y, u2.y, u3.y); uf[(nt0 + 2) * 32] = us(u0.z, u1.z, u2.z, u3.z);
        if ((q & 1) == 0) uf[nts * 32] = us(u0.w, u1.w, u2.w, u3.w); }
      }
      {
        const uint32_t xb = l16 + OFF(xf) + st * 7168;
        const uint32_t kqa = lq + QOFF(kq) + (s & 1) * 2048;
        uint4 k0 = lds128(kqa), k1 = lds128(kqa + 512), k2 = lds128(kqa + 1024); uint2 k3 = lds64(kqa + 1536);
        const uint32_t kk[14] = {k0.x, k0.y, k0.z, k0.w, k1.x, k1.y, k1.z, k1.w, k2.x, k2.y, k2.z, k2.w, k3.x, k3.y};
        float y[2][4];
#pragma unroll
        for (int f = 0; f < 7; f++)
#pragma unroll
          for (int m = 0; m < 2; m++) {
            uint4 xa = lds128(xb + (f * 2 + m) * 512);
            MMW(y[m], xa, kk[2 * f], kk[2 * f + 1], f == 0);
          }
        sts128(lq + QOFF(xred), __float_as_uint(y[0][0]), __float_as_uint(y[0][1]), __float_as_uint(y[0][2]), __float_as_uint(y[0][3]));
        sts128(lq + QOFF(xred) + 512, __float_as_uint(y[1][0]), __float_as_uint(y[1][1]), __float_as_uint(y[1][2]), __float_as_uint(y[1][3]));
        BAR_SYNC(15, 128);
        if (q < 2) {
          uint32_t xr = l16 + QOFF(xred) + q * 512; asm volatile("" : "+r"(xr));
          float4 t0 = lds128f(xr), t1 = lds128f(xr + QB), t2 = lds128f(xr + 2 * QB), t3 = lds128f(xr + 3 * QB);
          *(float4*)((char*)(g_SXM + ((((s * NH + h) * 4 + j) * 2 + q) * 32)) + (l16 - sb)) = make_float4(((t0.x + t1.x) + (t2.x + t3.x)) * inv, ((t0.y + t1.y) + (t2.y + t3.y)) * inv, ((t0.z + t1.z) + (t2.z + t3.z)) * inv, ((t0.w + t1.w) + (t2.w + t3.w)) * inv);
        }
      }
    }
  } else {
    asm volatile("setmaxnreg.dec.sync.aligned.u32 64;");
    const int lane = opaque_lane();
    const uint32_t l16 = sb + lane * 16;
    const int nt0 = q < 2 ? q * 3 : 8 + (q - 2) * 3, nts = 6 + (q >> 1);
    int se = (int)(127 - (__float_as_uint(g_inv0) >> 23));
    uint4* redp = acc_ptr(1, j * 4 + q, lane);
    const uint32_t dst_sx = mapa(l16 + OFF(sx) + (j >> 1) * 512 + (j & 1) * 8, q), dst_bar = mapa(bar_sx, q);
#pragma unroll 1
    for (int s = 0; s < NSEG; s++) {
      const int st = s & (NST - 1);
      float ya[4], yb[4], z[4];
      float mx;
      int nse;
      const float inv = __uint_as_float((uint32_t)(127 - se) << 23);
      const float c1 = LOG2E * inv;
      {
        const uint32_t vb = l16 + OFF(vf) + st * 7168;
        wait_bar1(bar_ld + 8 * st, (s / NST) & 1);
        uint4 v0 = lds128(vb + nt0 * 512), v1 = lds128(vb + nt0 * 512 + 512), v2 = lds128(vb + nt0 * 512 + 1024), v3 = lds128(vb + nts * 512);
        BAR_SYNC(14, 256);
        STAMP(2);
        {
          float2 t0 = lds64f(l16 + QOFF(red) + 8), t1 = lds64f(l16 + QOFF(red) + 8 + QB), t2 = lds64f(l16 + QOFF(red) + 8 + 2 * QB), t3 = lds64f(l16 + QOFF(red) + 8 + 3 * QB);
          st_async2(dst_sx, (t0.x + t1.x) + (t2.x + t3.x), (t0.y + t1.y) + (t2.y + t3.y), dst_bar);
        }
        STAMP(9);
        wait_bar1(bar_sx, s & 1);
        STAMP(12);
        float4 x0 = lds128f(l16 + OFF(sx)), x1 = lds128f(l16 + OFF(sx) + 512);
        float sx[8] = {x0.x, x0.y, x0.z, x0.w, x1.x, x1.y, x1.z, x1.w};
        mx = fmaxf(fmaxf(fmaxf(sx[0], sx[1]), fmaxf(sx[2], sx[3])), fmaxf(fmaxf(sx[4], sx[5]), fmaxf(sx[6], sx[7])));
        mx = fmaxf(mx, __shfl_xor_sync(0xffffffffu, mx, 1)); mx = fmaxf(mx, __shfl_xor_sync(0xffffffffu, mx, 2));
        mx *= c1;
#pragma unroll
        for (int i = 0; i < 8; i++) sx[i] = ex2(fmaf(sx[i], c1, -mx));
        uint32_t p0 = pack_bf16(sx[0], sx[1]), p1 = pack_bf16(sx[2], sx[3]), p2 = pack_bf16(sx[4], sx[5]), p3 = pack_bf16(sx[6], sx[7]);
        float o[4], r[4];
        mma_z(o, p0, p2, p1, p3, v0.x, v0.y); mma_z(r, p0, p2, p1, p3, v0.z, v0.w); ya[0] = o[0] + r[2]; ya[1] = o[1] + r[3];
        mma_z(o, p0, p2, p1, p3, v1.x, v1.y); mma_z(r, p0, p2, p1, p3, v1.z, v1.w); ya[2] = o[0] + r[2]; ya[3] = o[1] + r[3];
        mma_z(o, p0, p2, p1, p3, v2.x, v2.y); mma_z(r, p0, p2, p1, p3, v2.z, v2.w); yb[0] = o[0] + r[2]; yb[1] = o[1] + r[3];
        mma_z(o, p0, p2, p1, p3, v3.x, v3.y); mma_z(r, p0, p2, p1, p3, v3.z, v3.w); yb[2] = o[0] + r[2]; yb[3] = o[1] + r[3];
        mma_z(z, p0, p2, p1, p3, 0x3f803f80u, 0x3f803f80u); z[0] += z[2];
      }
      asm volatile("" : "+f"(ya[0]), "+f"(ya[1]), "+f"(ya[2]), "+f"(ya[3]), "+f"(yb[0]), "+f"(yb[1]), "+f"(yb[2]), "+f"(yb[3]), "+f"(z[0]));
      STAMP(5);
      FENCE(9);
      BAR_SYNC(3, 256);
      uint32_t u[4];
      {
        const uint32_t ub = l16 + QOFF(uQ) + q * 512;
        uint4 u0 = lds128(ub), u1 = lds128(ub + QB), u2 = lds128(ub + 2 * QB), u3 = lds128(ub + 3 * QB);
        u[0] = hadd_bf2(hadd_bf2(u0.x, u1.x), hadd_bf2(u2.x, u3.x)); u[1] = hadd_bf2(hadd_bf2(u0.y, u1.y), hadd_bf2(u2.y, u3.y));
        u[2] = hadd_bf2(hadd_bf2(u0.z, u1.z), hadd_bf2(u2.z, u3.z)); u[3] = hadd_bf2(hadd_bf2(u0.w, u1.w), hadd_bf2(u2.w, u3.w));
      }
      { const uint32_t nb = lds32(sb + OFF(sinv) + ((s + 1) & 1) * 4); nse = 127 - (int)(nb >> 23); z[0] *= __uint_as_float(nb); }
      const uint32_t zb = (uint32_t)(127 + se - nse) * 0x00800080u;
      const float c2 = c1 * inv;
      float off = -mx - (float)se;
      const float lim = 32.f - (float)se;
      STAMP(6);
      wait_bar1(bar_sm, s & 1);
      STAMP(7);
      {
        float4 t0 = lds128f(l16 + OFF(sm)), t1 = lds128f(l16 + OFF(sm) + 512);
        const float r0 = (t0.x + t0.z) + (t1.x + t1.z), r1 = (t0.y + t0.w) + (t1.y + t1.w);
        float a0 = fmaf(r0, c2, off), a1 = fmaf(r1, c2, off);
        uint32_t pm = pack_bf16(ex2v(a0), ex2v(a1));
        if (__any_sync(0xffffffffu, !(fmaxf(a0, a1) <= lim))) {
          float m = fmaxf(fmaxf(r0, r1) * c2, mx);
          m = fmaxf(m, __shfl_xor_sync(0xffffffffu, m, 1)); m = fmaxf(m, __shfl_xor_sync(0xffffffffu, m, 2));
          const float al = ex2(mx - m);
#pragma unroll
          for (int i = 0; i < 4; i++) { ya[i] *= al; yb[i] *= al; }
          z[0] *= al;
          off = -m - (float)se;
          pm = pack_bf16(ex2(fmaf(r0, c2, off)), ex2(fmaf(r1, c2, off)));
        }
        mma16816(z, pm, 0u, 0u, pm, zb, zb);
        mma16816(ya, pm, 0u, 0u, pm, u[0], u[1]); mma16816(yb, pm, 0u, 0u, pm, u[2], u[3]);
        float iz; asm("rcp.approx.ftz.f32 %0, %1;" : "=f"(iz) : "f"(z[0]));
        red_h8(redp, pack_f16(ya[0] * iz, ya[1] * iz), pack_f16(ya[2] * iz, ya[3] * iz), pack_f16(yb[0] * iz, yb[1] * iz), pack_f16(((q & 1) ? yb[3] : yb[2]) * iz, 1.f));
      }
      BAR_ARRIVE(4, 384);
      STAMP(8);
      redp += (s & 1) ? 32 : (1024 - 32);
      se = nse;
    }
  }
  asm volatile("barrier.cluster.arrive.release.aligned;\nbarrier.cluster.wait.acquire.aligned;" ::: "memory");
}

__global__ void n_xf(const bf16* x) {
  int i = blockIdx.x * blockDim.x + threadIdx.x;
  if (i >= NSEG * 4 * 14 * 32) return;
  int lane = i & 31, r = i >> 5, m = r & 1; r >>= 1; int f = r % 7; r /= 7; int j = r & 3, seg = r >> 2;
  int c0 = f == 6 ? 96 : (f & ~1) * 16 + (f & 1) * 8, c1 = f == 6 ? 104 : (f | 1) * 16 + (f & 1) * 8;
  const bf16* r0 = x + (seg * 32 + m * 16 + (lane >> 2)) * DM + j * 112 + (lane & 3) * 2;
  const bf16* r1 = r0 + 8 * DM;
  g_XF[i] = make_uint4(*(const uint32_t*)(r0 + c0), *(const uint32_t*)(r1 + c0), *(const uint32_t*)(r0 + c1), *(const uint32_t*)(r1 + c1));
}

__global__ void n_seed(const bf16* mem0) {
  __shared__ unsigned smx;
  if (threadIdx.x == 0) smx = 0;
  __syncthreads();
  float m = 0.f;
  for (int i = threadIdx.x; i < 8 * DM; i += 512) m = fmaxf(m, fabsf(b2f(mem0[i])));
  atomicMax(&smx, __float_as_uint(m));
  __syncthreads();
  int e = (int)(smx >> 23) - 127 + 1;
  int se = min(max(15 - e, -60), 60);
  float sc = __uint_as_float((uint32_t)(127 + se) << 23);
  if (threadIdx.x == 0) g_inv0 = __uint_as_float((uint32_t)(127 - se) << 23);
  int vec = threadIdx.x >> 5, lane = threadIdx.x & 31, j = vec >> 2, q = vec & 3;
  int nt0 = q < 2 ? q * 3 : 8 + (q - 2) * 3, nts = 6 + (q >> 1);
  const bf16* r = mem0 + (lane >> 2) * DM + j * 112 + (lane & 3) * 2;
  auto val = [&](int nt, int e2) { return b2f(r[nt * 8 + e2]) * sc; };
  *acc_ptr(0, vec, lane) = make_uint4(pack_f16(val(nt0, 0), val(nt0, 1)), pack_f16(val(nt0 + 1, 0), val(nt0 + 1, 1)), pack_f16(val(nt0 + 2, 0), val(nt0 + 2, 1)), pack_f16(val(nts, q & 1), 16.f));
}

__global__ void n_stats(const bf16* x) {
  if (blockIdx.x < 64) {
    float m = 0.f;
    for (int i = threadIdx.x; i < 32 * DM; i += 256) m = fmaxf(m, fabsf(b2f(x[blockIdx.x * 32 * DM + i])));
    atomicMax((unsigned*)&g_xmax[blockIdx.x], __float_as_uint(m));
  } else {
    int r = (blockIdx.x - 64) * 256 + threadIdx.x;
    if (r < NH * DM) { float a = 0.f; for (int k = 0; k < DM; k++) { float v = wf_elem(1, r / DM, r % DM, k); a += v * v; } atomicMax((unsigned*)&g_bmax, __float_as_uint(sqrtf(a))); }
  }
}

int g_poll_delay = POLL_DELAY;
extern "C" void kernel_launch(void* const* d_in, const int* in_sizes, int n_in, void* d_out, int out_size) {
  const bf16* x = (const bf16*)d_in[0];
  const bf16* wqkv = (const bf16*)d_in[1];
  const bf16* wphi = (const bf16*)d_in[2];
  const bf16* wo_a = (const bf16*)d_in[3];
  const bf16* mem0 = (const bf16*)d_in[5];
  const bf16* Wq = (const bf16*)d_in[6];
  const bf16* Wk = (const bf16*)d_in[7];
  const bf16* Wv = (const bf16*)d_in[8];
  const bf16* Wo = (const bf16*)d_in[9];
  const bf16* gate_w = (const bf16*)d_in[11];
  bf16* out = (bf16*)d_out;
  cudaFuncSetAttribute(r_kernel, cudaFuncAttributeMaxDynamicSharedMemorySize, (int)sizeof(RSmem));
  n_zero<<<(NSEG * 40 * 32 + 255) / 256, 256>>>();
  n_prep<<<(2 * NH * 28 * 28 * 32 + 255) / 256, 256>>>(Wq, Wk, Wv, Wo);
  n_stats<<<64 + 28, 256>>>(x);
  n_seed<<<1, 512>>>(mem0);
  n_xf<<<NSEG * 4 * 14 * 32 / 256, 256>>>(x);
  n_xgemm<<<2 * NH * 28 * NSEG * 32 / 256, 256>>>(x);
  r_kernel<<<64, 384, sizeof(RSmem)>>>(mem0, g_poll_delay);
  n_qkv<<<(S_LEN * 1344 + 255) / 256, 256>>>(x, wqkv);
  n_phi<<<(S_LEN * 2 * NH + 255) / 256, 256>>>(wphi);
  n_kv<<<(32 * NH * 56 * 29 + 255) / 256, 256>>>();
  n_oa<<<(S_LEN * DM + 255) / 256, 256>>>();
  n_x3<<<NSEG, 512>>>(x, wo_a, gate_w, out);
}
```

```cpp
#include <cuda_runtime.h>
#include <cuda_bf16.h>
#include <stdint.h>
#include <stddef.h>

typedef __nv_bfloat16 bf16;
#define S_LEN 2048
#define DM 448
#define NH 16
#define NSEG 64
#define SPIN_LIMIT (1 << 22)

__device__ uint4 g_WF[2 * NH * 28 * 28 * 32];
__device__ uint4 g_KF[NSEG * NH * 4 * 4 * 4 * 32];
__device__ uint4 g_VF[NSEG * NH * 56 * 32];
__device__ float4 g_SXM[NSEG * NH * 4 * 2 * 32];
__device__ uint4 g_XF[NSEG * 4 * 14 * 32];
__device__ uint32_t g_UF[NSEG * NH * 56 * 32];
__device__ uint4 g_ACC16[(NSEG + 2) * 16 * 32];
__device__ float g_xmax[NSEG];
__device__ float g_bmax;
__device__ float g_inv0;
__device__ float g_qkv[S_LEN * 1344];
__device__ float g_phiq[S_LEN * NH * 56];
__device__ float g_phik[S_LEN * NH * 56];
__device__ float g_kv[NH * 56 * 29];
__device__ float g_oa[S_LEN * DM];
__device__ int g_err;
__device__ unsigned g_ts[64 * 64 * 64];

__device__ __forceinline__ uint32_t pack_bf16(float lo, float hi) {
  uint32_t r; asm("cvt.rn.bf16x2.f32 %0, %1, %2;" : "=r"(r) : "f"(hi), "f"(lo)); return r;
}
__device__ __forceinline__ float bf_lo(uint32_t v) { return __uint_as_float(v << 16); }
__device__ __forceinline__ float bf_hi(uint32_t v) { return __uint_as_float(v & 0xffff0000u); }
__device__ __forceinline__ float b2f(bf16 v) { return __bfloat162float(v); }

__global__ void n_prep(const bf16* Wq, const bf16* Wk, const bf16* Wv, const bf16* Wo) {
  int idx = blockIdx.x * blockDim.x + threadIdx.x;
  if (idx >= 2 * NH * 28 * 28 * 32) return;
  int lane = idx & 31, r = idx >> 5;
  int ks = r % 28; r /= 28; int tile = r % 28; r /= 28; int h = r % NH; int mat = r / NH;
  int g = lane >> 2, tq = lane & 3;
  float v[8];
  for (int i = 0; i < 8; i++) {
    int row = tile * 16 + g + ((i >> 1) & 1) * 8;
    int col = ks * 16 + tq * 2 + (i & 1) + (i >> 2) * 8;
    float acc = 0.f;
    if (mat == 0) { for (int e = 0; e < 256; e++) acc += b2f(Wq[(row * NH + h) * 256 + e]) * b2f(Wk[(col * NH + h) * 256 + e]); acc *= 0.0625f; }
    else { for (int e = 0; e < 256; e++) acc += b2f(Wo[(h * 256 + e) * DM + row]) * b2f(Wv[(col * NH + h) * 256 + e]); }
    v[i] = acc;
  }
  g_WF[idx] = make_uint4(pack_bf16(v[0], v[1]), pack_bf16(v[2], v[3]), pack_bf16(v[4], v[5]), pack_bf16(v[6], v[7]));
}
__device__ __forceinline__ float wf_elem(int mat, int h, int row, int col) {
  int tile = row >> 4, ks = col >> 4, rr = row & 15, cc = col & 15;
  int lane = (rr & 7) * 4 + ((cc & 7) >> 1);
  int reg = (rr >> 3) + (cc >> 3) * 2;
  uint32_t w = ((const uint32_t*)g_WF)[((((mat * NH + h) * 28 + tile) * 28 + ks) * 32 + lane) * 4 + reg];
  return (cc & 1) ? bf_hi(w) : bf_lo(w);
}
__device__ __forceinline__ void mma16816(float* d, uint32_t a0, uint32_t a1, uint32_t a2, uint32_t a3, uint32_t b0, uint32_t b1) {
  asm volatile("mma.sync.aligned.m16n8k16.row.col.f32.bf16.bf16.f32 {%0,%1,%2,%3}, {%4,%5,%6,%7}, {%8,%9}, {%0,%1,%2,%3};"
    : "+f"(d[0]), "+f"(d[1]), "+f"(d[2]), "+f"(d[3]) : "r"(a0), "r"(a1), "r"(a2), "r"(a3), "r"(b0), "r"(b1));
}
__device__ __forceinline__ void mma1688(float* d, uint32_t a0, uint32_t a1, uint32_t b0) {
  asm volatile("mma.sync.aligned.m16n8k8.row.col.f32.bf16.bf16.f32 {%0,%1,%2,%3}, {%4,%5}, {%6}, {%0,%1,%2,%3};"
    : "+f"(d[0]), "+f"(d[1]), "+f"(d[2]), "+f"(d[3]) : "r"(a0), "r"(a1), "r"(b0));
}
__device__ __forceinline__ uint32_t movm(uint32_t a) { uint32_t d; asm volatile("movmatrix.sync.aligned.m8n8.trans.b16 %0, %1;" : "=r"(d) : "r"(a)); return d; }

__global__ void n_xgemm(const bf16* x) {
  int wid = (blockIdx.x * blockDim.x + threadIdx.x) >> 5, lane = threadIdx.x & 31;
  int seg = wid % NSEG; int r = wid / NSEG;
  int tile = r % 28; r /= 28; int h = r % NH; int mat = r / NH;
  if (mat >= 2) return;
  int g = lane >> 2, tq = lane & 3;
  float d[4][4] = {};
  const uint4* wf = g_WF + (((mat * NH + h) * 28 + tile) * 28) * 32 + lane;
  for (int ks = 0; ks < 28; ks++) {
    uint4 a = wf[ks * 32];
    for (int kg = 0; kg < 4; kg++) {
      const uint32_t* xr = (const uint32_t*)(x + (seg * 32 + kg * 8 + g) * DM + ks * 16 + tq * 2);
      mma16816(d[kg], a.x, a.y, a.z, a.w, xr[0], xr[4]);
    }
  }
  if (mat == 0) {
    for (int kg = 0; kg < 4; kg++) {
      uint32_t b0 = movm(pack_bf16(d[kg][0], d[kg][1])), b1 = movm(pack_bf16(d[kg][2], d[kg][3]));
      int jj = tile / 7, i = tile % 7;
      uint32_t* dst = (uint32_t*)&g_KF[((((seg * NH + h) * 4 + kg) * 4 + jj) * 4 + (i >> 1)) * 32 + lane];
      if (i == 6) { dst[0] = b0; dst[1] = b1; } else { dst[i & 1] = b0; dst[2 + (i & 1)] = b1; }
    }
  } else {
    g_VF[((seg * NH + h) * 56 + tile * 2) * 32 + lane] = make_uint4(pack_bf16(d[0][0], d[0][1]), pack_bf16(d[1][0], d[1][1]), pack_bf16(d[2][0], d[2][1]), pack_bf16(d[3][0], d[3][1]));
    g_VF[((seg * NH + h) * 56 + tile * 2 + 1) * 32 + lane] = make_uint4(pack_bf16(d[0][2], d[0][3]), pack_bf16(d[1][2], d[1][3]), pack_bf16(d[2][2], d[2][3]), pack_bf16(d[3][2], d[3][3]));
  }
}
__global__ void n_zero() {
  int i = blockIdx.x * blockDim.x + threadIdx.x;
  if (i < (NSEG + 2) * 16 * 32) g_ACC16[i] = make_uint4(0, 0, 0, 0);
  if (i < NSEG) g_xmax[i] = 0.f;
  if (i == 0) g_bmax = 0.f;
  if (i < NH * 56 * 29) g_kv[i] = 0.f;
}
__global__ void n_qkv(const bf16* x, const bf16* w) {
  int i = blockIdx.x * blockDim.x + threadIdx.x;
  if (i >= S_LEN * 1344) return;
  int n = i % 1344, t = i / 1344;
  float acc = 0.f;
  for (int k = 0; k < DM; k++) acc += b2f(x[t * DM + k]) * b2f(w[k * 1344 + n]);
  g_qkv[i] = acc;
}
__global__ void n_phi(const bf16* wphi) {
  int i = blockIdx.x * blockDim.x + threadIdx.x;
  if (i >= S_LEN * 2 * NH) return;
  int h = i % NH, which = (i / NH) % 2, t = i / (2 * NH);
  float p[28]; float mx = -1e30f, mn = 1e30f;
  for (int f = 0; f < 28; f++) {
    float acc = 0.f;
    for (int d = 0; d < 28; d++) acc += g_qkv[t * 1344 + which * 448 + h * 28 + d] * b2f(wphi[(h * 28 + d) * 28 + f]);
    p[f] = acc; mx = fmaxf(mx, acc); mn = fminf(mn, acc);
  }
  float s1 = 0.f, s2 = 0.f;
  for (int f = 0; f < 28; f++) { s1 += __expf(p[f] - mx); s2 += __expf(mn - p[f]); }
  float* o = (which ? g_phik : g_phiq) + (t * NH + h) * 56;
  for (int f = 0; f < 28; f++) { o[f] = __expf(p[f] - mx) / s1; o[28 + f] = __expf(mn - p[f]) / s2; }
}
__global__ void n_kv() {
  int i = blockIdx.x * blockDim.x + threadIdx.x;
  if (i >= 32 * NH * 56 * 29) return;
  int d = i % 29, f = (i / 29) % 56, h = (i / (29 * 56)) % NH, ch = i / (29 * 56 * NH);
  float acc = 0.f;
  for (int t = ch * 64; t < ch * 64 + 64; t++) acc += g_phik[(t * NH + h) * 56 + f] * (d < 28 ? g_qkv[t * 1344 + 896 + h * 28 + d] : 1.f);
  atomicAdd(&g_kv[(h * 56 + f) * 29 + d], acc);
}
__global__ void n_oa() {
  int i = blockIdx.x * blockDim.x + threadIdx.x;
  if (i >= S_LEN * DM) return;
  int c = i % DM, t = i / DM, h = c / 28, d = c % 28;
  float num = 0.f, den = 0.f;
  for (int f = 0; f < 56; f++) { float p = g_phiq[(t * NH + h) * 56 + f]; num += p * g_kv[(h * 56 + f) * 29 + d]; den += p * g_kv[(h * 56 + f) * 29 + 28]; }
  g_oa[i] = num / (den + 1e-6f);
}

__global__ void __launch_bounds__(512) n_x3(const bf16* x, const bf16* wo, const bf16* gate_w, bf16* out) {
  __shared__ uint32_t sP[NH][2][32][10];
  __shared__ float sG[32];
  int seg = blockIdx.x, w = threadIdx.x >> 5, lane = threadIdx.x & 31, g = lane >> 2, tq = lane & 3;
  for (int r = w; r < 32; r += 16) {
    float acc = 0.f;
    for (int k = lane; k < DM; k += 32) acc += b2f(x[(seg * 32 + r) * DM + k]) * b2f(gate_w[k]);
    for (int o = 16; o; o >>= 1) acc += __shfl_xor_sync(0xffffffffu, acc, o);
    if (lane == 0) sG[r] = 1.f / (1.f + __expf(-acc));
  }
  {
    int h = w;
    float s[2][5][4] = {};
    for (int ct = 0; ct < 28; ct++) {
      uint32_t a[2][4];
      for (int m = 0; m < 2; m++) {
        const uint32_t* r0 = (const uint32_t*)(x + (seg * 32 + m * 16 + g) * DM + ct * 16 + tq * 2);
        const uint32_t* r1 = (const uint32_t*)(x + (seg * 32 + m * 16 + g + 8) * DM + ct * 16 + tq * 2);
        a[m][0] = r0[0]; a[m][1] = r1[0]; a[m][2] = r0[4]; a[m][3] = r1[4];
      }
      int j = ct / 7, i = ct % 7;
      for (int kg = 0; kg < 4; kg++) {
        const uint32_t* src = (const uint32_t*)&g_KF[((((seg * NH + h) * 4 + kg) * 4 + j) * 4 + (i >> 1)) * 32 + lane];
        uint2 b = i == 6 ? make_uint2(src[0], src[1]) : make_uint2(src[i & 1], src[2 + (i & 1)]);
        for (int m = 0; m < 2; m++) mma16816(s[m][1 + kg], a[m][0], a[m][1], a[m][2], a[m][3], b.x, b.y);
      }
    }
    for (int m = 0; m < 2; m++) for (int j = 0; j < 4; j++) {
      float4 t = g_SXM[(((seg * NH + h) * 4 + j) * 2 + m) * 32 + lane];
      s[m][0][0] += t.x; s[m][0][1] += t.y; s[m][0][2] += t.z; s[m][0][3] += t.w;
    }
    for (int m = 0; m < 2; m++) for (int hf = 0; hf < 2; hf++) {
      int t = m * 16 + hf * 8 + g;
      float v[10]; float mx = -1e30f;
      for (int n = 0; n < 5; n++) for (int e = 0; e < 2; e++) {
        float val = s[m][n][hf * 2 + e];
        if (n > 0 && (n - 1) * 8 + tq * 2 + e > t) val = -1e30f;
        v[n * 2 + e] = val; mx = fmaxf(mx, val);
      }
      mx = fmaxf(mx, __shfl_xor_sync(0xffffffffu, mx, 1)); mx = fmaxf(mx, __shfl_xor_sync(0xffffffffu, mx, 2));
      float z = 0.f;
      for (int i = 0; i < 10; i++) { v[i] = __expf(v[i] - mx); z += v[i]; }
      z += __shfl_xor_sync(0xffffffffu, z, 1); z += __shfl_xor_sync(0xffffffffu, z, 2);
      float iz = 1.f / z;
      sP[h][m][lane][hf] = pack_bf16(v[0] * iz, v[1] * iz);
      sP[h][m][lane][2 + hf] = pack_bf16(v[2] * iz, v[3] * iz);
      sP[h][m][lane][4 + hf] = pack_bf16(v[4] * iz, v[5] * iz);
      sP[h][m][lane][6 + hf] = pack_bf16(v[6] * iz, v[7] * iz);
      sP[h][m][lane][8 + hf] = pack_bf16(v[8] * iz, v[9] * iz);
    }
  }
  __syncthreads();
  if (w < 14) {
    float o[2][4][4] = {};
    for (int h = 0; h < NH; h++) {
      for (int n = 0; n < 4; n++) {
        int nt = w * 4 + n;
        uint4 v = g_VF[((seg * NH + h) * 56 + nt) * 32 + lane];
        uint32_t u = g_UF[((seg * NH + h) * 56 + nt) * 32 + lane];
        for (int m = 0; m < 2; m++) {
          const uint32_t* p = sP[h][m][lane];
          mma1688(o[m][n], p[0], p[1], u);
          mma16816(o[m][n], p[2], p[3], p[4], p[5], v.x, v.y);
          mma16816(o[m][n], p[6], p[7], p[8], p[9], v.z, v.w);
        }
      }
    }
    for (int m = 0; m < 2; m++) for (int n = 0; n < 4; n++) for (int i = 0; i < 4; i++) {
      int r = m * 16 + (i >> 1) * 8 + g, c = (w * 4 + n) * 8 + tq * 2 + (i & 1);
      int t = seg * 32 + r;
      float a = 0.f;
      for (int k = 0; k < DM; k++) a += g_oa[t * DM + k] * b2f(wo[k * DM + c]);
      float gt = sG[r];
      out[t * DM + c] = __float2bfloat16(gt * a + (1.f - gt) * o[m][n][i]);
    }
  }
}

__device__ __forceinline__ uint32_t smem_u32(const void* p) { return (uint32_t)__cvta_generic_to_shared(p); }
__device__ __forceinline__ uint32_t mapa(uint32_t a, uint32_t r) { uint32_t o; asm volatile("mapa.shared::cluster.u32 %0, %1, %2;" : "=r"(o) : "r"(a), "r"(r)); return o; }
__device__ __forceinline__ bool try_wait(uint32_t bar, uint32_t parity) {
  uint32_t ok; asm volatile("{\n.reg .pred p;\nmbarrier.try_wait.parity.shared::cta.b64 p, [%1], %2;\nselp.u32 %0, 1, 0, p;\n}" : "=r"(ok) : "r"(bar), "r"(parity) : "memory"); return ok; }
__device__ __forceinline__ void wait_bar(uint32_t bar, uint32_t parity) {
  int n = 0; while (!try_wait(bar, parity)) { if (++n > SPIN_LIMIT) { g_err = 1; break; } } }
__device__ __forceinline__ void arm_bar(uint32_t bar, uint32_t bytes) { asm volatile("mbarrier.arrive.expect_tx.shared::cta.b64 _, [%0], %1;" :: "r"(bar), "r"(bytes) : "memory"); }
__device__ __forceinline__ float4 ld_relaxed4(const void* p) { float4 v; asm volatile("ld.relaxed.gpu.global.v4.f32 {%0,%1,%2,%3}, [%4];" : "=f"(v.x), "=f"(v.y), "=f"(v.z), "=f"(v.w) : "l"(p) : "memory"); return v; }
__device__ __forceinline__ void red4(void* p, float a, float b, float c, float d) { asm volatile("red.relaxed.gpu.global.add.v4.f32 [%0], {%1,%2,%3,%4};" :: "l"(p), "f"(a), "f"(b), "f"(c), "f"(d) : "memory"); }
__device__ __forceinline__ void st_async2(uint32_t dst, float a, float b, uint32_t bar) { asm volatile("st.async.shared::cluster.mbarrier::complete_tx::bytes.v2.f32 [%0], {%1,%2}, [%3];" :: "r"(dst), "f"(a), "f"(b), "r"(bar) : "memory"); }
__device__ __forceinline__ void bulk_g2s(uint32_t dst, const void* src, uint32_t bytes, uint32_t bar) {
  asm volatile("cp.async.bulk.shared::cluster.global.mbarrier::complete_tx::bytes [%0], [%1], %2, [%3];" :: "r"(dst), "l"(src), "r"(bytes), "r"(bar) : "memory"); }
__device__ __forceinline__ unsigned clk() { unsigned c; asm volatile("mov.u32 %0, %%clock;" : "=r"(c) :: "memory"); return c; }
__device__ __forceinline__ float ex2(float x) { float y; asm("ex2.approx.ftz.f32 %0, %1;" : "=f"(y) : "f"(x)); return y; }

#define NST 4
struct QBlk {
  uint4 memF[4][32];
  uint4 wA[7][32], wB[7][32];
  uint4 kf[NST][4][32];
  float4 xred[2][32];
  float4 red[32];
  uint4 uQ[4][32];
  uint4 kq[2][4][32];
};
#define QB ((uint32_t)sizeof(QBlk))
#define QOFF(f) ((uint32_t)offsetof(QBlk, f))
struct RSmem {
  QBlk qb[4];
  uint4 vf[NST][14][32];
  uint4 xf[NST][14][32];
  float4 sx[2][32];
  float4 sm[2][32];
  uint32_t smax[4];
  float xmax[NSEG];
  float sinv[4];
  unsigned long long bar_ld[NST], bar_sx, bar_sm;
  unsigned ts[64 * 64];
};
#define LD_BYTES (8192 + 7168 + 7168)
#define POLL_DELAY 300
#define STAMP(i)
__device__ __forceinline__ void wait_slow(uint32_t bar, uint32_t parity) {
#pragma unroll 1
  for (int n = 0; n < SPIN_LIMIT; n++) if (try_wait(bar, parity)) return;
  g_err = 1;
}
__device__ __forceinline__ void wait_bar1(uint32_t bar, uint32_t parity) { if (!try_wait(bar, parity)) wait_slow(bar, parity); }
__device__ __forceinline__ uint4 ld_relaxed_u4(const void* p) { uint4 v; asm volatile("ld.relaxed.gpu.global.v4.u32 {%0,%1,%2,%3}, [%4];" : "=r"(v.x), "=r"(v.y), "=r"(v.z), "=r"(v.w) : "l"(p) : "memory"); return v; }
__device__ __forceinline__ void red_h8(void* p, uint32_t a, uint32_t b, uint32_t c, uint32_t d) { asm volatile("red.relaxed.gpu.global.add.noftz.v4.f16x2 [%0], {%1,%2,%3,%4};" :: "l"(p), "r"(a), "r"(b), "r"(c), "r"(d) : "memory"); }
__device__ __forceinline__ uint32_t pack_f16(float lo, float hi) { uint32_t r; asm("cvt.rn.f16x2.f32 %0, %1, %2;" : "=r"(r) : "f"(hi), "f"(lo)); return r; }
__device__ __forceinline__ uint32_t h2_to_bf2(uint32_t v) {
  float lo, hi; asm("{.reg .f16 l, h; mov.b32 {l, h}, %2; cvt.f32.f16 %0, l; cvt.f32.f16 %1, h;}" : "=f"(lo), "=f"(hi) : "r"(v)); return pack_bf16(lo, hi); }
__device__ __forceinline__ uint2 lds64(uint32_t a) { uint2 v; asm volatile("ld.shared.v2.u32 {%0,%1}, [%2];" : "=r"(v.x), "=r"(v.y) : "r"(a) : "memory"); return v; }
__device__ __forceinline__ float2 lds64f(uint32_t a) { float2 v; asm volatile("ld.shared.v2.f32 {%0,%1}, [%2];" : "=f"(v.x), "=f"(v.y) : "r"(a) : "memory"); return v; }
__device__ __forceinline__ uint4 lds128(uint32_t a) { uint4 v; asm volatile("ld.shared.v4.u32 {%0,%1,%2,%3}, [%4];" : "=r"(v.x), "=r"(v.y), "=r"(v.z), "=r"(v.w) : "r"(a) : "memory"); return v; }
__device__ __forceinline__ uint4 lds128v(uint32_t a) { uint4 v; asm volatile("ld.volatile.shared.v4.u32 {%0,%1,%2,%3}, [%4];" : "=r"(v.x), "=r"(v.y), "=r"(v.z), "=r"(v.w) : "r"(a) : "memory"); return v; }
__device__ __forceinline__ uint32_t lds32(uint32_t a) { uint32_t v; asm volatile("ld.shared.u32 %0, [%1];" : "=r"(v) : "r"(a) : "memory"); return v; }
__device__ __forceinline__ void sts64(uint32_t a, uint32_t x, uint32_t y) { asm volatile("st.shared.v2.u32 [%0], {%1,%2};" :: "r"(a), "r"(x), "r"(y) : "memory"); }
__device__ __forceinline__ void sts64f(uint32_t a, float x, float y) { asm volatile("st.shared.v2.f32 [%0], {%1,%2};" :: "r"(a), "f"(x), "f"(y) : "memory"); }
__device__ __forceinline__ void sts32(uint32_t a, uint32_t x) { asm volatile("st.shared.u32 [%0], %1;" :: "r"(a), "r"(x) : "memory"); }
__device__ __forceinline__ void mma_z(float* d, uint32_t a0, uint32_t a1, uint32_t a2, uint32_t a3, uint32_t b0, uint32_t b1) {
  asm volatile("mma.sync.aligned.m16n8k16.row.col.f32.bf16.bf16.f32 {%0,%1,%2,%3}, {%4,%5,%6,%7}, {%8,%9}, {%10,%10,%10,%10};"
    : "=f"(d[0]), "=f"(d[1]), "=f"(d[2]), "=f"(d[3]) : "r"(a0), "r"(a1), "r"(a2), "r"(a3), "r"(b0), "r"(b1), "f"(0.f));
}
__device__ __forceinline__ void mma8_z(float* d, uint32_t a0, uint32_t a1, uint32_t b0) {
  asm volatile("mma.sync.aligned.m16n8k8.row.col.f32.bf16.bf16.f32 {%0,%1,%2,%3}, {%4,%5}, {%6}, {%7,%7,%7,%7};"
    : "=f"(d[0]), "=f"(d[1]), "=f"(d[2]), "=f"(d[3]) : "r"(a0), "r"(a1), "r"(b0), "f"(0.f));
}
#define OFF(f) ((uint32_t)offsetof(RSmem, f))
#define BAR_SYNC(id, n) asm volatile("bar.sync %0, %1;" :: "n"(id), "n"(n) : "memory")
#define BAR_ARRIVE(id, n) asm volatile("bar.arrive %0, %1;" :: "n"(id), "n"(n) : "memory")

__device__ __forceinline__ void sts128(uint32_t a, uint32_t x, uint32_t y, uint32_t z, uint32_t w) { asm volatile("st.shared.v4.u32 [%0], {%1,%2,%3,%4};" :: "r"(a), "r"(x), "r"(y), "r"(z), "r"(w) : "memory"); }
template <int K>
__device__ __forceinline__ void kstep(const uint4 (&W)[42], float (&acc)[7][4], uint32_t b0, uint32_t b1, uint4& w6, uint32_t ws) {
#pragma unroll
  for (int t = 0; t < 6; t++) {
    const uint4& w = W[K * 6 + t];
    if (K == 0) mma_z(acc[t], w.x, w.y, w.z, w.w, b0, b1); else mma16816(acc[t], w.x, w.y, w.z, w.w, b0, b1);
  }
  if (K == 0) mma_z(acc[6], w6.x, w6.y, w6.z, w6.w, b0, b1); else mma16816(acc[6], w6.x, w6.y, w6.z, w6.w, b0, b1);
  if (K < 6) w6 = lds128(ws + (K + 1) * 512);
}
__device__ __forceinline__ uint4* acc_ptr(int step, int vec, int lane) { return g_ACC16 + (((step >> 1) * 16 + vec) * 2 + (step & 1)) * 32 + lane; }

__device__ __forceinline__ bool elect1() { uint32_t p; asm volatile("{.reg .pred p; elect.sync _|p, 0xffffffff; selp.u32 %0, 1, 0, p;}" : "=r"(p)); return p; }
__device__ __forceinline__ float4 lds128f(uint32_t a) { float4 v; asm volatile("ld.shared.v4.f32 {%0,%1,%2,%3}, [%4];" : "=f"(v.x), "=f"(v.y), "=f"(v.z), "=f"(v.w) : "r"(a) : "memory"); return v; }
__device__ __forceinline__ float ex2v(float x) { float y; asm volatile("ex2.approx.ftz.f32 %0, %1;" : "=f"(y) : "f"(x)); return y; }
__device__ __forceinline__ uint32_t hadd_bf2(uint32_t a, uint32_t b) { uint32_t d; asm("add.rn.bf16x2 %0, %1, %2;" : "=r"(d) : "r"(a), "r"(b)); return d; }
__device__ __forceinline__ uint32_t amax2(uint32_t m, uint32_t x, uint32_t y) { return __vmaxu2(m, __vmaxu2(x & 0x7fff7fffu, y & 0x7fff7fffu)); }

#define FENCE(n) do { if (__builtin_expect((poll_delay >> (16 + (n))) & 1, 0)) { _Pragma("unroll 1") for (int i_ = poll_delay & 7; i_ > 0; i_--) asm volatile("nanosleep.u32 %0;" :: "n"(n) : "memory"); } } while (0)
#define BAR_SYNC_R(id, n) asm volatile("bar.sync %0, %1;" :: "r"(id), "n"(n) : "memory")
#define BAR_ARRIVE_R(id, n) asm volatile("bar.arrive %0, %1;" :: "r"(id), "n"(n) : "memory")
#define MMW(A, WW, B0, B1, first) do { if (first) mma_z(A, WW.x, WW.y, WW.z, WW.w, B0, B1); else mma16816(A, WW.x, WW.y, WW.z, WW.w, B0, B1); } while (0)
__device__ __forceinline__ void issue_loads(uint32_t sb, int s, int h, int j) {
  const int st = s & (NST - 1), s0 = s;
  const uint32_t bar = sb + OFF(bar_ld) + 8 * st;
  arm_bar(bar, LD_BYTES);
#pragma unroll
  for (int qq = 0; qq < 4; qq++) bulk_g2s(sb + qq * QB + QOFF(kf) + st * 2048, g_KF + ((s * NH + h) * 4 + j) * 512 + qq * 128, 2048, bar);
  bulk_g2s(sb + OFF(vf) + st * 7168, g_VF + ((s * NH + h) * 56 + 14 * j) * 32, 7168, bar);
  bulk_g2s(sb + OFF(xf) + st * 7168, g_XF + (s * 4 + j) * 448, 7168, bar);
  asm volatile("prefetch.global.L2 [%0];" :: "l"(acc_ptr(s0, h, j * 8)));
}
__device__ __forceinline__ int opaque_lane() { return __shfl_sync(0xffffffffu, threadIdx.x & 31, threadIdx.x & 31); }

__global__ void __cluster_dims__(4, 1, 1) __launch_bounds__(384, 1) r_kernel(const bf16* mem0, int poll_delay) {
  extern __shared__ __align__(128) unsigned char smem_raw[];
  RSmem& sm = *reinterpret_cast<RSmem*>(smem_raw);
  const int h = blockIdx.x >> 2, j = blockIdx.x & 3;
  const int w = __shfl_sync(0xffffffffu, threadIdx.x >> 5, 0), q = w & 3, role = w >> 2;
  const uint32_t sb = smem_u32(smem_raw);
  const uint32_t bar_ld = sb + OFF(bar_ld), bar_sx = sb + OFF(bar_sx), bar_sm = sb + OFF(bar_sm);
  if (threadIdx.x == 0) {
    for (int i = 0; i < NST; i++) asm volatile("mbarrier.init.shared::cta.b64 [%0], 1;" :: "r"(bar_ld + 8 * i));
    asm volatile("mbarrier.init.shared::cta.b64 [%0], 1;" :: "r"(bar_sx));
    asm volatile("mbarrier.init.shared::cta.b64 [%0], 1;" :: "r"(bar_sm));
    asm volatile("fence.mbarrier_init.release.cluster;" ::: "memory");
    arm_bar(bar_sx, 1024); arm_bar(bar_sm, 1024);
    for (int s = 0; s < NST; s++) issue_loads(sb, s, h, j);
    sm.sinv[0] = g_inv0;
  }
  if (threadIdx.x < NSEG) sm.xmax[threadIdx.x] = g_xmax[threadIdx.x];
  if (role < 2) {
    const int lane = threadIdx.x & 31;
    const uint4* wf = g_WF + (((role * NH + h) * 28 + 7 * j) * 28 + 7 * q) * 32 + lane;
#pragma unroll
    for (int e = 0; e < 7; e++) (role ? sm.qb[q].wB : sm.qb[q].wA)[e][lane] = wf[e * 28 * 32];
  }
  asm volatile("barrier.cluster.arrive.release.aligned;\nbarrier.cluster.wait.acquire.aligned;" ::: "memory");
  const float LOG2E = 1.4426950408889634f;

  if (role == 0) {
    asm volatile("setmaxnreg.inc.sync.aligned.u32 224;");
    const int lane = opaque_lane();
    const uint32_t l16 = sb + lane * 16;
    uint4 W[42];
    {
      const uint4* wf = g_WF + ((h * 28 + 7 * j) * 28 + 7 * q) * 32 + lane;
#pragma unroll
      for (int k = 1; k < 7; k++)
#pragma unroll
        for (int t = 0; t < 7; t++) W[(k - 1) * 7 + t] = wf[(t * 28 + k) * 32];
    }
    const uint32_t lq = l16 + q * QB, mj = l16 + j * QB;
#define ws (lq + QOFF(wA))
#define mq lq
    const uint32_t dst_sm = mapa(l16 + OFF(sm) + (j >> 1) * 512 + (j & 1) * 8, q), dst_bar = mapa(bar_sm, q);
    const uint4* p = acc_ptr(0, q * 4, lane);
#define TM(t, k) do { if ((k) == 0) mma_z(acc[t], f[t].x, f[t].y, f[t].z, f[t].w, b[0], b[1]); else { const uint4& w_ = W[((k) - 1) * 7 + (t)]; mma16816(acc[t], w_.x, w_.y, w_.z, w_.w, b[2 * (k)], b[2 * (k) + 1]); } } while (0)
#define T3(k) do { TM(0, k); TM(1, k); TM(2, k); } while (0)
#define T4(k) do { TM(3, k); TM(4, k); TM(5, k); TM(6, k); } while (0)
#define TR(t) do { kl[t] = movm(pack_bf16(acc[t][0], acc[t][1])); kh[t] = movm(pack_bf16(acc[t][2], acc[t][3])); } while (0)
    wait_bar1(bar_ld, 0);
#pragma unroll 1
    for (int s = 0; s < NSEG; s++) {
      STAMP(0);
      uint4 v0 = ld_relaxed_u4(p), v1 = ld_relaxed_u4(p + 64), v2 = ld_relaxed_u4(p + 128), v3 = ld_relaxed_u4(p + 192);
      const uint32_t kb = lq + QOFF(kf) + (s & (NST - 1)) * 2048;
      uint4 k0 = lds128(kb), k1 = lds128(kb + 512), k2 = lds128(kb + 1024); uint2 k3 = lds64(kb + 1536);
      uint4 f[7];
      f[0] = lds128v(ws); f[1] = lds128v(ws + 512); f[2] = lds128v(ws + 1024);
      if (!__all_sync(0xffffffffu, __byte_perm(v0.w, v1.w, 0x7632) == 0x4C004C00u && __byte_perm(v2.w, v3.w, 0x7632) == 0x4C004C00u)) {
#pragma unroll 1
        for (int n = 0; n < SPIN_LIMIT; n++) {
          v0 = ld_relaxed_u4(p); v1 = ld_relaxed_u4(p + 64); v2 = ld_relaxed_u4(p + 128); v3 = ld_relaxed_u4(p + 192);
          if (__all_sync(0xffffffffu, __byte_perm(v0.w, v1.w, 0x7632) == 0x4C004C00u && __byte_perm(v2.w, v3.w, 0x7632) == 0x4C004C00u)) break;
        }
      }
      STAMP(1);
      uint32_t b[14];
      float dl[4], dh[4], el[4], eh[4];
      b[0] = h2_to_bf2(v0.x); b[1] = h2_to_bf2(v0.y); b[2] = h2_to_bf2(v0.z); b[3] = h2_to_bf2(v1.x);
      mma_z(dl, b[0], b[1], b[2], b[3], k0.x, k0.y); mma_z(dh, b[0], b[1], b[2], b[3], k0.z, k0.w);
      b[4] = h2_to_bf2(v1.y); b[5] = h2_to_bf2(v1.z);
      b[6] = h2_to_bf2(__byte_perm(v0.w, v1.w, 0x5410)); b[7] = h2_to_bf2(__byte_perm(v2.w, v3.w, 0x5410));
      mma_z(el, b[4], b[5], b[6], b[7], k1.x, k1.y); mma_z(eh, b[4], b[5], b[6], b[7], k1.z, k1.w);
      b[8] = h2_to_bf2(v2.x); b[9] = h2_to_bf2(v2.y); b[10] = h2_to_bf2(v2.z); b[11] = h2_to_bf2(v3.x);
      mma16816(dl, b[8], b[9], b[10], b[11], k2.x, k2.y); mma16816(dh, b[8], b[9], b[10], b[11], k2.z, k2.w);
      b[12] = h2_to_bf2(v3.y); b[13] = h2_to_bf2(v3.z);
      mma1688(el, b[12], b[13], k3.x); mma1688(eh, b[12], b[13], k3.y);
      float acc[7][4];
      T3(0); T3(1);
      sts64f(lq + QOFF(red) + 8, (dl[0] + dh[2]) + (el[0] + eh[2]), (dl[1] + dh[3]) + (el[1] + eh[3]));
      BAR_ARRIVE(14, 256);
      f[3] = lds128(ws + 1536); f[4] = lds128(ws + 2048); f[5] = lds128(ws + 2560); f[6] = lds128(ws + 3072);
      sts128(mq, b[0], b[1], b[2], b[3]); sts128(mq + 512, b[4], b[5], b[6], b[7]); sts128(mq + 1024, b[8], b[9], b[10], b[11]); sts64(mq + 1536, b[12], b[13]);
      BAR_ARRIVE_R(5 + q, 64);
      T3(2);
      FENCE(2);
      T3(3); T4(0); T3(4); T4(1); T3(5); T4(2); T3(6); T4(3);
      FENCE(4);
      BAR_SYNC(1, 128);
      uint4 a0 = lds128(mj), a1 = lds128(mj + 512), a2 = lds128(mj + 1024); uint2 a3 = lds64(mj + 1536);
      uint32_t kl[7], kh[7];
      T4(4); TR(0); TR(1); T4(5); TR(2); T4(6);
      mma_z(dl, a0.x, a0.y, a0.z, a0.w, kl[0], kl[1]); mma_z(dh, a0.x, a0.y, a0.z, a0.w, kh[0], kh[1]);
      BAR_ARRIVE_R(10 + q, 64);
      FENCE(5);
      STAMP(3);
      TR(3); TR(4); TR(5); TR(6);
      mma_z(el, a1.x, a1.y, a1.z, a1.w, kl[2], kl[3]); mma_z(eh, a1.x, a1.y, a1.z, a1.w, kh[2], kh[3]);
      mma16816(dl, a2.x, a2.y, a2.z, a2.w, kl[4], kl[5]); mma16816(dh, a2.x, a2.y, a2.z, a2.w, kh[4], kh[5]);
      float gl[4], gh[4];
      mma8_z(gl, a3.x, a3.y, kl[6]); mma8_z(gh, a3.x, a3.y, kh[6]);
      dl[0] += el[0]; dh[2] += eh[2]; dl[1] += el[1]; dh[3] += eh[3]; el[0] = gl[0]; el[1] = gl[1]; eh[2] = gh[2]; eh[3] = gh[3];
      sts64f(lq + QOFF(red), (dl[0] + dh[2]) + (el[0] + eh[2]), (dl[1] + dh[3]) + (el[1] + eh[3]));
      BAR_SYNC(2, 128);
      {
        float2 t0 = lds64f(l16 + QOFF(red)), t1 = lds64f(l16 + QOFF(red) + QB), t2 = lds64f(l16 + QOFF(red) + 2 * QB), t3 = lds64f(l16 + QOFF(red) + 3 * QB);
        st_async2(dst_sm, (t0.x + t1.x) + (t2.x + t3.x), (t0.y + t1.y) + (t2.y + t3.y), dst_bar);
      }
      STAMP(4);
      { const uint32_t kqa = lq + QOFF(kq) + (s & 1) * 2048;
      sts128(kqa, kl[0], kl[1], kh[0], kh[1]); sts128(kqa + 512, kl[2], kl[3], kh[2], kh[3]);
      sts128(kqa + 1024, kl[4], kl[5], kh[4], kh[5]); sts64(kqa + 1536, kl[6], kh[6]); }
      p += (s & 1) ? (1024 - 32) : 32;
      if (q == 1 && s >= 2 && s + 2 < NSEG) { if (elect1()) issue_loads(sb, s + 2, h, j); __syncwarp(); }
      if (s + 1 < NSEG) wait_bar1(bar_ld + 8 * ((s + 1) & (NST - 1)), ((s + 1) / NST) & 1);
      BAR_SYNC(4, 384);
      unsigned tred = clk();
      if (q == 0) { if (elect1()) { arm_bar(bar_sx, 1024); arm_bar(bar_sm, 1024); } __syncwarp(); }
      while (clk() - tred < (unsigned)(poll_delay & 0xffff)) {}
    }
  } else if (role == 1) {
    asm volatile("setmaxnreg.inc.sync.aligned.u32 208;");
    const int lane = opaque_lane();
    const uint32_t l16 = sb + lane * 16;
    uint4 W[42];
    {
      const uint4* wf = g_WF + (((NH + h) * 28 + 7 * j) * 28 + 7 * q) * 32 + lane;
#pragma unroll
      for (int k = 1; k < 7; k++)
#pragma unroll
        for (int t = 0; t < 7; t++) W[(k - 1) * 7 + t] = wf[(t * 28 + k) * 32];
    }
#undef ws
#define ws (lq + QOFF(wB))
    const uint32_t lq = l16 + q * QB;
#define uq (lq + QOFF(uQ))
#pragma unroll 1
    for (int s = 0; s < NSEG; s++) {
      const int st = s & (NST - 1);
      uint4 f[7];
#pragma unroll
      for (int t = 0; t < 7; t++) f[t] = lds128(ws + t * 512);
      BAR_SYNC_R(10 + q, 64);
      STAMP(10);
      float acc[7][4];
      uint32_t b[14];
#define LB(p) do { if ((p) < 3) { uint4 t_ = lds128(mq + (p) * 512); b[4 * (p)] = t_.x; b[4 * (p) + 1] = t_.y; b[4 * (p) + 2] = t_.z; b[4 * (p) + 3] = t_.w; } else { uint2 t_ = lds64(mq + 1536); b[12] = t_.x; b[13] = t_.y; } } while (0)
      LB(0); LB(1); T3(0); T3(1); LB(2); T3(2); T3(3); LB(3); T3(4); T3(5); T3(6);
      LB(0);
      FENCE(8);
#define UP(nt) pack_bf16(acc[(nt) >> 1][((nt) & 1) * 2], acc[(nt) >> 1][((nt) & 1) * 2 + 1])
      LB(1); T4(0); T4(1); LB(2); T4(2); T4(3); LB(3); T4(4); T4(5); T4(6);
      { uint32_t u6 = UP(6), u7 = UP(7);
        sts128(uq, UP(0), UP(1), UP(2), u6); sts128(uq + 512, UP(3), UP(4), UP(5), u6);
        sts128(uq + 1024, UP(8), UP(9), UP(10), u7); sts128(uq + 1536, UP(11), UP(12), UP(13), u7); }
      BAR_ARRIVE(3, 256);
      STAMP(11);
      const float inv = __uint_as_float(lds32(sb + OFF(sinv) + (s & 1) * 4));
      BAR_SYNC(4, 384);
      {
        const int nt0 = q < 2 ? q * 3 : 8 + (q - 2) * 3, nts = 6 + (q >> 1);
        uint32_t ub = l16 + QOFF(uQ) + q * 512; asm volatile("" : "+r"(ub));
        uint4 u0 = lds128(ub), u1 = lds128(ub + QB), u2 = lds128(ub + 2 * QB), u3 = lds128(ub + 3 * QB);
        auto us = [&](uint32_t a, uint32_t b, uint32_t c, uint32_t d) { return pack_bf16(((bf_lo(a) + bf_lo(b)) + (bf_lo(c) + bf_lo(d))) * inv, ((bf_hi(a) + bf_hi(b)) + (bf_hi(c) + bf_hi(d))) * inv); };
        uint32_t* uf = (uint32_t*)((char*)(g_UF + ((s * NH + h) * 56 + 14 * j) * 32) + ((l16 - sb) >> 2));
        { uf[(nt0 + 0) * 32] = us(u0.x, u1.x, u2.x, u3.x); uf[(nt0 + 1) * 32] = us(u0.y, u1.y, u2.y, u3.y); uf[(nt0 + 2) * 32] = us(u0.z, u1.z, u2.z, u3.z);
        if ((q & 1) == 0) uf[nts * 32] = us(u0.w, u1.w, u2.w, u3.w); }
      }
      {
        const uint32_t xb = l16 + OFF(xf) + st * 7168;
        const uint32_t kqa = lq + QOFF(kq) + (s & 1) * 2048;
        uint4 k0 = lds128(kqa), k1 = lds128(kqa + 512), k2 = lds128(kqa + 1024); uint2 k3 = lds64(kqa + 1536);
        const uint32_t kk[14] = {k0.x, k0.y, k0.z, k0.w, k1.x, k1.y, k1.z, k1.w, k2.x, k2.y, k2.z, k2.w, k3.x, k3.y};
        float y[2][4];
#pragma unroll
        for (int f = 0; f < 7; f++)
#pragma unroll
          for (int m = 0; m < 2; m++) {
            uint4 xa = lds128(xb + (f * 2 + m) * 512);
            MMW(y[m], xa, kk[2 * f], kk[2 * f + 1], f == 0);
          }
        sts128(lq + QOFF(xred), __float_as_uint(y[0][0]), __float_as_uint(y[0][1]), __float_as_uint(y[0][2]), __float_as_uint(y[0][3]));
        sts128(lq + QOFF(xred) + 512, __float_as_uint(y[1][0]), __float_as_uint(y[1][1]), __float_as_uint(y[1][2]), __float_as_uint(y[1][3]));
        BAR_SYNC(15, 128);
        if (q < 2) {
          uint32_t xr = l16 + QOFF(xred) + q * 512; asm volatile("" : "+r"(xr));
          float4 t0 = lds128f(xr), t1 = lds128f(xr + QB), t2 = lds128f(xr + 2 * QB), t3 = lds128f(xr + 3 * QB);
          *(float4*)((char*)(g_SXM + ((((s * NH + h) * 4 + j) * 2 + q) * 32)) + (l16 - sb)) = make_float4(((t0.x + t1.x) + (t2.x + t3.x)) * inv, ((t0.y + t1.y) + (t2.y + t3.y)) * inv, ((t0.z + t1.z) + (t2.z + t3.z)) * inv, ((t0.w + t1.w) + (t2.w + t3.w)) * inv);
        }
      }
    }
  } else {
    asm volatile("setmaxnreg.dec.sync.aligned.u32 72;");
    const int lane = opaque_lane();
    const uint32_t l16 = sb + lane * 16;
    const int nt0 = q < 2 ? q * 3 : 8 + (q - 2) * 3, nts = 6 + (q >> 1);
    const float bmax = g_bmax;
    int se = (int)(127 - (__float_as_uint(g_inv0) >> 23));
    uint4* redp = acc_ptr(1, j * 4 + q, lane);
    const uint32_t dst_sx = mapa(l16 + OFF(sx) + (j >> 1) * 512 + (j & 1) * 8, q), dst_bar = mapa(bar_sx, q);
#pragma unroll 1
    for (int s = 0; s < NSEG; s++) {
      const int st = s & (NST - 1);
      float ya[4], yb[4], z[4];
      float mx;
      int nse;
      const float inv = __uint_as_float((uint32_t)(127 - se) << 23);
      const float c1 = LOG2E * inv;
      {
        const uint32_t vb = l16 + OFF(vf) + st * 7168;
        wait_bar1(bar_ld + 8 * st, (s / NST) & 1);
        uint4 v0 = lds128(vb + nt0 * 512), v1 = lds128(vb + nt0 * 512 + 512), v2 = lds128(vb + nt0 * 512 + 1024), v3 = lds128(vb + nts * 512);
        BAR_SYNC(14, 256);
        STAMP(2);
        {
          float2 t0 = lds64f(l16 + QOFF(red) + 8), t1 = lds64f(l16 + QOFF(red) + 8 + QB), t2 = lds64f(l16 + QOFF(red) + 8 + 2 * QB), t3 = lds64f(l16 + QOFF(red) + 8 + 3 * QB);
          st_async2(dst_sx, (t0.x + t1.x) + (t2.x + t3.x), (t0.y + t1.y) + (t2.y + t3.y), dst_bar);
        }
        STAMP(9);
        BAR_SYNC_R(5 + q, 64);
        {
          const uint32_t mq_ = l16 + q * QB;
          uint4 p0 = lds128(mq_), p1 = lds128(mq_ + 512), p2 = lds128(mq_ + 1024); uint2 p3 = lds64(mq_ + 1536);
          uint32_t m = amax2(amax2(amax2(amax2(0u, p0.x, p0.y), p0.z, p0.w), p1.x, p1.y), p1.z, p1.w);
          m = amax2(amax2(amax2(m, p2.x, p2.y), p2.z, p2.w), p3.x, p3.y);
          m = max(m & 0xffffu, m >> 16);
          m = __reduce_max_sync(0xffffffffu, m);
          sts32(sb + OFF(smax) + q * 4, m);
        }
        BAR_SYNC(9, 128);
        {
          uint4 m4 = lds128(sb + OFF(smax));
          uint32_t mb = max(max(m4.x, m4.y), max(m4.z, m4.w));
          float mh = fmaxf(__uint_as_float(mb << 16) * inv, __uint_as_float(lds32(sb + OFF(xmax) + s * 4)));
          float bound = mh * bmax;
          int e = (int)(__float_as_uint(bound) >> 23) - 127 + 10;
          nse = min(max(15 - e, -60), 60);
        }
        const uint32_t one_n = (uint32_t)(127 - nse) * 0x00800080u;
        wait_bar1(bar_sx, s & 1);
        STAMP(12);
        float4 x0 = lds128f(l16 + OFF(sx)), x1 = lds128f(l16 + OFF(sx) + 512);
        float sx[8] = {x0.x, x0.y, x0.z, x0.w, x1.x, x1.y, x1.z, x1.w};
        mx = fmaxf(fmaxf(fmaxf(sx[0], sx[1]), fmaxf(sx[2], sx[3])), fmaxf(fmaxf(sx[4], sx[5]), fmaxf(sx[6], sx[7])));
        mx = fmaxf(mx, __shfl_xor_sync(0xffffffffu, mx, 1)); mx = fmaxf(mx, __shfl_xor_sync(0xffffffffu, mx, 2));
        mx *= c1;
#pragma unroll
        for (int i = 0; i < 8; i++) sx[i] = ex2(fmaf(sx[i], c1, -mx));
        uint32_t p0 = pack_bf16(sx[0], sx[1]), p1 = pack_bf16(sx[2], sx[3]), p2 = pack_bf16(sx[4], sx[5]), p3 = pack_bf16(sx[6], sx[7]);
        float o[4], r[4];
        mma_z(o, p0, p2, p1, p3, v0.x, v0.y); mma_z(r, p0, p2, p1, p3, v0.z, v0.w); ya[0] = o[0] + r[2]; ya[1] = o[1] + r[3];
        mma_z(o, p0, p2, p1, p3, v1.x, v1.y); mma_z(r, p0, p2, p1, p3, v1.z, v1.w); ya[2] = o[0] + r[2]; ya[3] = o[1] + r[3];
        mma_z(o, p0, p2, p1, p3, v2.x, v2.y); mma_z(r, p0, p2, p1, p3, v2.z, v2.w); yb[0] = o[0] + r[2]; yb[1] = o[1] + r[3];
        mma_z(o, p0, p2, p1, p3, v3.x, v3.y); mma_z(r, p0, p2, p1, p3, v3.z, v3.w); yb[2] = o[0] + r[2]; yb[3] = o[1] + r[3];
        mma_z(z, p0, p2, p1, p3, one_n, one_n); z[0] += z[2];
      }
      asm volatile("" : "+f"(ya[0]), "+f"(ya[1]), "+f"(ya[2]), "+f"(ya[3]), "+f"(yb[0]), "+f"(yb[1]), "+f"(yb[2]), "+f"(yb[3]), "+f"(z[0]));
      STAMP(5);
      FENCE(9);
      BAR_SYNC(3, 256);
      uint32_t u[4];
      {
        const uint32_t ub = l16 + QOFF(uQ) + q * 512;
        uint4 u0 = lds128(ub), u1 = lds128(ub + QB), u2 = lds128(ub + 2 * QB), u3 = lds128(ub + 3 * QB);
        u[0] = hadd_bf2(hadd_bf2(u0.x, u1.x), hadd_bf2(u2.x, u3.x)); u[1] = hadd_bf2(hadd_bf2(u0.y, u1.y), hadd_bf2(u2.y, u3.y));
        u[2] = hadd_bf2(hadd_bf2(u0.z, u1.z), hadd_bf2(u2.z, u3.z)); u[3] = hadd_bf2(hadd_bf2(u0.w, u1.w), hadd_bf2(u2.w, u3.w));
      }
      const uint32_t zb = (uint32_t)(127 + se - nse) * 0x00800080u;
      const float c2 = c1 * inv;
      float off = -mx - (float)se;
      const float lim = 32.f - (float)se;
      STAMP(6);
      wait_bar1(bar_sm, s & 1);
      STAMP(7);
      {
        float4 t0 = lds128f(l16 + OFF(sm)), t1 = lds128f(l16 + OFF(sm) + 512);
        const float r0 = (t0.x + t0.z) + (t1.x + t1.z), r1 = (t0.y + t0.w) + (t1.y + t1.w);
        float a0 = fmaf(r0, c2, off), a1 = fmaf(r1, c2, off);
        uint32_t pm = pack_bf16(ex2v(a0), ex2v(a1));
        if (__any_sync(0xffffffffu, !(fmaxf(a0, a1) <= lim))) {
          float m = fmaxf(fmaxf(r0, r1) * c2, mx);
          m = fmaxf(m, __shfl_xor_sync(0xffffffffu, m, 1)); m = fmaxf(m, __shfl_xor_sync(0xffffffffu, m, 2));
          const float al = ex2(mx - m);
#pragma unroll
          for (int i = 0; i < 4; i++) { ya[i] *= al; yb[i] *= al; }
          z[0] *= al;
          off = -m - (float)se;
          pm = pack_bf16(ex2(fmaf(r0, c2, off)), ex2(fmaf(r1, c2, off)));
        }
        mma16816(z, pm, 0u, 0u, pm, zb, zb);
        mma16816(ya, pm, 0u, 0u, pm, u[0], u[1]); mma16816(yb, pm, 0u, 0u, pm, u[2], u[3]);
        float iz; asm("rcp.approx.ftz.f32 %0, %1;" : "=f"(iz) : "f"(z[0]));
        red_h8(redp, pack_f16(ya[0] * iz, ya[1] * iz), pack_f16(ya[2] * iz, ya[3] * iz), pack_f16(yb[0] * iz, yb[1] * iz), pack_f16(((q & 1) ? yb[3] : yb[2]) * iz, 1.f));
      }
      BAR_ARRIVE(4, 384);
      STAMP(8);
      if (q == 0) sts32(sb + OFF(sinv) + ((s + 1) & 1) * 4, (uint32_t)(127 - nse) << 23);
      redp += (s & 1) ? 32 : (1024 - 32);
      se = nse;
    }
  }
  asm volatile("barrier.cluster.arrive.release.aligned;\nbarrier.cluster.wait.acquire.aligned;" ::: "memory");
}

__global__ void n_xf(const bf16* x) {
  int i = blockIdx.x * blockDim.x + threadIdx.x;
  if (i >= NSEG * 4 * 14 * 32) return;
  int lane = i & 31, r = i >> 5, m = r & 1; r >>= 1; int f = r % 7; r /= 7; int j = r & 3, seg = r >> 2;
  int c0 = f == 6 ? 96 : (f & ~1) * 16 + (f & 1) * 8, c1 = f == 6 ? 104 : (f | 1) * 16 + (f & 1) * 8;
  const bf16* r0 = x + (seg * 32 + m * 16 + (lane >> 2)) * DM + j * 112 + (lane & 3) * 2;
  const bf16* r1 = r0 + 8 * DM;
  g_XF[i] = make_uint4(*(const uint32_t*)(r0 + c0), *(const uint32_t*)(r1 + c0), *(const uint32_t*)(r0 + c1), *(const uint32_t*)(r1 + c1));
}

__global__ void n_seed(const bf16* mem0) {
  __shared__ unsigned smx;
  if (threadIdx.x == 0) smx = 0;
  __syncthreads();
  float m = 0.f;
  for (int i = threadIdx.x; i < 8 * DM; i += 512) m = fmaxf(m, fabsf(b2f(mem0[i])));
  atomicMax(&smx, __float_as_uint(m));
  __syncthreads();
  int e = (int)(smx >> 23) - 127 + 1;
  int se = min(max(15 - e, -60), 60);
  float sc = __uint_as_float((uint32_t)(127 + se) << 23);
  if (threadIdx.x == 0) g_inv0 = __uint_as_float((uint32_t)(127 - se) << 23);
  int vec = threadIdx.x >> 5, lane = threadIdx.x & 31, j = vec >> 2, q = vec & 3;
  int nt0 = q < 2 ? q * 3 : 8 + (q - 2) * 3, nts = 6 + (q >> 1);
  const bf16* r = mem0 + (lane >> 2) * DM + j * 112 + (lane & 3) * 2;
  auto val = [&](int nt, int e2) { return b2f(r[nt * 8 + e2]) * sc; };
  *acc_ptr(0, vec, lane) = make_uint4(pack_f16(val(nt0, 0), val(nt0, 1)), pack_f16(val(nt0 + 1, 0), val(nt0 + 1, 1)), pack_f16(val(nt0 + 2, 0), val(nt0 + 2, 1)), pack_f16(val(nts, q & 1), 16.f));
}

__global__ void n_stats(const bf16* x) {
  if (blockIdx.x < 64) {
    float m = 0.f;
    for (int i = threadIdx.x; i < 32 * DM; i += 256) m = fmaxf(m, fabsf(b2f(x[blockIdx.x * 32 * DM + i])));
    atomicMax((unsigned*)&g_xmax[blockIdx.x], __float_as_uint(m));
  } else {
    int r = (blockIdx.x - 64) * 256 + threadIdx.x;
    if (r < NH * DM) { float a = 0.f; for (int k = 0; k < DM; k++) { float v = wf_elem(1, r / DM, r % DM, k); a += v * v; } atomicMax((unsigned*)&g_bmax, __float_as_uint(sqrtf(a))); }
  }
}

int g_poll_delay = POLL_DELAY;
extern "C" void kernel_launch(void* const* d_in, const int* in_sizes, int n_in, void* d_out, int out_size) {
  const bf16* x = (const bf16*)d_in[0];
  const bf16* wqkv = (const bf16*)d_in[1];
  const bf16* wphi = (const bf16*)d_in[2];
  const bf16* wo_a = (const bf16*)d_in[3];
  const bf16* mem0 = (const bf16*)d_in[5];
  const bf16* Wq = (const bf16*)d_in[6];
  const bf16* Wk = (const bf16*)d_in[7];
  const bf16* Wv = (const bf16*)d_in[8];
  const bf16* Wo = (const bf16*)d_in[9];
  const bf16* gate_w = (const bf16*)d_in[11];
  bf16* out = (bf16*)d_out;
  cudaFuncSetAttribute(r_kernel, cudaFuncAttributeMaxDynamicSharedMemorySize, (int)sizeof(RSmem));
  n_zero<<<(NSEG * 40 * 32 + 255) / 256, 256>>>();
  n_prep<<<(2 * NH * 28 * 28 * 32 + 255) / 256, 256>>>(Wq, Wk, Wv, Wo);
  n_stats<<<64 + 28, 256>>>(x);
  n_seed<<<1, 512>>>(mem0);
  n_xf<<<NSEG * 4 * 14 * 32 / 256, 256>>>(x);
  n_xgemm<<<2 * NH * 28 * NSEG * 32 / 256, 256>>>(x);
  r_kernel<<<64, 384, sizeof(RSmem)>>>(mem0, g_poll_delay);
  n_qkv<<<(S_LEN * 1344 + 255) / 256, 256>>>(x, wqkv);
  n_phi<<<(S_LEN * 2 * NH + 255) / 256, 256>>>(wphi);
  n_kv<<<(32 * NH * 56 * 29 + 255) / 256, 256>>>();
  n_oa<<<(S_LEN * DM + 255) / 256, 256>>>();
  n_x3<<<NSEG, 512>>>(x, wo_a, gate_w, out);
}
```

```cpp
#include <cuda_runtime.h>
#include <cuda_bf16.h>
#include <stdint.h>
#include <stddef.h>
#include <cuda.h>
#include <cudaTypedefs.h>

typedef __nv_bfloat16 bf16;
#define S_LEN 2048
#define DM 448
#define NH 16
#define NSEG 64
#define SPIN_LIMIT (1 << 18)

__device__ uint4 g_WF[2 * NH * 28 * 28 * 32];
__device__ __align__(128) uint32_t g_WS[2 * NH * 7 * 28 * 512];
__device__ uint2 g_KF[NSEG * NH * 4 * 4 * 7 * 32];
__device__ unsigned g_ready[NSEG * NH];
__device__ float g_wmax[128];
__device__ float g_gate[S_LEN];
__device__ uint4 g_AF[NSEG * 28 * 2 * 32];
__device__ unsigned g_rdone[NSEG];
__device__ uint4 g_VF[NSEG * NH * 56 * 32];
__device__ float4 g_SXM[NSEG * NH * 4 * 4 * 32];
__device__ uint4 g_XF[NSEG * 4 * 14 * 32];
__device__ uint32_t g_UF[NSEG * NH * 56 * 32];
__device__ __align__(2097152) uint4 g_ACC16[131072];
__device__ __align__(8) unsigned g_reg[2];
__device__ float g_xmax[NSEG];
__device__ float g_bmax;
__device__ float g_inv0;
__device__ float g_kv[NH * 32 * 64];
__device__ uint4 g_PQ[128 * NH * 4 * 32];
__device__ unsigned g_a1done[1], g_a2done[16], g_job[1];
__device__ unsigned g_go[1];
__device__ int g_err;
#define TLS(i)
__device__ unsigned g_ts[64 * 64 * 64];

__device__ __forceinline__ uint32_t pack_bf16(float lo, float hi) {
  uint32_t r; asm("cvt.rn.bf16x2.f32 %0, %1, %2;" : "=r"(r) : "f"(hi), "f"(lo)); return r;
}
__device__ __forceinline__ float bf_lo(uint32_t v) { return __uint_as_float(v << 16); }
__device__ __forceinline__ float bf_hi(uint32_t v) { return __uint_as_float(v & 0xffff0000u); }
__device__ __forceinline__ float b2f(bf16 v) { return __bfloat162float(v); }

__device__ __forceinline__ void mma16816(float* d, uint32_t a0, uint32_t a1, uint32_t a2, uint32_t a3, uint32_t b0, uint32_t b1) {
  asm volatile("mma.sync.aligned.m16n8k16.row.col.f32.bf16.bf16.f32 {%0,%1,%2,%3}, {%4,%5,%6,%7}, {%8,%9}, {%0,%1,%2,%3};"
    : "+f"(d[0]), "+f"(d[1]), "+f"(d[2]), "+f"(d[3]) : "r"(a0), "r"(a1), "r"(a2), "r"(a3), "r"(b0), "r"(b1));
}
__device__ __forceinline__ void mma1688(float* d, uint32_t a0, uint32_t a1, uint32_t b0) {
  asm volatile("mma.sync.aligned.m16n8k8.row.col.f32.bf16.bf16.f32 {%0,%1,%2,%3}, {%4,%5}, {%6}, {%0,%1,%2,%3};"
    : "+f"(d[0]), "+f"(d[1]), "+f"(d[2]), "+f"(d[3]) : "r"(a0), "r"(a1), "r"(b0));
}
__device__ __forceinline__ uint32_t movm(uint32_t a) { uint32_t d; asm volatile("movmatrix.sync.aligned.m8n8.trans.b16 %0, %1;" : "=r"(d) : "r"(a)); return d; }

__device__ __forceinline__ uint32_t smem_u32(const void* p) { return (uint32_t)__cvta_generic_to_shared(p); }
__device__ __forceinline__ uint32_t mapa(uint32_t a, uint32_t r) { uint32_t o; asm volatile("mapa.shared::cluster.u32 %0, %1, %2;" : "=r"(o) : "r"(a), "r"(r)); return o; }
__device__ __forceinline__ bool try_wait(uint32_t bar, uint32_t parity) {
  uint32_t ok; asm volatile("{\n.reg .pred p;\nmbarrier.try_wait.parity.shared::cta.b64 p, [%1], %2;\nselp.u32 %0, 1, 0, p;\n}" : "=r"(ok) : "r"(bar), "r"(parity) : "memory"); return ok; }
__device__ __forceinline__ void wait_bar(uint32_t bar, uint32_t parity) {
  int n = 0; while (!try_wait(bar, parity)) { if (++n > SPIN_LIMIT) { g_err = 1; break; } } }
__device__ __forceinline__ void arm_bar(uint32_t bar, uint32_t bytes) { asm volatile("mbarrier.arrive.expect_tx.shared::cta.b64 _, [%0], %1;" :: "r"(bar), "r"(bytes) : "memory"); }
__device__ __forceinline__ float4 ld_relaxed4(const void* p) { float4 v; asm volatile("ld.relaxed.gpu.global.v4.f32 {%0,%1,%2,%3}, [%4];" : "=f"(v.x), "=f"(v.y), "=f"(v.z), "=f"(v.w) : "l"(p) : "memory"); return v; }
__device__ __forceinline__ void red4(void* p, float a, float b, float c, float d) { asm volatile("red.relaxed.gpu.global.add.v4.f32 [%0], {%1,%2,%3,%4};" :: "l"(p), "f"(a), "f"(b), "f"(c), "f"(d) : "memory"); }
__device__ __forceinline__ void st_async2(uint32_t dst, float a, float b, uint32_t bar) { asm volatile("st.async.shared::cluster.mbarrier::complete_tx::bytes.v2.f32 [%0], {%1,%2}, [%3];" :: "r"(dst), "f"(a), "f"(b), "r"(bar) : "memory"); }
__device__ __forceinline__ void bulk_g2s(uint32_t dst, const void* src, uint32_t bytes, uint32_t bar) {
  asm volatile("cp.async.bulk.shared::cluster.global.mbarrier::complete_tx::bytes [%0], [%1], %2, [%3];" :: "r"(dst), "l"(src), "r"(bytes), "r"(bar) : "memory"); }
__device__ __forceinline__ unsigned clk() { unsigned c; asm volatile("mov.u32 %0, %%clock;" : "=r"(c) :: "memory"); return c; }
__device__ __forceinline__ float ex2(float x) { float y; asm("ex2.approx.ftz.f32 %0, %1;" : "=f"(y) : "f"(x)); return y; }

#define NST 4
struct QBlk {
  uint4 memF[4][32];
  uint4 wA[14][32], wB[14][32];
  float4 xred[2][32], xred2[2][32];
  uint4 kq[4][32];
  uint4 uQ[4][32];
};
#define R_LAG 0
#define QB ((uint32_t)sizeof(QBlk))
#define QOFF(f) ((uint32_t)offsetof(QBlk, f))
struct RSmem {
  QBlk qb[4];
  uint4 vf[NST][14][32];
  uint2 kf[NST][28][32];
  uint4 xf[2][56][32];
  uint4 pub[2][240];
  float4 red[2][32], red2[2][32];
  float4 sx[2][32];
  float4 sm[2][32];
  uint32_t smax[8];
  float xmax[NSEG];
  int xexp[NSEG];
  float sinv[4];
  unsigned long long bar_ld[NST], bar_sx, bar_sm, bar_xf[2];
};
#define LD_BYTES (7168 * 2)
#define POLL_DELAY 260
#define STAMP(i)
__device__ __forceinline__ void wait_slow(uint32_t bar, uint32_t parity) {
#pragma unroll 1
  for (int n = 0; n < SPIN_LIMIT; n++) if (try_wait(bar, parity)) return;
  g_err = 1;
}
__device__ __forceinline__ void spin_bar(uint32_t bar, uint32_t parity) {
#pragma unroll 1
  for (int n = 0; n < (SPIN_LIMIT << 4); n++) {
    uint32_t ok; asm volatile("{\n.reg .pred p;\nmbarrier.test_wait.parity.shared::cta.b64 p, [%1], %2;\nselp.u32 %0, 1, 0, p;\n}" : "=r"(ok) : "r"(bar), "r"(parity) : "memory");
    if (ok) return;
  }
  g_err = 1;
}
__device__ __forceinline__ void wait_bar1(uint32_t bar, uint32_t parity) { if (!try_wait(bar, parity)) wait_slow(bar, parity); }
__device__ __forceinline__ uint4 ld_relaxed_u4(const void* p) { uint4 v; asm volatile("ld.relaxed.gpu.global.v4.u32 {%0,%1,%2,%3}, [%4];" : "=r"(v.x), "=r"(v.y), "=r"(v.z), "=r"(v.w) : "l"(p) : "memory"); return v; }
__device__ __forceinline__ void red_h8(void* p, uint32_t a, uint32_t b, uint32_t c, uint32_t d) { asm volatile("red.relaxed.gpu.global.add.noftz.v4.f16x2 [%0], {%1,%2,%3,%4};" :: "l"(p), "r"(a), "r"(b), "r"(c), "r"(d) : "memory"); }
__device__ __forceinline__ uint32_t pack_f16(float lo, float hi) { uint32_t r; asm("cvt.rn.f16x2.f32 %0, %1, %2;" : "=r"(r) : "f"(hi), "f"(lo)); return r; }
__device__ __forceinline__ uint32_t h2_to_bf2(uint32_t v) {
  float lo, hi; asm("{.reg .f16 l, h; mov.b32 {l, h}, %2; cvt.f32.f16 %0, l; cvt.f32.f16 %1, h;}" : "=f"(lo), "=f"(hi) : "r"(v)); return pack_bf16(lo, hi); }
__device__ __forceinline__ uint2 lds64(uint32_t a) { uint2 v; asm volatile("ld.shared.v2.u32 {%0,%1}, [%2];" : "=r"(v.x), "=r"(v.y) : "r"(a) : "memory"); return v; }
__device__ __forceinline__ float2 lds64f(uint32_t a) { float2 v; asm volatile("ld.shared.v2.f32 {%0,%1}, [%2];" : "=f"(v.x), "=f"(v.y) : "r"(a) : "memory"); return v; }
__device__ __forceinline__ uint4 lds128(uint32_t a) { uint4 v; asm volatile("ld.shared.v4.u32 {%0,%1,%2,%3}, [%4];" : "=r"(v.x), "=r"(v.y), "=r"(v.z), "=r"(v.w) : "r"(a) : "memory"); return v; }
__device__ __forceinline__ uint4 lds128v(uint32_t a) { uint4 v; asm volatile("ld.volatile.shared.v4.u32 {%0,%1,%2,%3}, [%4];" : "=r"(v.x), "=r"(v.y), "=r"(v.z), "=r"(v.w) : "r"(a) : "memory"); return v; }
__device__ __forceinline__ uint32_t lds32(uint32_t a) { uint32_t v; asm volatile("ld.shared.u32 %0, [%1];" : "=r"(v) : "r"(a) : "memory"); return v; }
__device__ __forceinline__ void sts64(uint32_t a, uint32_t x, uint32_t y) { asm volatile("st.shared.v2.u32 [%0], {%1,%2};" :: "r"(a), "r"(x), "r"(y) : "memory"); }
__device__ __forceinline__ void sts64f(uint32_t a, float x, float y) { asm volatile("st.shared.v2.f32 [%0], {%1,%2};" :: "r"(a), "f"(x), "f"(y) : "memory"); }
__device__ __forceinline__ void sts32(uint32_t a, uint32_t x) { asm volatile("st.shared.u32 [%0], %1;" :: "r"(a), "r"(x) : "memory"); }
__device__ __forceinline__ void mma_z(float* d, uint32_t a0, uint32_t a1, uint32_t a2, uint32_t a3, uint32_t b0, uint32_t b1) {
  asm volatile("mma.sync.aligned.m16n8k16.row.col.f32.bf16.bf16.f32 {%0,%1,%2,%3}, {%4,%5,%6,%7}, {%8,%9}, {%10,%10,%10,%10};"
    : "=f"(d[0]), "=f"(d[1]), "=f"(d[2]), "=f"(d[3]) : "r"(a0), "r"(a1), "r"(a2), "r"(a3), "r"(b0), "r"(b1), "f"(0.f));
}
__device__ __forceinline__ void mma8_z(float* d, uint32_t a0, uint32_t a1, uint32_t b0) {
  asm volatile("mma.sync.aligned.m16n8k8.row.col.f32.bf16.bf16.f32 {%0,%1,%2,%3}, {%4,%5}, {%6}, {%7,%7,%7,%7};"
    : "=f"(d[0]), "=f"(d[1]), "=f"(d[2]), "=f"(d[3]) : "r"(a0), "r"(a1), "r"(b0), "f"(0.f));
}
__device__ __forceinline__ void hmma(float* d, uint32_t a0, uint32_t a1, uint32_t a2, uint32_t a3, uint32_t b0, uint32_t b1) {
  asm volatile("mma.sync.aligned.m16n8k16.row.col.f32.f16.f16.f32 {%0,%1,%2,%3}, {%4,%5,%6,%7}, {%8,%9}, {%0,%1,%2,%3};"
    : "+f"(d[0]), "+f"(d[1]), "+f"(d[2]), "+f"(d[3]) : "r"(a0), "r"(a1), "r"(a2), "r"(a3), "r"(b0), "r"(b1));
}
__device__ __forceinline__ void hmma_z(float* d, uint32_t a0, uint32_t a1, uint32_t a2, uint32_t a3, uint32_t b0, uint32_t b1) {
  asm volatile("mma.sync.aligned.m16n8k16.row.col.f32.f16.f16.f32 {%0,%1,%2,%3}, {%4,%5,%6,%7}, {%8,%9}, {%10,%10,%10,%10};"
    : "=f"(d[0]), "=f"(d[1]), "=f"(d[2]), "=f"(d[3]) : "r"(a0), "r"(a1), "r"(a2), "r"(a3), "r"(b0), "r"(b1), "f"(0.f));
}
__device__ __forceinline__ void hmma8(float* d, uint32_t a0, uint32_t a1, uint32_t b0) {
  asm volatile("mma.sync.aligned.m16n8k8.row.col.f32.f16.f16.f32 {%0,%1,%2,%3}, {%4,%5}, {%6}, {%0,%1,%2,%3};"
    : "+f"(d[0]), "+f"(d[1]), "+f"(d[2]), "+f"(d[3]) : "r"(a0), "r"(a1), "r"(b0));
}
__device__ __forceinline__ void hmma8_z(float* d, uint32_t a0, uint32_t a1, uint32_t b0) {
  asm volatile("mma.sync.aligned.m16n8k8.row.col.f32.f16.f16.f32 {%0,%1,%2,%3}, {%4,%5}, {%6}, {%7,%7,%7,%7};"
    : "=f"(d[0]), "=f"(d[1]), "=f"(d[2]), "=f"(d[3]) : "r"(a0), "r"(a1), "r"(b0), "f"(0.f));
}
__device__ __forceinline__ void lag(unsigned cyc) { const unsigned t = clk(); while (clk() - t < cyc) {} }
__device__ __forceinline__ float pow2i(int e) { return __uint_as_float((uint32_t)(127 + e) << 23); }
__device__ __forceinline__ int expo(float x) { return (int)(__float_as_uint(x) >> 23) - 127; }
__device__ __forceinline__ uint32_t bf2_to_h2(uint32_t v, float sc) { return pack_f16(bf_lo(v) * sc, bf_hi(v) * sc); }
__device__ __forceinline__ uint4 bf8_to_h8(uint4 v, float sc) { return make_uint4(bf2_to_h2(v.x, sc), bf2_to_h2(v.y, sc), bf2_to_h2(v.z, sc), bf2_to_h2(v.w, sc)); }
struct Scales { float amax, bmax, xmax; int sa, sb, sk; };
__device__ __forceinline__ float warp_max(float v) { return __uint_as_float(__reduce_max_sync(0xffffffffu, __float_as_uint(v))); }
__device__ __forceinline__ Scales get_scales() {
  const int lane = threadIdx.x & 31;
  Scales r;
  r.amax = warp_max(fmaxf(__ldcg(g_wmax + lane), __ldcg(g_wmax + 32 + lane)));
  r.bmax = warp_max(fmaxf(__ldcg(g_wmax + 64 + lane), __ldcg(g_wmax + 96 + lane)));
  r.xmax = warp_max(fmaxf(__ldcg(g_xmax + lane), __ldcg(g_xmax + 32 + lane)));
  r.sa = min(max(-10 - expo(r.amax), -40), 40);
  r.sb = min(max(-1 - expo(r.bmax), -40), 40);
  r.sk = min(max(15 - (expo(r.amax * r.xmax) + 10), -40), 40);
  return r;
}
__device__ __forceinline__ const uint4* wf_ptr(int mh, int t16, int ks, int lane) { return g_WF + ((mh * 28 + t16) * 28 + ks) * 32 + lane; }
__device__ __forceinline__ uint4 wf_ld(const uint4* p) { return __ldcg(p); }
__device__ __forceinline__ int seg_sx(float xm) { return min(max(14 - expo(xm), -40), 40); }
#define OFF(f) ((uint32_t)offsetof(RSmem, f))
#define BAR_SYNC(id, n) asm volatile("bar.sync %0, %1;" :: "n"(id), "n"(n) : "memory")
#define BAR_ARRIVE(id, n) asm volatile("bar.arrive %0, %1;" :: "n"(id), "n"(n) : "memory")

__device__ __forceinline__ void sts128(uint32_t a, uint32_t x, uint32_t y, uint32_t z, uint32_t w) { asm volatile("st.shared.v4.u32 [%0], {%1,%2,%3,%4};" :: "r"(a), "r"(x), "r"(y), "r"(z), "r"(w) : "memory"); }
template <int K>
__device__ __forceinline__ void kstep(const uint4 (&W)[42], float (&acc)[7][4], uint32_t b0, uint32_t b1, uint4& w6, uint32_t ws) {
#pragma unroll
  for (int t = 0; t < 6; t++) {
    const uint4& w = W[K * 6 + t];
    if (K == 0) mma_z(acc[t], w.x, w.y, w.z, w.w, b0, b1); else mma16816(acc[t], w.x, w.y, w.z, w.w, b0, b1);
  }
  if (K == 0) mma_z(acc[6], w6.x, w6.y, w6.z, w6.w, b0, b1); else mma16816(acc[6], w6.x, w6.y, w6.z, w6.w, b0, b1);
  if (K < 6) w6 = lds128(ws + (K + 1) * 512);
}
__device__ __forceinline__ uint32_t acc_page(uint32_t lp, uint32_t part) { return 2 * lp + ((lp ^ (lp >> 3) ^ (lp >> 4) ^ (lp >> 6) ^ part) & 1); }
__device__ __forceinline__ uint4* acc_ptr(int step, int vec, int lane, uint32_t part) {
  return g_ACC16 + acc_page((step >> 1) * 4 + (vec >> 2), part) * 256 + ((vec & 3) * 2 + (step & 1)) * 32 + lane; }

__device__ __forceinline__ bool elect1() { uint32_t p; asm volatile("{.reg .pred p; elect.sync _|p, 0xffffffff; selp.u32 %0, 1, 0, p;}" : "=r"(p)); return p; }
__device__ __forceinline__ float4 lds128f(uint32_t a) { float4 v; asm volatile("ld.shared.v4.f32 {%0,%1,%2,%3}, [%4];" : "=f"(v.x), "=f"(v.y), "=f"(v.z), "=f"(v.w) : "r"(a) : "memory"); return v; }
__device__ __forceinline__ float ex2v(float x) { float y; asm volatile("ex2.approx.ftz.f32 %0, %1;" : "=f"(y) : "f"(x)); return y; }
__device__ __forceinline__ uint32_t hadd_bf2(uint32_t a, uint32_t b) { uint32_t d; asm("add.rn.bf16x2 %0, %1, %2;" : "=r"(d) : "r"(a), "r"(b)); return d; }
__device__ __forceinline__ uint32_t amax2(uint32_t m, uint32_t x, uint32_t y) { return __vmaxu2(m, __vmaxu2(x & 0x7fff7fffu, y & 0x7fff7fffu)); }

#define FENCE(n) asm volatile("{.reg .pred p; setp.ne.u32 p, %0, 0; @p exit;}" :: "r"(poll_delay & (1 << (16 + (n)))) : "memory")
#define NT0(q) (((q) & 1) * 8 + ((q) >> 1) * 4)
#define NT2(q) ((q) == 3 ? 11 : NT0(q) + 2)
#define NTS(q) (3 + ((q) >> 1) * 4)
#define BURST1 T3(1)
#define BURST1B do { LB(0); T4(1); } while (0)
#define DEP(id, x) ((id) + (__float_as_uint(x) & zero))
#define BAR_SYNC_R(id, n) asm volatile("bar.sync %0, %1;" :: "r"(id), "n"(n) : "memory")
#define BAR_ARRIVE_R(id, n) asm volatile("bar.arrive %0, %1;" :: "r"(id), "n"(n) : "memory")
#define MMW(A, WW, B0, B1, first) do { if (first) mma_z(A, WW.x, WW.y, WW.z, WW.w, B0, B1); else mma16816(A, WW.x, WW.y, WW.z, WW.w, B0, B1); } while (0)
__device__ __forceinline__ void issue_loads(uint32_t sb, int s, int h, int j, uint32_t part) {
  const int st = s & (NST - 1), s0 = s;
  const uint32_t bar = sb + OFF(bar_ld) + 8 * st;
  arm_bar(bar, LD_BYTES);
  bulk_g2s(sb + OFF(kf) + st * 7168, g_KF + ((s * NH + h) * 4 + j) * 896, 7168, bar);
  bulk_g2s(sb + OFF(vf) + st * 7168, g_VF + ((s * NH + h) * 56 + 14 * j) * 32, 7168, bar);
  asm volatile("prefetch.global.L2 [%0];" :: "l"(acc_ptr(s0, h, j * 8, part)));
}
__device__ __forceinline__ void issue_xf(uint32_t sb, int s, int j) {
  const uint32_t bar = sb + OFF(bar_xf) + 8 * (s & 1);
  arm_bar(bar, 28672);
  asm volatile("cp.async.bulk.shared::cluster.global.mbarrier::complete_tx::bytes.multicast::cluster [%0], [%1], 7168, [%2], %3;"
    :: "r"(sb + OFF(xf) + (s & 1) * 28672 + j * 7168), "l"(g_XF + (s * 4 + j) * 448), "r"(bar), "h"((unsigned short)15) : "memory");
}
__device__ __forceinline__ int pump_loads(uint32_t sb, int nxt, int must, int lim, int h, int j, uint32_t part, int rdy) {
#pragma unroll 1
  while (nxt <= lim && nxt < NSEG) {
    if (nxt > rdy && nxt > must) break;
    if ((nxt & 1) == 0 && nxt > rdy) {
      bool ok = false;
#pragma unroll 1
      for (int it = 0; it < SPIN_LIMIT; it++) {
        unsigned v; asm volatile("ld.relaxed.gpu.global.u32 %0, [%1];" : "=r"(v) : "l"(g_ready + (nxt >> 1) * NH + h) : "memory");
        ok = v >= 14;
        if (ok || nxt > must) break;
      }
      if (!ok && nxt > must) break;
      asm volatile("fence.proxy.async.global;" ::: "memory");
    }
    issue_loads(sb, nxt, h, j, part);
    nxt++;
  }
  return nxt;
}
__device__ __forceinline__ unsigned ld_relaxed_u32(const unsigned* p) { unsigned v; asm volatile("ld.relaxed.gpu.global.u32 %0, [%1];" : "=r"(v) : "l"(p) : "memory"); return v; }
__device__ __forceinline__ void load_weights(uint4 (&W)[35], const uint4* wf, uint32_t ws, float wsc) {
#pragma unroll
  for (int i = 0; i < 35; i++) W[i] = __ldcg(wf + ((i % 7) * 28 + i / 7 + 1) * 32);
#pragma unroll 1
  for (int e = 0; e < 14; e += 7) {
    uint4 v[7];
#pragma unroll
    for (int t = 0; t < 7; t++) v[t] = __ldcg(wf + (t * 28 + (e ? 6 : 0)) * 32);
#pragma unroll
    for (int t = 0; t < 7; t++) { const uint4 c = bf8_to_h8(v[t], wsc); sts128(ws + (e + t) * 512, c.x, c.y, c.z, c.w); }
  }
#pragma unroll
  for (int i = 0; i < 35; i++) W[i] = bf8_to_h8(W[i], wsc);
}
__device__ __forceinline__ int opaque_lane() { return __shfl_sync(0xffffffffu, threadIdx.x & 31, threadIdx.x & 31); }

__global__ void __cluster_dims__(4, 1, 1) __launch_bounds__(384, 1) r_kernel(const bf16* mem0, int poll_delay) {
  extern __shared__ __align__(128) unsigned char smem_raw[];
  RSmem& sm = *reinterpret_cast<RSmem*>(smem_raw);
  const int j = blockIdx.x & 3;
  const int w = __reduce_max_sync(0xffffffffu, threadIdx.x >> 5), q = w & 3, role = w >> 2;
  const uint32_t sb = smem_u32(smem_raw);
  const uint32_t bar_ld = sb + OFF(bar_ld), bar_sx = sb + OFF(bar_sx), bar_sm = sb + OFF(bar_sm);
  if (threadIdx.x == 0) {
    for (int i = 0; i < NST; i++) asm volatile("mbarrier.init.shared::cta.b64 [%0], 1;" :: "r"(bar_ld + 8 * i));
    asm volatile("mbarrier.init.shared::cta.b64 [%0], 1;" :: "r"(bar_sx));
    asm volatile("mbarrier.init.shared::cta.b64 [%0], 1;" :: "r"(bar_sm));
    asm volatile("mbarrier.init.shared::cta.b64 [%0], 1;" :: "r"(bar_sm + 8));
    asm volatile("mbarrier.init.shared::cta.b64 [%0], 1;" :: "r"(bar_sm + 16));
    asm volatile("fence.mbarrier_init.release.cluster;" ::: "memory");
    arm_bar(bar_sx, 1024); arm_bar(bar_sm, 1024);
  }
  if (threadIdx.x == 0 && blockIdx.x == 0) TLS(256);
  asm volatile("griddepcontrol.launch_dependents;" ::: "memory");
  if (j == 0) {
    if ((threadIdx.x & 31) == 0) {
      unsigned best = ~0u;
      const int w_ = threadIdx.x >> 5;
      unsigned* pp = (unsigned*)(g_ACC16 + acc_page(200 + (w_ >> 1), w_ & 1) * 256) + (blockIdx.x >> 2) * 32;
#pragma unroll 1
      for (int it = 0; it < 3; it++) {
        const unsigned t0 = clk();
        const unsigned v = atomicAdd(pp, 0);
        sts32(sb + OFF(xexp) + 128 + (threadIdx.x >> 3), v);
        best = min(best, clk() - t0);
      }
      sm.xexp[w_] = best;
    }
    __syncthreads();
  }
  asm volatile("barrier.cluster.arrive.relaxed.aligned;\nbarrier.cluster.wait.aligned;" ::: "memory");
  if (j == 0 && threadIdx.x == 0) {
    int b0 = 1 << 30, b1 = 1 << 30;
#pragma unroll
    for (int i = 0; i < 6; i++) { b0 = min(b0, sm.xexp[2 * i]); b1 = min(b1, sm.xexp[2 * i + 1]); }
    const unsigned pme = b0 < b1 ? 0 : 1;
    const unsigned tk = atomicAdd(&g_reg[pme], 1);
    unsigned c0 = 0, c1 = 0;
#pragma unroll 1
    for (int it = 0; it < SPIN_LIMIT; it++) {
      asm volatile("ld.relaxed.gpu.global.v2.u32 {%0,%1}, [%2];" : "=r"(c0), "=r"(c1) : "l"(g_reg) : "memory");
      if (c0 + c1 >= (gridDim.x >> 2) || 2 * c0 >= (gridDim.x >> 2) + 0 * NH && c0 >= NH || 2 * c1 > (gridDim.x >> 2) && c1 >= NH) break;
    }
    const unsigned P = c0 >= c1 ? 0 : 1;
    const unsigned id = pme == P ? tk : (P ? c1 : c0) + tk;
#pragma unroll
    for (int r = 0; r < 4; r++) asm volatile("st.shared::cluster.u32 [%0], %1;" :: "r"(mapa(sb + OFF(smax) + 20, r)), "r"(id * 2 + P) : "memory");
  }
  asm volatile("barrier.cluster.arrive.release.aligned;\nbarrier.cluster.wait.acquire.aligned;" ::: "memory");
  const uint32_t hv = __reduce_max_sync(0xffffffffu, lds32(sb + OFF(smax) + 20));
  const int h = hv >> 1; const uint32_t part = hv & 1;
  if (h >= NH) {
    if (threadIdx.x == 0 && j == 0) { asm volatile("griddepcontrol.wait;" ::: "memory"); asm volatile("st.release.gpu.global.u32 [%0], 1;" :: "l"(g_go) : "memory"); }
    return;
  }
  Scales sc;
  {
    const int pass = 1;
    {
      asm volatile("griddepcontrol.wait;" ::: "memory");
      if (threadIdx.x == 256 && j == 0) asm volatile("st.release.gpu.global.u32 [%0], 1;" :: "l"(g_go) : "memory");
      if (threadIdx.x == 0 && h == 0 && j == 0) TLS(257);
      if (threadIdx.x == 0) { sm.sinv[0] = g_inv0; sm.sinv[3] = 0.f; sm.smax[4] = 2; sm.smax[6] = 1; }
      if (threadIdx.x < NSEG) { sm.xmax[threadIdx.x] = g_xmax[threadIdx.x]; sm.xexp[threadIdx.x] = expo(g_xmax[threadIdx.x]) + 1; }
    }
    sc = get_scales();
  }
  __syncthreads();
  const float LOG2E = 1.4426950408889634f;
  const uint32_t zero = (uint32_t)poll_delay >> 31;

  if (role == 0) {
    asm volatile("setmaxnreg.inc.sync.aligned.u32 216;");
    const int lane = opaque_lane();
    const uint32_t l16 = sb + lane * 16;
    const uint32_t lq = l16 + q * QB, mj = l16 + j * QB;
#define ws (lq + QOFF(wA))
    uint4 W[35];
    load_weights(W, wf_ptr(h, 7 * j, 7 * q, lane), ws, pow2i(sc.sa));
#define mq lq
    const uint32_t dst_sm = mapa(sb + lane * 8 + OFF(sm) + j * 256, q), dst_bar = mapa(bar_sm, q);
    const uint32_t redw = l16 + OFF(red) + (q >> 1) * 512 + (q & 1) * 8;
#define TM(t, k) do { if ((k) == 0) hmma_z(acc[t], f[t].x, f[t].y, f[t].z, f[t].w, b[0], b[1]); else { const uint4& w_ = (k) == 6 ? f[t] : W[(((k) - 1) % 5) * 7 + (t)]; hmma(acc[t], w_.x, w_.y, w_.z, w_.w, b[2 * (k)], b[2 * (k) + 1]); } } while (0)
#define T3(k) do { TM(0, k); TM(1, k); TM(2, k); } while (0)
#define T4(k) do { TM(3, k); TM(4, k); TM(5, k); TM(6, k); } while (0)
#define TR(t) do { kl[t] = movm(pack_f16(acc[t][0], acc[t][1])); kh[t] = movm(pack_f16(acc[t][2], acc[t][3])); } while (0)
#define T7(k) do { T3(k); T4(k); } while (0)
    if (h == 0 && j == 0 && threadIdx.x == 0) TLS(880);
    wait_bar1(bar_ld, 0);
    if (h == 0 && j == 0 && threadIdx.x == 0) TLS(881);
    unsigned tgo = clk();
    auto publish = [&](int sp) {
      if (elect1()) {
        if (sp > 0) { asm volatile("cp.async.bulk.wait_group 0;" ::: "memory"); asm volatile("red.relaxed.gpu.global.add.u32 [%0], 1;" :: "l"(&g_rdone[sp - 1]) : "memory"); }
        const uint32_t pa = sb + OFF(pub) + (sp & 1) * 3840;
        asm volatile("cp.async.bulk.global.shared::cta.bulk_group [%0], [%1], 1792;" :: "l"(g_UF + ((sp * NH + h) * 56 + 14 * j) * 32), "r"(pa) : "memory");
        asm volatile("cp.async.bulk.global.shared::cta.bulk_group [%0], [%1], 2048;" :: "l"(g_SXM + (((sp * NH + h) * 4 + j) * 4) * 32), "r"(pa + 1792) : "memory");
        asm volatile("cp.async.bulk.commit_group;" ::: "memory");
        if (h == 0 && j == 0) TLS(260 + sp);
      }
      __syncwarp();
    };
    uint2 kx[7];
    uint4 f[7];
#pragma unroll
    for (int t = 0; t < 7; t++) f[t] = lds128(ws + t * 512);
#pragma unroll 1
    for (int s = 0; s < NSEG; s++) {
      const uint4* p = (const uint4*)((const char*)acc_ptr(s, q * 4, 0, part) + (l16 - sb));
      { const uint32_t kb = sb + OFF(kf) + q * 1792 + (s & (NST - 1)) * 7168 + ((l16 - sb) >> 1);
#pragma unroll
        for (int i = 0; i < 7; i++) kx[i] = lds64(kb + i * 256); }
      asm volatile("" : "+l"(p));
      while ((int)(clk() - tgo) < 0) {}
      STAMP(0);
      uint4 v0 = ld_relaxed_u4(p), v1 = ld_relaxed_u4(p + 64), v2 = ld_relaxed_u4(p + 128), v3 = ld_relaxed_u4(p + 192);
      if (!__all_sync(0xffffffffu, __byte_perm(v0.w, v1.w, 0x7632) == 0x4C004C00u && __byte_perm(v2.w, v3.w, 0x7632) == 0x4C004C00u)) {
#pragma unroll 1
        for (int n = 0; n < SPIN_LIMIT; n++) {
          v0 = ld_relaxed_u4(p); v1 = ld_relaxed_u4(p + 64); v2 = ld_relaxed_u4(p + 128); v3 = ld_relaxed_u4(p + 192);
          if (__all_sync(0xffffffffu, __byte_perm(v0.w, v1.w, 0x7632) == 0x4C004C00u && __byte_perm(v2.w, v3.w, 0x7632) == 0x4C004C00u)) break;
        }
      }
      STAMP(1);
      const uint32_t b[14] = {v0.x, v0.y, v0.z, __byte_perm(v0.w, v1.w, 0x5410), v2.x, v2.y, v2.z, __byte_perm(v2.w, v3.w, 0x5410), v1.x, v1.y, v1.z, v3.z, v3.x, v3.y};
      float acc[7][4];
      float dl[4], dh[4], el[4], eh[4];
      hmma_z(dl, b[0], b[1], b[2], b[3], kx[0].x, kx[0].y); hmma_z(dh, b[0], b[1], b[2], b[3], kx[1].x, kx[1].y);
      hmma_z(el, b[4], b[5], b[6], b[7], kx[2].x, kx[2].y); hmma_z(eh, b[4], b[5], b[6], b[7], kx[3].x, kx[3].y);
      hmma(dl, b[8], b[9], b[10], b[11], kx[4].x, kx[4].y); hmma(dh, b[8], b[9], b[10], b[11], kx[5].x, kx[5].y);
      hmma8(el, b[12], b[13], kx[6].x); hmma8(eh, b[12], b[13], kx[6].y);
      sts128(mq, b[0], b[1], b[2], b[3]); sts128(mq + 512, b[4], b[5], b[6], b[7]); sts128(mq + 1024, b[8], b[9], b[10], b[11]); sts64(mq + 1536, b[12], b[13]);
      T7(0);
      sts64f(redw + 1024, (dl[0] + dh[2]) + (el[0] + eh[2]), (dl[1] + dh[3]) + (el[1] + eh[3]));
      BAR_ARRIVE(14, 256);
      BAR_ARRIVE(5, 256);
      FENCE(1);
#define LG(t) f[t] = lds128(ws + (7 + (t)) * 512)
#define T3B(k) do { TM(4, k); TM(5, k); TM(6, k); } while (0)
#define T4A(k) do { T3(k); TM(3, k); } while (0)
      LG(0); LG(1); LG(2); LG(3); T7(1); T7(2); T4A(3);
      FENCE(2);
      BAR_SYNC(15, 128);
      uint4 a0 = lds128v(mj), a1 = lds128v(mj + 512), a2 = lds128v(mj + 1024); uint2 a3 = lds64(mj + 1536);
      T4A(4); T3B(3);
      FENCE(4);
      LG(4); LG(5); LG(6);
      T4A(5); T3B(4); T4A(6); T3B(5);
      BAR_ARRIVE(1, 256);
      FENCE(3);
      uint32_t kl[7], kh[7];
      TR(0); TR(1); T3B(6); TR(2); TR(3);
      hmma_z(dl, a0.x, a0.y, a0.z, a0.w, kl[0], kh[0]); hmma_z(dh, a0.x, a0.y, a0.z, a0.w, kl[1], kh[1]);
      TR(4); TR(5); TR(6);
      hmma_z(el, a1.x, a1.y, a1.z, a1.w, kl[2], kh[2]); hmma_z(eh, a1.x, a1.y, a1.z, a1.w, kl[3], kh[3]);
      hmma(dl, a2.x, a2.y, a2.z, a2.w, kl[4], kh[4]); hmma(dh, a2.x, a2.y, a2.z, a2.w, kl[5], kh[5]);
      hmma8(el, a3.x, a3.y, kl[6]); hmma8(eh, a3.x, a3.y, kh[6]);
      BAR_ARRIVE_R(10 + q + (kh[6] & kh[5] & zero), 64);
      sts64f(redw, (dl[0] + dh[2]) + (el[0] + eh[2]), (dl[1] + dh[3]) + (el[1] + eh[3]));
      STAMP(3);
      BAR_SYNC(2, 128);
      {
        float4 t0 = lds128f(l16 + OFF(red)), t1 = lds128f(l16 + OFF(red) + 512);
        st_async2(dst_sm, (t0.x + t0.z) + (t1.x + t1.z), (t0.y + t0.w) + (t1.y + t1.w), dst_bar);
      }
      STAMP(4);
      FENCE(5);
      BAR_SYNC(6, 256);
      sts128(lq + QOFF(kq), kl[0], kh[0], kl[1], kh[1]); sts128(lq + QOFF(kq) + 512, kl[2], kh[2], kl[3], kh[3]);
      sts128(lq + QOFF(kq) + 1024, kl[4], kh[4], kl[5], kh[5]); sts64(lq + QOFF(kq) + 1536, kl[6], kh[6]);
      if (q == 3 && s > 0) publish(s - 1);
      BAR_ARRIVE(7, 384);
#pragma unroll
      for (int t = 0; t < 7; t++) f[t] = lds128v(ws + t * 512);
      if (q == 1) {
        if (elect1()) {
          uint32_t nx, rd; asm volatile("ld.volatile.shared.u32 %0, [%2];\n\tld.volatile.shared.u32 %1, [%2+8];" : "=r"(nx), "=r"(rd) : "r"(sb + OFF(smax) + 16) : "memory");
          sts32(sb + OFF(smax) + 16, pump_loads(sb, nx, s + 1, s + 2, h, j, part, rd));
        }
        __syncwarp();
      }
      if (s + 1 < NSEG) wait_bar1(bar_ld + 8 * ((s + 1) & (NST - 1)), ((s + 1) / NST) & 1);

      BAR_SYNC(4, 256);
      tgo = clk() + (poll_delay & 0xffff);
    }
    BAR_SYNC(6, 256);
    if (q == 3) { publish(NSEG - 1); if (elect1()) { asm volatile("cp.async.bulk.wait_group 0;" ::: "memory"); asm volatile("red.relaxed.gpu.global.add.u32 [%0], 1;" :: "l"(&g_rdone[NSEG - 1]) : "memory"); } __syncwarp(); }
  } else if (role == 1) {
    asm volatile("setmaxnreg.inc.sync.aligned.u32 200;");
    const int lane = opaque_lane();
    const uint32_t l16 = sb + lane * 16;
#undef ws
#define ws (lq + QOFF(wB))
    const uint32_t lq = l16 + q * QB;
#define uq (lq + QOFF(uQ))
    uint4 W[35];
    load_weights(W, wf_ptr(NH + h, 7 * j, 7 * q, lane), ws, pow2i(sc.sb));
#pragma unroll 1
    for (int s = 0; s < NSEG; s++) {
      const int st = s & (NST - 1);
      float acc[7][4];
      uint32_t b[14];
#define LB(p) do { if ((p) < 3) { uint4 t_ = lds128(mq + (p) * 512); b[4 * (p)] = t_.x; b[4 * (p) + 1] = t_.y; b[4 * (p) + 2] = t_.z; b[4 * (p) + 3] = t_.w; } else { uint2 t_ = lds64(mq + 1536); b[12] = t_.x; b[13] = t_.y; } } while (0)
#define UP(nt) pack_bf16(acc[(nt) >> 1][((nt) & 1) * 2], acc[(nt) >> 1][((nt) & 1) * 2 + 1])
      BAR_ARRIVE(6, 256);
      uint4 f[7];
#pragma unroll
      for (int t = 0; t < 7; t++) f[t] = lds128(ws + t * 512);
      BAR_SYNC(5, 256);
      LB(0); LB(1); LB(2); LB(3);
      {
        uint32_t m = amax2(amax2(amax2(amax2(0u, b[0], b[1]), b[2], b[3]), b[4], b[5]), b[6], b[7]);
        m = amax2(amax2(amax2(m, b[8], b[9]), b[10], b[11]), b[12], b[13]);
        m = max(m & 0xffffu, m >> 16);
        m = __reduce_max_sync(0xffffffffu, m);
        sts32(sb + OFF(smax) + q * 4, m);
      }
      BAR_SYNC(1, 256);
      FENCE(6);
      STAMP(10);
      T7(0); T3(1);
      FENCE(7);
      BAR_SYNC_R(10 + q, 64);
      FENCE(8);
      T4(1); T7(2); LG(0); LG(1); LG(2); T7(3);
      FENCE(10);
      LG(3); LG(4); LG(5); LG(6); T7(4); T7(5); T7(6);
      { uint32_t u3 = UP(3), u7 = UP(7);
        sts128(uq, UP(0), UP(1), UP(2), u3); sts128(uq + 1024, UP(4), UP(5), UP(6), u7);
        sts128(uq + 512, UP(8), UP(9), UP(10), u3); sts128(uq + 1536, UP(12), UP(13), UP(11), u7); }
      BAR_ARRIVE(3, 256);
      STAMP(11);
      const float inv0 = __uint_as_float(lds32(sb + OFF(sinv) + (s & 1) * 4));
      const unsigned flagv = ld_relaxed_u32(g_ready + (min(s + 3, NSEG - 1) >> 1) * NH + h + (lane & zero));
      BAR_SYNC(7, 384);
      {
        wait_bar1(sb + OFF(bar_xf) + 8 * (s & 1), (s >> 1) & 1);
        const uint32_t xb = l16 + OFF(xf) + (s & 1) * 28672 + j * 7168;
        uint32_t kr = l16 + QOFF(kq) + q * 512; asm volatile("" : "+r"(kr));
        const uint4 x0 = lds128(xb + q * 2048), x1 = lds128(xb + q * 2048 + 512);
        uint4 x2 = make_uint4(0, 0, 0, 0), x3 = x2;
        if (q < 3) { x2 = lds128(xb + q * 2048 + 1024); x3 = lds128(xb + q * 2048 + 1536); }
        float y[4][4];
#pragma unroll
        for (int i = 0; i < 4; i++) {
          uint4 kk = lds128(kr + i * QB);
          if (q == 3) { kk.z = 0; kk.w = 0; }
          if (i == 0) { hmma_z(y[0], x0.x, x0.y, x0.z, x0.w, kk.x, kk.y); hmma_z(y[2], x1.x, x1.y, x1.z, x1.w, kk.x, kk.y); hmma_z(y[1], x2.x, x2.y, x2.z, x2.w, kk.z, kk.w); hmma_z(y[3], x3.x, x3.y, x3.z, x3.w, kk.z, kk.w); }
          else { hmma(y[0], x0.x, x0.y, x0.z, x0.w, kk.x, kk.y); hmma(y[2], x1.x, x1.y, x1.z, x1.w, kk.x, kk.y); hmma(y[1], x2.x, x2.y, x2.z, x2.w, kk.z, kk.w); hmma(y[3], x3.x, x3.y, x3.z, x3.w, kk.z, kk.w); }
        }
#pragma unroll
        for (int m = 0; m < 2; m++)
          sts128(lq + QOFF(xred) + m * 512, __float_as_uint(y[2 * m][0] + y[2 * m + 1][0]), __float_as_uint(y[2 * m][1] + y[2 * m + 1][1]), __float_as_uint(y[2 * m][2] + y[2 * m + 1][2]), __float_as_uint(y[2 * m][3] + y[2 * m + 1][3]));
      }
      {
        const int nt0 = NT0(q), nt2 = NT2(q), nts = NTS(q);
        const float inv = inv0 * pow2i(-sc.sb);
        uint32_t ub = l16 + QOFF(uQ) + q * 512; asm volatile("" : "+r"(ub));
        uint4 u0 = lds128(ub), u1 = lds128(ub + QB), u2 = lds128(ub + 2 * QB), u3 = lds128(ub + 3 * QB);
        auto us = [&](uint32_t a, uint32_t b, uint32_t c, uint32_t d) { return pack_bf16(((bf_lo(a) + bf_lo(b)) + (bf_lo(c) + bf_lo(d))) * inv, ((bf_hi(a) + bf_hi(b)) + (bf_hi(c) + bf_hi(d))) * inv); };
        const uint32_t ua = sb + OFF(pub) + (s & 1) * 3840 + ((l16 - sb) >> 2);
        sts32(ua + (nt0 + 0) * 128, us(u0.x, u1.x, u2.x, u3.x)); sts32(ua + (nt0 + 1) * 128, us(u0.y, u1.y, u2.y, u3.y)); sts32(ua + nt2 * 128, us(u0.z, u1.z, u2.z, u3.z));
        if ((q & 1) == 0) sts32(ua + nts * 128, us(u0.w, u1.w, u2.w, u3.w));
      }
      {
        BAR_SYNC(0, 256);
        if (q == 2) { if (elect1()) { arm_bar(bar_sx, 1024); arm_bar(bar_sm, 1024); } __syncwarp(); }
        {
          const int sx_ = seg_sx(__uint_as_float(lds32(sb + OFF(xmax) + s * 4)));
          const float inv = q < 2 ? inv0 * pow2i(-sc.sa - sx_) : pow2i(-sc.sk - sx_);
          uint32_t xr = l16 + QOFF(xred) + q * 512; asm volatile("" : "+r"(xr));
          float4 t0 = lds128f(xr), t1 = lds128f(xr + QB), t2 = lds128f(xr + 2 * QB), t3 = lds128f(xr + 3 * QB);
          sts128(l16 + OFF(pub) + (s & 1) * 3840 + 1792 + q * 512, __float_as_uint(((t0.x + t1.x) + (t2.x + t3.x)) * inv), __float_as_uint(((t0.y + t1.y) + (t2.y + t3.y)) * inv),
                 __float_as_uint(((t0.z + t1.z) + (t2.z + t3.z)) * inv), __float_as_uint(((t0.w + t1.w) + (t2.w + t3.w)) * inv));
        }
        asm volatile("fence.proxy.async.shared::cta;" ::: "memory");
        if (q == 3 && flagv >= 14) sts32(sb + OFF(smax) + 24, (s + 3) | 1);
      }
    }
    BAR_ARRIVE(6, 256);
  } else {
    asm volatile("setmaxnreg.dec.sync.aligned.u32 88;");
    const int lane = opaque_lane();
    const uint32_t l16 = sb + lane * 16;
    const int nt0 = NT0(q), nt2 = NT2(q), nts = NTS(q);
    const int ebm = expo(sc.bmax) + 1 + 13;
    int se = (int)(127 - (__float_as_uint(g_inv0) >> 23));
    if (q == 0) { if (elect1()) { asm volatile("fence.proxy.async.global;" ::: "memory"); issue_xf(sb, 0, j); pump_loads(sb, 0, 1, 1, h, j, part, -1); } __syncwarp(); }
    const uint32_t l8 = sb + lane * 8;
    const uint32_t dst_sx = mapa(l8 + OFF(sx) + j * 256, q), dst_bar = mapa(bar_sx, q);
#pragma unroll 1
    for (int s = 0; s < NSEG; s++) {
      const int st = s & (NST - 1);
      float ya[4], yb[4], z[4];
      float mx;
      int nse;
      const float inv = __uint_as_float((uint32_t)(127 - se) << 23);
      const float c1 = LOG2E * inv * pow2i(-sc.sk);
      {
        const uint32_t vb = l16 + OFF(vf) + st * 7168;
        wait_bar1(bar_ld + 8 * st, (s / NST) & 1);
        uint4 v0 = lds128(vb + nt0 * 512), v1 = lds128(vb + nt0 * 512 + 512), v2 = lds128(vb + nt2 * 512), v3 = lds128(vb + nts * 512);
        BAR_SYNC(14, 256);
        STAMP(2);
        {
          float4 t0 = lds128f(l16 + OFF(red2)), t1 = lds128f(l16 + OFF(red2) + 512);
          st_async2(dst_sx, (t0.x + t0.z) + (t1.x + t1.z), (t0.y + t0.w) + (t1.y + t1.w), dst_bar);
        }
        STAMP(9);
        wait_bar1(bar_sx, s & 1);
        STAMP(12);
        const float2 x0 = lds64f(l8 + OFF(sx)), x1 = lds64f(l8 + OFF(sx) + 256), x2 = lds64f(l8 + OFF(sx) + 512), x3 = lds64f(l8 + OFF(sx) + 768);
        float sx[8] = {x0.x, x0.y, x1.x, x1.y, x2.x, x2.y, x3.x, x3.y};
        mx = fmaxf(fmaxf(fmaxf(sx[0], sx[1]), fmaxf(sx[2], sx[3])), fmaxf(fmaxf(sx[4], sx[5]), fmaxf(sx[6], sx[7])));
        mx = fmaxf(mx, __shfl_xor_sync(0xffffffffu, mx, 1)); mx = fmaxf(mx, __shfl_xor_sync(0xffffffffu, mx, 2));
        mx *= c1;
#pragma unroll
        for (int i = 0; i < 8; i++) sx[i] = ex2(fmaf(sx[i], c1, -mx));
        uint32_t p0 = pack_bf16(sx[0], sx[1]), p1 = pack_bf16(sx[2], sx[3]), p2 = pack_bf16(sx[4], sx[5]), p3 = pack_bf16(sx[6], sx[7]);
        float o[4], r[4];
        mma_z(o, p0, p2, p1, p3, v0.x, v0.y); mma_z(r, p0, p2, p1, p3, v0.z, v0.w); ya[0] = o[0] + r[2]; ya[1] = o[1] + r[3];
        mma_z(o, p0, p2, p1, p3, v1.x, v1.y); mma_z(r, p0, p2, p1, p3, v1.z, v1.w); ya[2] = o[0] + r[2]; ya[3] = o[1] + r[3];
        mma_z(o, p0, p2, p1, p3, v2.x, v2.y); mma_z(r, p0, p2, p1, p3, v2.z, v2.w); yb[0] = o[0] + r[2]; yb[1] = o[1] + r[3];
        mma_z(o, p0, p2, p1, p3, v3.x, v3.y); mma_z(r, p0, p2, p1, p3, v3.z, v3.w); yb[2] = o[0] + r[2]; yb[3] = o[1] + r[3];
        mma_z(z, p0, p2, p1, p3, 0x3f803f80u, 0x3f803f80u); z[0] += z[2];
      }
      asm volatile("" : "+f"(ya[0]), "+f"(ya[1]), "+f"(ya[2]), "+f"(ya[3]), "+f"(yb[0]), "+f"(yb[1]), "+f"(yb[2]), "+f"(yb[3]), "+f"(z[0]));
      STAMP(5);
      const int su = se + sc.sb;
      const uint32_t zb = (uint32_t)(127 + su) * 0x00800080u;
      const float c2 = LOG2E * pow2i(-2 * se - sc.sa);
      float off = -mx - (float)su;
      const float lim = 32.f - (float)su;
      const int xe = (int)lds32(sb + OFF(xmax) + 256 + s * 4);
      uint4* redp = (uint4*)((char*)acc_ptr(s + 1, j * 4 + q, 0, part) + (l16 - sb));
      FENCE(9);
      if (q == 3 && s + 1 < NSEG) { if (elect1()) issue_xf(sb, s + 1, j); __syncwarp(); }
      STAMP(6);
      wait_bar1(bar_sm, s & 1);
      STAMP(7);
      {
        const float2 t0 = lds64f(l8 + OFF(sm)), t1 = lds64f(l8 + OFF(sm) + 256), t2 = lds64f(l8 + OFF(sm) + 512), t3 = lds64f(l8 + OFF(sm) + 768);
        const float r0 = (t0.x + t1.x) + (t2.x + t3.x), r1 = (t0.y + t1.y) + (t2.y + t3.y);
        float a0 = fmaf(r0, c2, off), a1 = fmaf(r1, c2, off);
        uint32_t pm = pack_bf16(ex2v(a0), ex2v(a1));
        if (__any_sync(0xffffffffu, !(fmaxf(a0, a1) <= lim))) {
          float m = fmaxf(fmaxf(r0, r1) * c2, mx);
          m = fmaxf(m, __shfl_xor_sync(0xffffffffu, m, 1)); m = fmaxf(m, __shfl_xor_sync(0xffffffffu, m, 2));
          const float al = ex2(mx - m);
#pragma unroll
          for (int i = 0; i < 4; i++) { ya[i] *= al; yb[i] *= al; }
          z[0] *= al;
          off = -m - (float)su;
          pm = pack_bf16(ex2(fmaf(r0, c2, off)), ex2(fmaf(r1, c2, off)));
        }
        BAR_SYNC(3, 256);
        const uint32_t ub = l16 + QOFF(uQ) + q * 512;
        const uint4 u0 = lds128(ub), u1 = lds128(ub + QB), u2 = lds128(ub + 2 * QB), u3 = lds128(ub + 3 * QB);
        mma16816(z, pm, 0u, 0u, pm, zb, zb);
        {
          uint4 m4 = lds128(sb + OFF(smax));
          uint32_t mb = max(max(m4.x, m4.y), max(m4.z, m4.w));
          const int eh = max((int)(mb >> 10) - 14 - se, xe);
          nse = min(max(15 - (eh + ebm), -40), 40);
        }
        float yc[4], yd[4];
        mma16816(ya, pm, 0u, 0u, pm, u0.x, u0.y); mma16816(yb, pm, 0u, 0u, pm, u0.z, u0.w);
        mma_z(yc, pm, 0u, 0u, pm, u1.x, u1.y); mma_z(yd, pm, 0u, 0u, pm, u1.z, u1.w);
        mma16816(ya, pm, 0u, 0u, pm, u2.x, u2.y); mma16816(yb, pm, 0u, 0u, pm, u2.z, u2.w);
        mma16816(yc, pm, 0u, 0u, pm, u3.x, u3.y); mma16816(yd, pm, 0u, 0u, pm, u3.z, u3.w);
        float iz; asm("rcp.approx.ftz.f32 %0, %1;" : "=f"(iz) : "f"(z[0]));
        iz *= pow2i(nse);
#pragma unroll
        for (int i = 0; i < 4; i++) { ya[i] += yc[i]; yb[i] += yd[i]; }
        red_h8(redp, pack_f16(ya[0] * iz, ya[1] * iz), pack_f16(ya[2] * iz, ya[3] * iz), pack_f16(yb[0] * iz, yb[1] * iz), pack_f16(((q & 1) ? yb[3] : yb[2]) * iz, 1.f));
      }
      BAR_ARRIVE(4, 256);
      BAR_ARRIVE(7, 384);
      STAMP(8);
      if (q == 0) sts32(sb + OFF(sinv) + ((s + 1) & 1) * 4, (uint32_t)(127 - nse) << 23);
      se = nse;
      {
        FENCE(12);
        wait_bar1(sb + OFF(bar_xf) + 8 * (s & 1), (s >> 1) & 1);
        const uint32_t xb = l16 + OFF(xf) + (s & 1) * 28672 + q * 7168, kb = l8 + OFF(kf) + q * 1792 + st * 7168;
        float y[4][4];
#pragma unroll
        for (int f = 0; f < 7; f++) {
          const uint2 kk = lds64(kb + f * 256);
#pragma unroll
          for (int m = 0; m < 2; m++) {
            const uint4 xa = lds128(xb + (f * 2 + m) * 512);
            if (f < 2) hmma_z(y[m * 2 + f], xa.x, xa.y, xa.z, xa.w, kk.x, kk.y); else hmma(y[m * 2 + (f & 1)], xa.x, xa.y, xa.z, xa.w, kk.x, kk.y);
          }
        }
#pragma unroll
        for (int m = 0; m < 2; m++)
          sts128(l16 + q * QB + QOFF(xred2) + m * 512, __float_as_uint(y[2 * m][0] + y[2 * m + 1][0]), __float_as_uint(y[2 * m][1] + y[2 * m + 1][1]), __float_as_uint(y[2 * m][2] + y[2 * m + 1][2]), __float_as_uint(y[2 * m][3] + y[2 * m + 1][3]));
        BAR_SYNC(0, 256);
      }
    }
  }
  asm volatile("barrier.cluster.arrive.release.aligned;\nbarrier.cluster.wait.acquire.aligned;" ::: "memory");
}

__device__ __forceinline__ void wg_ss112(float (&d)[56], uint64_t da, uint64_t db, int acc) {
  asm volatile("{\n.reg .pred p;\nsetp.ne.b32 p, %58, 0;\nwgmma.mma_async.sync.aligned.m64n112k16.f32.bf16.bf16 {%0, %1, %2, %3, %4, %5, %6, %7, %8, %9, %10, %11, %12, %13, %14, %15, %16, %17, %18, %19, %20, %21, %22, %23, %24, %25, %26, %27, %28, %29, %30, %31, %32, %33, %34, %35, %36, %37, %38, %39, %40, %41, %42, %43, %44, %45, %46, %47, %48, %49, %50, %51, %52, %53, %54, %55}, %56, %57, p, 1, 1, 0, 0;\n}"
    : "+f"(d[0]), "+f"(d[1]), "+f"(d[2]), "+f"(d[3]), "+f"(d[4]), "+f"(d[5]), "+f"(d[6]), "+f"(d[7]), "+f"(d[8]), "+f"(d[9]), "+f"(d[10]), "+f"(d[11]), "+f"(d[12]), "+f"(d[13]), "+f"(d[14]), "+f"(d[15]), "+f"(d[16]), "+f"(d[17]), "+f"(d[18]), "+f"(d[19]), "+f"(d[20]), "+f"(d[21]), "+f"(d[22]), "+f"(d[23]), "+f"(d[24]), "+f"(d[25]), "+f"(d[26]), "+f"(d[27]), "+f"(d[28]), "+f"(d[29]), "+f"(d[30]), "+f"(d[31]), "+f"(d[32]), "+f"(d[33]), "+f"(d[34]), "+f"(d[35]), "+f"(d[36]), "+f"(d[37]), "+f"(d[38]), "+f"(d[39]), "+f"(d[40]), "+f"(d[41]), "+f"(d[42]), "+f"(d[43]), "+f"(d[44]), "+f"(d[45]), "+f"(d[46]), "+f"(d[47]), "+f"(d[48]), "+f"(d[49]), "+f"(d[50]), "+f"(d[51]), "+f"(d[52]), "+f"(d[53]), "+f"(d[54]), "+f"(d[55])
    : "l"(da), "l"(db), "r"(acc));
}
__device__ __forceinline__ void wg_ss112_ta(float (&d)[56], uint64_t da, uint64_t db, int acc) {
  asm volatile("{\n.reg .pred p;\nsetp.ne.b32 p, %58, 0;\nwgmma.mma_async.sync.aligned.m64n112k16.f32.bf16.bf16 {%0, %1, %2, %3, %4, %5, %6, %7, %8, %9, %10, %11, %12, %13, %14, %15, %16, %17, %18, %19, %20, %21, %22, %23, %24, %25, %26, %27, %28, %29, %30, %31, %32, %33, %34, %35, %36, %37, %38, %39, %40, %41, %42, %43, %44, %45, %46, %47, %48, %49, %50, %51, %52, %53, %54, %55}, %56, %57, p, 1, 1, 1, 0;\n}"
    : "+f"(d[0]), "+f"(d[1]), "+f"(d[2]), "+f"(d[3]), "+f"(d[4]), "+f"(d[5]), "+f"(d[6]), "+f"(d[7]), "+f"(d[8]), "+f"(d[9]), "+f"(d[10]), "+f"(d[11]), "+f"(d[12]), "+f"(d[13]), "+f"(d[14]), "+f"(d[15]), "+f"(d[16]), "+f"(d[17]), "+f"(d[18]), "+f"(d[19]), "+f"(d[20]), "+f"(d[21]), "+f"(d[22]), "+f"(d[23]), "+f"(d[24]), "+f"(d[25]), "+f"(d[26]), "+f"(d[27]), "+f"(d[28]), "+f"(d[29]), "+f"(d[30]), "+f"(d[31]), "+f"(d[32]), "+f"(d[33]), "+f"(d[34]), "+f"(d[35]), "+f"(d[36]), "+f"(d[37]), "+f"(d[38]), "+f"(d[39]), "+f"(d[40]), "+f"(d[41]), "+f"(d[42]), "+f"(d[43]), "+f"(d[44]), "+f"(d[45]), "+f"(d[46]), "+f"(d[47]), "+f"(d[48]), "+f"(d[49]), "+f"(d[50]), "+f"(d[51]), "+f"(d[52]), "+f"(d[53]), "+f"(d[54]), "+f"(d[55])
    : "l"(da), "l"(db), "r"(acc));
}
__device__ __forceinline__ void wg_rs32(float (&d)[16], const uint4& a, uint64_t db, int acc) {
  asm volatile("{\n.reg .pred p;\nsetp.ne.b32 p, %21, 0;\nwgmma.mma_async.sync.aligned.m64n32k16.f32.bf16.bf16 {%0, %1, %2, %3, %4, %5, %6, %7, %8, %9, %10, %11, %12, %13, %14, %15}, {%16, %17, %18, %19}, %20, p, 1, 1, 0;\n}"
    : "+f"(d[0]), "+f"(d[1]), "+f"(d[2]), "+f"(d[3]), "+f"(d[4]), "+f"(d[5]), "+f"(d[6]), "+f"(d[7]), "+f"(d[8]), "+f"(d[9]), "+f"(d[10]), "+f"(d[11]), "+f"(d[12]), "+f"(d[13]), "+f"(d[14]), "+f"(d[15])
    : "r"(a.x), "r"(a.y), "r"(a.z), "r"(a.w), "l"(db), "r"(acc));
}
__device__ __forceinline__ void wg_ss64(float (&d)[32], uint64_t da, uint64_t db, int acc) {
  asm volatile("{\n.reg .pred p;\nsetp.ne.b32 p, %34, 0;\nwgmma.mma_async.sync.aligned.m64n64k16.f32.bf16.bf16 {%0, %1, %2, %3, %4, %5, %6, %7, %8, %9, %10, %11, %12, %13, %14, %15, %16, %17, %18, %19, %20, %21, %22, %23, %24, %25, %26, %27, %28, %29, %30, %31}, %32, %33, p, 1, 1, 0, 0;\n}"
    : "+f"(d[0]), "+f"(d[1]), "+f"(d[2]), "+f"(d[3]), "+f"(d[4]), "+f"(d[5]), "+f"(d[6]), "+f"(d[7]), "+f"(d[8]), "+f"(d[9]), "+f"(d[10]), "+f"(d[11]), "+f"(d[12]), "+f"(d[13]), "+f"(d[14]), "+f"(d[15]), "+f"(d[16]), "+f"(d[17]), "+f"(d[18]), "+f"(d[19]), "+f"(d[20]), "+f"(d[21]), "+f"(d[22]), "+f"(d[23]), "+f"(d[24]), "+f"(d[25]), "+f"(d[26]), "+f"(d[27]), "+f"(d[28]), "+f"(d[29]), "+f"(d[30]), "+f"(d[31])
    : "l"(da), "l"(db), "r"(acc));
}

__device__ __forceinline__ void wg_ss32(float (&d)[16], uint64_t da, uint64_t db, int acc) {
  asm volatile("{\n.reg .pred p;\nsetp.ne.b32 p, %18, 0;\nwgmma.mma_async.sync.aligned.m64n32k16.f32.bf16.bf16 {%0, %1, %2, %3, %4, %5, %6, %7, %8, %9, %10, %11, %12, %13, %14, %15}, %16, %17, p, 1, 1, 0, 0;\n}"
    : "+f"(d[0]), "+f"(d[1]), "+f"(d[2]), "+f"(d[3]), "+f"(d[4]), "+f"(d[5]), "+f"(d[6]), "+f"(d[7]), "+f"(d[8]), "+f"(d[9]), "+f"(d[10]), "+f"(d[11]), "+f"(d[12]), "+f"(d[13]), "+f"(d[14]), "+f"(d[15])
    : "l"(da), "l"(db), "r"(acc));
}
__device__ __forceinline__ void wg_ss56_tb(float (&d)[28], uint64_t da, uint64_t db, int acc) {
  asm volatile("{\n.reg .pred p;\nsetp.ne.b32 p, %30, 0;\nwgmma.mma_async.sync.aligned.m64n56k16.f32.bf16.bf16 {%0, %1, %2, %3, %4, %5, %6, %7, %8, %9, %10, %11, %12, %13, %14, %15, %16, %17, %18, %19, %20, %21, %22, %23, %24, %25, %26, %27}, %28, %29, p, 1, 1, 0, 1;\n}"
    : "+f"(d[0]), "+f"(d[1]), "+f"(d[2]), "+f"(d[3]), "+f"(d[4]), "+f"(d[5]), "+f"(d[6]), "+f"(d[7]), "+f"(d[8]), "+f"(d[9]), "+f"(d[10]), "+f"(d[11]), "+f"(d[12]), "+f"(d[13]), "+f"(d[14]), "+f"(d[15]), "+f"(d[16]), "+f"(d[17]), "+f"(d[18]), "+f"(d[19]), "+f"(d[20]), "+f"(d[21]), "+f"(d[22]), "+f"(d[23]), "+f"(d[24]), "+f"(d[25]), "+f"(d[26]), "+f"(d[27])
    : "l"(da), "l"(db), "r"(acc));
}
__device__ __forceinline__ void wg_ss64_tab(float (&d)[32], uint64_t da, uint64_t db, int acc) {
  asm volatile("{\n.reg .pred p;\nsetp.ne.b32 p, %34, 0;\nwgmma.mma_async.sync.aligned.m64n64k16.f32.bf16.bf16 {%0, %1, %2, %3, %4, %5, %6, %7, %8, %9, %10, %11, %12, %13, %14, %15, %16, %17, %18, %19, %20, %21, %22, %23, %24, %25, %26, %27, %28, %29, %30, %31}, %32, %33, p, 1, 1, 1, 1;\n}"
    : "+f"(d[0]), "+f"(d[1]), "+f"(d[2]), "+f"(d[3]), "+f"(d[4]), "+f"(d[5]), "+f"(d[6]), "+f"(d[7]), "+f"(d[8]), "+f"(d[9]), "+f"(d[10]), "+f"(d[11]), "+f"(d[12]), "+f"(d[13]), "+f"(d[14]), "+f"(d[15]), "+f"(d[16]), "+f"(d[17]), "+f"(d[18]), "+f"(d[19]), "+f"(d[20]), "+f"(d[21]), "+f"(d[22]), "+f"(d[23]), "+f"(d[24]), "+f"(d[25]), "+f"(d[26]), "+f"(d[27]), "+f"(d[28]), "+f"(d[29]), "+f"(d[30]), "+f"(d[31])
    : "l"(da), "l"(db), "r"(acc));
}
__device__ __forceinline__ void wg_ss64_ta(float (&d)[32], uint64_t da, uint64_t db, int acc) {
  asm volatile("{\n.reg .pred p;\nsetp.ne.b32 p, %34, 0;\nwgmma.mma_async.sync.aligned.m64n64k16.f32.bf16.bf16 {%0, %1, %2, %3, %4, %5, %6, %7, %8, %9, %10, %11, %12, %13, %14, %15, %16, %17, %18, %19, %20, %21, %22, %23, %24, %25, %26, %27, %28, %29, %30, %31}, %32, %33, p, 1, 1, 1, 0;\n}"
    : "+f"(d[0]), "+f"(d[1]), "+f"(d[2]), "+f"(d[3]), "+f"(d[4]), "+f"(d[5]), "+f"(d[6]), "+f"(d[7]), "+f"(d[8]), "+f"(d[9]), "+f"(d[10]), "+f"(d[11]), "+f"(d[12]), "+f"(d[13]), "+f"(d[14]), "+f"(d[15]), "+f"(d[16]), "+f"(d[17]), "+f"(d[18]), "+f"(d[19]), "+f"(d[20]), "+f"(d[21]), "+f"(d[22]), "+f"(d[23]), "+f"(d[24]), "+f"(d[25]), "+f"(d[26]), "+f"(d[27]), "+f"(d[28]), "+f"(d[29]), "+f"(d[30]), "+f"(d[31])
    : "l"(da), "l"(db), "r"(acc));
}
__device__ __forceinline__ void wg_fence() { asm volatile("wgmma.fence.sync.aligned;" ::: "memory"); }
__device__ __forceinline__ void wg_commit() { asm volatile("wgmma.commit_group.sync.aligned;" ::: "memory"); }
__device__ __forceinline__ void wg_wait0() { asm volatile("wgmma.wait_group.sync.aligned 0;" ::: "memory"); }
__device__ __forceinline__ uint64_t make_desc(uint32_t addr, uint32_t lbo, uint32_t sbo, uint32_t swz) {
  return (uint64_t)((addr & 0x3FFFF) >> 4) | ((uint64_t)(lbo >> 4) << 16) | ((uint64_t)(sbo >> 4) << 32) | ((uint64_t)swz << 62);
}
__device__ __forceinline__ void tma2d(uint32_t dst, const CUtensorMap* m, int c0, int c1, uint32_t bar) {
  asm volatile("cp.async.bulk.tensor.2d.shared::cluster.global.mbarrier::complete_tx::bytes [%0], [%1, {%3, %4}], [%2];" :: "r"(dst), "l"(m), "r"(bar), "r"(c0), "r"(c1) : "memory"); }
__device__ __forceinline__ void tma3d(uint32_t dst, const CUtensorMap* m, int c0, int c1, int c2, uint32_t bar) {
  asm volatile("cp.async.bulk.tensor.3d.shared::cluster.global.mbarrier::complete_tx::bytes [%0], [%1, {%3, %4, %5}], [%2];" :: "r"(dst), "l"(m), "r"(bar), "r"(c0), "r"(c1), "r"(c2) : "memory"); }
__device__ __forceinline__ void mbar_init(uint32_t bar, int cnt) { asm volatile("mbarrier.init.shared::cta.b64 [%0], %1;" :: "r"(bar), "r"(cnt)); }
__device__ __forceinline__ void mbar_arrive(uint32_t bar) { asm volatile("mbarrier.arrive.shared::cta.b64 _, [%0];" :: "r"(bar) : "memory"); }

#define K0_LAG 3500
#define K0_LAG2 700
__device__ __noinline__ void code_anchor() { asm volatile(""); }
__device__ unsigned long long g_dbg;
#define K0_GRID 129
#define K0_SMEM (57344 + 5 * 32768 + 1024 + 128)
__global__ void __launch_bounds__(640, 1) k0_prep(const __grid_constant__ CUtensorMap mWq, const __grid_constant__ CUtensorMap mWk, const __grid_constant__ CUtensorMap mWv,
                                                  const __grid_constant__ CUtensorMap mWo, const bf16* __restrict__ x, const bf16* __restrict__ mem0, const bf16* __restrict__ gate_w) {
  extern __shared__ unsigned char smem_raw[];
  __shared__ unsigned s_max[2];
  const uint32_t sb = __shfl_sync(0xffffffffu, (smem_u32(smem_raw) + 1023) & ~1023u, 0);
  const uint32_t sB = sb, sA = sb + 57344, bars = sb + 57344 + 5 * 32768;
  const int cta = blockIdx.x, mat = cta >> 6, h = (cta >> 2) & 15, q = cta & 3;
  const int tid = threadIdx.x, wg = __shfl_sync(0xffffffffu, tid >> 7, 0), warp = __shfl_sync(0xffffffffu, (tid >> 5) & 3, 0), lane = tid & 31;
  asm volatile("griddepcontrol.launch_dependents;" ::: "memory");
  if (cta == 128) {
    if (tid < 512) {
      uint32_t a = 0;
#pragma unroll
      for (int i = 0; i < 14; i++) { const uint4 v = ((const uint4*)mem0)[i * 32 + lane]; a = amax2(amax2(a, v.x, v.y), v.z, v.w); }
      a = __reduce_max_sync(0xffffffffu, max(a & 0xffffu, a >> 16));
      const int se = min(max(15 - (expo(__uint_as_float(a << 16)) + 1), -40), 40);
      const float sc = pow2i(se);
      if (tid == 0) g_inv0 = pow2i(-se);
      const int vec = tid >> 5, jj = vec >> 2, qq = vec & 3;
      const int nt0 = NT0(qq), nt2 = NT2(qq), nts = NTS(qq);
      const bf16* r = mem0 + (lane >> 2) * DM + jj * 112 + (lane & 3) * 2;
      auto val = [&](int nt, int e2) { return b2f(r[nt * 8 + e2]) * sc; };
      *acc_ptr(0, vec, lane, 0) = *acc_ptr(0, vec, lane, 1) = make_uint4(pack_f16(val(nt0, 0), val(nt0, 1)), pack_f16(val(nt0 + 1, 0), val(nt0 + 1, 1)), pack_f16(val(nt2, 0), val(nt2, 1)), pack_f16(val(nts, qq & 1), 16.f));
    }
    return;
  }
  auto load_tile = [&](int i, int ln) {
    const int t = i;
    const uint32_t dst = sA + (i % 5) * 32768, bar = bars + 8 * i;
    if (ln == 0) arm_bar(bar, 32768);
    __syncwarp();
    if (mat == 0) {
      if (ln < 8) {
        const int gam = t * 8 + ln, tau = gam >> 1, sg = gam & 1, jj = tau / 7, f = tau % 7;
        const int row = 112 * jj + (f < 6 ? ((f & ~1) + sg) * 16 + (f & 1) * 8 : 96 + sg * 8);
        tma3d(dst + ln * 4096, &mWq, 0, row, 4 * h, bar);
      }
    } else if (ln == 0) tma2d(dst, &mWo, t * 64, h * 256, bar);
  };
  if (tid == 0) TLS(cta);
  if (wg >= 3) {
    const int t2 = tid - 384, seg = cta >> 1;
    uint4 xv[7];
    const uint4* xs = (const uint4*)(x + seg * 32 * DM);
#pragma unroll
    for (int i = 0; i < 7; i++) xv[i] = xs[i * 256 + t2];
    if (t2 == 0) s_max[0] = 0;
    for (int i = cta * 528 + t2; i < cta * 528 + 528; i += 256) if (!(i < 2048 && ((i >> 5) & 1) == 0)) g_ACC16[i] = make_uint4(0, 0, 0, 0);
    if (t2 < 8) g_ready[cta * 8 + t2] = 0;
    if (t2 == 8 && cta < NSEG) g_rdone[cta] = 0;
    g_kv[cta * 256 + t2] = 0.f;
    if (t2 == 9 && cta < 16) g_a2done[cta] = 0;
    if (t2 == 10 && cta == 0) { g_a1done[0] = 0; g_job[0] = 0; }
    BAR_SYNC(6, 256);
    uint32_t a = 0;
#pragma unroll
    for (int i = 0; i < 7; i++) a = amax2(amax2(a, xv[i].x, xv[i].y), xv[i].z, xv[i].w);
    a = __reduce_max_sync(0xffffffffu, max(a & 0xffffu, a >> 16));
    if (lane == 0) atomicMax(&s_max[0], a << 16);
    uint4 v[4];
#pragma unroll
    for (int it = 0; it < 4; it++) {
      const int i = min((cta & 1) * 896 + it * 256 + t2, (cta & 1) * 896 + 895);
      int l = i & 31, r = i >> 5, mm = r & 1; r >>= 1; int f = r % 7, jj = r / 7;
      int c0 = f == 6 ? 96 : (f & ~1) * 16 + (f & 1) * 8, c1 = f == 6 ? 104 : (f | 1) * 16 + (f & 1) * 8;
      const bf16* r0 = x + (seg * 32 + mm * 16 + (l >> 2)) * DM + jj * 112 + (l & 3) * 2;
      const bf16* r1 = r0 + 8 * DM;
      v[it] = make_uint4(*(const uint32_t*)(r0 + c0), *(const uint32_t*)(r1 + c0), *(const uint32_t*)(r0 + c1), *(const uint32_t*)(r1 + c1));
    }
#pragma unroll
    for (int rr = 0; rr < 2; rr++) {
      const int t = cta * 16 + (t2 >> 5) * 2 + rr; float acc = 0.f;
#pragma unroll
      for (int k = 0; k < 7; k++) { uint32_t xw = ((const uint32_t*)(x + t * DM))[k * 32 + lane], gv = ((const uint32_t*)gate_w)[k * 32 + lane]; acc += bf_lo(xw) * bf_lo(gv) + bf_hi(xw) * bf_hi(gv); }
#pragma unroll
      for (int o = 16; o; o >>= 1) acc += __shfl_xor_sync(0xffffffffu, acc, o);
      if (lane == 0) g_gate[t] = 1.f / (1.f + __expf(-acc));
    }
    BAR_SYNC(6, 256);
    const float xm = __uint_as_float(s_max[0]);
    const float xsc = pow2i(seg_sx(xm));
#pragma unroll
    for (int it = 0; it < 4; it++) if (it * 256 + t2 < 896) g_XF[seg * 1792 + (cta & 1) * 896 + it * 256 + t2] = bf8_to_h8(v[it], xsc);
    if (t2 == 0) g_xmax[seg] = xm;
    if (t2 == 0 && (cta & 63) == 5) TLS(820 + mat * 32);
    return;
  }
  if (tid == 0) { for (int i = 0; i < 8; i++) mbar_init(bars + 8 * i, 1); asm volatile("fence.mbarrier_init.release.cluster;" ::: "memory"); s_max[1] = 0; }
  BAR_SYNC(7, 384);
  if (tid < 32) {
    if (lane == 0) arm_bar(bars + 56, 57344);
    __syncwarp();
    if (lane < 14) tma3d(sB + lane * 4096, mat ? &mWv : &mWk, 0, q * 112 + lane * 8, 4 * h, bars + 56);
    load_tile(0, lane);
  } else if (wg == 2) { lag(K0_LAG + warp * K0_LAG2); load_tile(1 + warp, lane); }
  wait_bar1(bars + 56, 0);
  if (tid == 0 && (cta & 63) == 5) TLS(800 + mat * 32);
  uint32_t bm = 0;
#pragma unroll 1
  for (int i = wg; i < 7; i += 3) {
    const int t = i;
    wait_bar1(bars + 8 * i, 0);
    if ((tid & 127) == 0 && (cta & 63) == 5) TLS(801 + mat * 32 + i);
    float d[56];
    const uint32_t at = sA + (i % 5) * 32768;
    const uint64_t db = make_desc(sB, 16, 4096, 1);
    if (mat == 0) {
      const uint64_t da = make_desc(at, 16, 4096, 1);
      wg_fence();
#pragma unroll
      for (int ks = 0; ks < 16; ks++) { const uint64_t o = (uint64_t)(((ks >> 2) * 1024 + (ks & 3) * 32) >> 4); wg_ss112(d, da + o, db + o, ks); }
      wg_commit(); wg_wait0();
    } else {
      const uint64_t da = make_desc(at, 16, 1024, 1);
      wg_fence();
#pragma unroll
      for (int ks = 0; ks < 16; ks++) { const uint64_t o = (uint64_t)(((ks >> 2) * 1024 + (ks & 3) * 32) >> 4); wg_ss112_ta(d, da + (uint64_t)(ks * 128), db + o, ks); }
      wg_commit(); wg_wait0();
    }
    if ((tid & 127) == 0 && (cta & 63) == 5) TLS(810 + mat * 32 + i);
    if (i < 2) { BAR_SYNC_R(1 + wg, 128); if (warp == 0) load_tile(i + 5, lane); }
    const float sc = mat ? 1.f : 0.0625f;
    uint4* dst = (uint4*)wf_ptr(mat * NH + h, 4 * t + warp, 7 * q, lane);
    const int T64 = (mat * NH + h) * 7 + t;
    const bool ss = T64 % 5 >= 3;
    uint32_t* ds = g_WS + (T64 * 28 + 7 * q) * 512 + warp * 64 + lane;
#pragma unroll
    for (int k = 0; k < 7; k++) {
      uint4 v = make_uint4(pack_bf16(d[8 * k] * sc, d[8 * k + 1] * sc), pack_bf16(d[8 * k + 2] * sc, d[8 * k + 3] * sc), pack_bf16(d[8 * k + 4] * sc, d[8 * k + 5] * sc), pack_bf16(d[8 * k + 6] * sc, d[8 * k + 7] * sc));
      dst[k * 32] = v;
      if (ss) { ds[k * 512] = v.x; ds[k * 512 + 32] = v.y; ds[k * 512 + 256] = v.z; ds[k * 512 + 288] = v.w; }
      bm = amax2(amax2(bm, v.x, v.y), v.z, v.w);
    }
  }
  bm = __reduce_max_sync(0xffffffffu, max(bm & 0xffffu, bm >> 16));
  if (lane == 0) atomicMax(&s_max[1], bm << 16);
  BAR_SYNC(7, 384);
  if (tid == 0) TLS(128 + cta);
  if (tid == 0) g_wmax[cta] = __uint_as_float(s_max[1]);
}

#define G_LAG 2500
#define G_CTAS 45
#define X_CTAS 48
#define G_SMEM (4 * 57344 + 1024 + 512)
__device__ __forceinline__ void wait_go() {
#pragma unroll 1
  for (int it = 0; it < SPIN_LIMIT; it++) { unsigned v; asm volatile("ld.acquire.gpu.global.u32 %0, [%1];" : "=r"(v) : "l"(g_go) : "memory"); if (v) return; }
  g_err = 4;
}
__device__ __forceinline__ void g_store(const float* d, int T, int seg, int warp, int lane, float ksc) {
  const int mh = T / 7, t16 = (T % 7) * 4 + warp, h = mh & 15;
  if (mh < NH) {
    uint2* dst = g_KF + (((seg * NH + h) * 4) * 28 + t16) * 32 + lane;
#pragma unroll
    for (int kg = 0; kg < 4; kg++) dst[kg * 28 * 32] = make_uint2(movm(pack_f16(d[4 * kg] * ksc, d[4 * kg + 1] * ksc)), movm(pack_f16(d[4 * kg + 2] * ksc, d[4 * kg + 3] * ksc)));
  } else {
    uint4* dst = g_VF + ((seg * NH + h) * 56 + t16 * 2) * 32 + lane;
    dst[0] = make_uint4(pack_bf16(d[0], d[1]), pack_bf16(d[4], d[5]), pack_bf16(d[8], d[9]), pack_bf16(d[12], d[13]));
    dst[32] = make_uint4(pack_bf16(d[2], d[3]), pack_bf16(d[6], d[7]), pack_bf16(d[10], d[11]), pack_bf16(d[14], d[15]));
  }
}
__device__ __forceinline__ void flag_add(unsigned* p, unsigned v) { asm volatile("red.release.gpu.global.add.u32 [%0], %1;" :: "l"(p), "r"(v) : "memory"); }

__global__ void __launch_bounds__(512, 1) g_kernel(const __grid_constant__ CUtensorMap mX) {
  extern __shared__ unsigned char smem_raw[];
  asm volatile("griddepcontrol.launch_dependents;" ::: "memory");
  const uint32_t sb = __shfl_sync(0xffffffffu, (smem_u32(smem_raw) + 1023) & ~1023u, 0);
  const uint32_t sX = sb, sW = sb + 2 * 57344, bars = sb + 4 * 57344;
  const int tid = threadIdx.x, wg = __shfl_sync(0xffffffffu, tid >> 7, 0), warp = __shfl_sync(0xffffffffu, (tid >> 5) & 3, 0), lane = tid & 31;
  const int T0 = blockIdx.x * 5;
  if (tid == 0 && blockIdx.x == 0) TLS(330);
  auto load_stage = [&](int n) {
    const uint32_t bar = bars + 8 * (n & 1);
    arm_bar(bar, 57344);
#pragma unroll
    for (int c = 0; c < 7; c++) tma2d(sX + (n & 1) * 57344 + c * 8192, &mX, c * 64, n * 64, bar);
  };
  if (tid == 0) {
    for (int i = 0; i < 2; i++) { mbar_init(bars + 8 * i, 1); mbar_init(bars + 16 + 8 * i, 12); }
    asm volatile("fence.mbarrier_init.release.cluster;" ::: "memory");
    mbar_init(bars + 32, 1);
    asm volatile("fence.mbarrier_init.release.cluster;" ::: "memory");
    load_stage(0);
    wait_go();
  }
  __syncthreads();
  if (wg < 3) {
    asm volatile("setmaxnreg.inc.sync.aligned.u32 160;");
    const int T = T0 + wg;
    const uint4* wsrc = g_WF + ((T * 4 + warp) * 28) * 32 + lane;
    uint4 W[24];
#pragma unroll
    for (int ks = 0; ks < 24; ks++) W[ks] = wf_ld(wsrc + ks * 32);
    const float ksc = pow2i(get_scales().sk);
    int rot = wg;
#pragma unroll 1
    for (int n = 0; n < NSEG / 2; n++) {
      const uint64_t db0 = make_desc(sX + (n & 1) * 57344, 16, 1024, 1);
      const int Ts = T0 + 3 + rot;
      {
        uint4 X[4];
#pragma unroll
        for (int i = 0; i < 4; i++) asm volatile("ld.global.v4.u32 {%0,%1,%2,%3}, [%4];" : "=r"(X[i].x), "=r"(X[i].y), "=r"(X[i].z), "=r"(X[i].w) : "l"(wsrc + (24 + i) * 32));
        wait_bar1(bars + 8 * (n & 1), (n >> 1) & 1);
#pragma unroll
        for (int hf = 0; hf < 2; hf++) {
          float d[16];
          const uint64_t db = db0 + (uint64_t)(hf * 256);
          wg_fence();
#pragma unroll
          for (int ks = 0; ks < 24; ks++) wg_rs32(d, W[ks], db + (uint64_t)(((ks >> 2) * 8192 + (ks & 3) * 32) >> 4), ks);
          if (hf == 0) wg_fence();
#pragma unroll
          for (int ks = 24; ks < 28; ks++) wg_rs32(d, X[ks - 24], db + (uint64_t)(((ks >> 2) * 8192 + (ks & 3) * 32) >> 4), ks);
          wg_commit(); wg_wait0();
          if (hf == 1 && !(rot < 2 && Ts < 224) && lane == 0) mbar_arrive(bars + 16 + 8 * (n & 1));
          g_store(d, T, 2 * n + hf, warp, lane, ksc);
        }
      }
      if (n < 2) wait_bar1(bars + 32, 0);
      if (rot < 2 && Ts < 224) {
        float d[32];
        const uint64_t da = make_desc(sW + rot * 57344, 1024, 128, 0);
        wg_fence();
#pragma unroll
        for (int ks = 0; ks < 28; ks++) wg_ss64(d, da + (uint64_t)(ks * 128), db0 + (uint64_t)(((ks >> 2) * 8192 + (ks & 3) * 32) >> 4), ks);
        wg_commit(); wg_wait0();
        if (lane == 0) mbar_arrive(bars + 16 + 8 * (n & 1));
        g_store(d, Ts, 2 * n, warp, lane, ksc); g_store(d + 16, Ts, 2 * n + 1, warp, lane, ksc);
      }
      if (n >= 2) BAR_SYNC_R(7 + wg * 2 + (n & 1), 160);
      BAR_ARRIVE_R(1 + wg * 2 + (n & 1), 160);
      rot = rot == 2 ? 0 : rot + 1;
    }
  } else {
    asm volatile("setmaxnreg.dec.sync.aligned.u32 32;");
    if (tid == 384 && blockIdx.x == 0) TLS(870);
    if (warp < 3) {
      const int T = T0 + warp;
      int rot = warp;
#pragma unroll 1
      for (int n = 0; n < NSEG / 2; n++) {
        BAR_SYNC_R(1 + warp * 2 + (n & 1), 160);
        if (n + 2 < NSEG / 2) BAR_ARRIVE_R(7 + warp * 2 + (n & 1), 160);
        if (elect1()) {
          __threadfence();
          atomicAdd(&g_ready[n * NH + ((T / 7) & 15)], 1);
          if (blockIdx.x == 0 && warp == 0) TLS(331 + n);
          const int Ts = T0 + 3 + rot;
          if (rot < 2 && Ts < 224) atomicAdd(&g_ready[n * NH + ((Ts / 7) & 15)], 1);
        }
        __syncwarp();
        rot = rot == 2 ? 0 : rot + 1;
      }
    } else if (elect1()) {
      lag(G_LAG);
      asm volatile("fence.proxy.async.global;" ::: "memory");
      arm_bar(bars + 32, 114688);
      bulk_g2s(sW, g_WS + (T0 + 3) * 28 * 512, 57344, bars + 32); bulk_g2s(sW + 57344, g_WS + min(T0 + 4, 223) * 28 * 512, 57344, bars + 32);
      lag(2000);
      load_stage(1);
#pragma unroll 1
      for (int n = 2; n < NSEG / 2; n++) { wait_bar1(bars + 16 + 8 * (n & 1), ((n - 2) >> 1) & 1); load_stage(n); }
    }
  }
}

#define X3_SMEM (28672 + 40960 + 16384 + 64)
__device__ __forceinline__ unsigned ld_acquire(const unsigned* p) { unsigned v; asm volatile("ld.acquire.gpu.global.u32 %0, [%1];" : "=r"(v) : "l"(p) : "memory"); return v; }
__device__ __forceinline__ void wait_flags(const unsigned* p, int n, unsigned want) {
  const int lane = threadIdx.x & 31;
#pragma unroll 1
  for (int it = 0; it < SPIN_LIMIT; it++) {
    const bool ok = lane >= n || ld_acquire(p + lane) >= want;
    if (__all_sync(0xffffffffu, ok)) return;
    __nanosleep(100);
  }
  g_err = 3;
}
__device__ __forceinline__ uint4 ldg128(const uint4* p) { uint4 v; asm volatile("ld.global.v4.u32 {%0,%1,%2,%3}, [%4];" : "=r"(v.x), "=r"(v.y), "=r"(v.z), "=r"(v.w) : "l"(p) : "memory"); return v; }
__device__ __forceinline__ uint2 ldg64(const uint2* p) { uint2 v; asm volatile("ld.global.v2.u32 {%0,%1}, [%2];" : "=r"(v.x), "=r"(v.y) : "l"(p) : "memory"); return v; }
__device__ __forceinline__ uint32_t ldg32(const uint32_t* p) { uint32_t v; asm volatile("ld.global.u32 %0, [%1];" : "=r"(v) : "l"(p) : "memory"); return v; }

__device__ __forceinline__ void mix_store(const float* d, const uint4 f0, const uint4 f1, bf16* __restrict__ out, int seg, int t16, int lane) {
  const uint32_t fa[8] = {f0.x, f0.y, f0.z, f0.w, f1.x, f1.y, f1.z, f1.w};
  uint32_t* op = (uint32_t*)(out + (seg * 32 + (lane >> 2)) * DM + t16 * 16 + (lane & 3) * 2);
#pragma unroll
  for (int i = 0; i < 4; i++) {
    const uint32_t lo = movm(pack_bf16(d[4 * i] + bf_lo(fa[2 * i]), d[4 * i + 1] + bf_hi(fa[2 * i])));
    const uint32_t hi = movm(pack_bf16(d[4 * i + 2] + bf_lo(fa[2 * i + 1]), d[4 * i + 3] + bf_hi(fa[2 * i + 1])));
    op[i * 8 * DM / 2] = lo; op[i * 8 * DM / 2 + 4] = hi;
  }
}
__device__ __forceinline__ void frag_store(const float* e, int seg, int t16, int lane) {
  uint4* af = g_AF + ((seg * 28 + t16) * 2) * 32 + lane;
  af[0] = make_uint4(pack_bf16(e[0], e[1]), pack_bf16(e[2], e[3]), pack_bf16(e[4], e[5]), pack_bf16(e[6], e[7]));
  af[32] = make_uint4(pack_bf16(e[8], e[9]), pack_bf16(e[10], e[11]), pack_bf16(e[12], e[13]), pack_bf16(e[14], e[15]));
}
#define SEG_REV 40
__device__ __forceinline__ void x3_job(uint32_t sb, uint32_t bars, int seg, int t0, int t1, bf16* __restrict__ out) {
  const int tid = threadIdx.x, w = __shfl_sync(0xffffffffu, tid >> 5, 0), lane = tid & 31, g = lane >> 2, tq = lane & 3;
  const uint32_t sP = sb, sRing = sb + 40960;
  float gate[4];
#pragma unroll
  for (int tg = 0; tg < 4; tg++) gate[tg] = 1.f - __ldcg(g_gate + seg * 32 + tg * 8 + g);
  const int wg = w >> 2, warp = w & 3;
  const uint32_t vring = sRing + wg * 43008, vbar = bars + 416 + wg * 16;
  auto load_v = [&](int buf, int tile, int hq, bool with_arm) {
    if (with_arm) arm_bar(vbar + buf * 8, 20480);
#pragma unroll
    for (int i = 0; i < 4; i++) bulk_g2s(vring + buf * 20480 + i * 4096, g_VF + ((seg * NH + hq * 4 + i) * 56 + tile * 8) * 32, 4096, vbar + buf * 8);
  };
  auto load_u = [&](int buf, int tile, int hq) {
#pragma unroll
    for (int i = 0; i < 4; i++) bulk_g2s(vring + buf * 20480 + 16384 + i * 1024, g_UF + ((seg * NH + hq * 4 + i) * 56 + tile * 8) * 32, 1024, vbar + buf * 8);
  };
  if (tid == 0 && seg == 5) TLS(901);
  const bool act = t0 + wg < t1, lead = (tid & 127) == 0;
  if (warp == 0) {
    wait_flags(g_ready + (seg >> 1) * NH, NH, 14);
    if (act && lead) { asm volatile("fence.proxy.async.global;" ::: "memory"); load_v(0, t0 + wg, 0, true); load_v(1, t0 + wg, 1, true); }
  }
  if (w == 2) wait_flags(g_rdone + seg, 1, 64);
  if (w == 1 && seg >= SEG_REV) wait_flags(g_a2done + (seg >> 2), 1, 1);
  __syncthreads();
  if (act && lead) { asm volatile("fence.proxy.async.global;" ::: "memory"); load_u(0, t0 + wg, 0); load_u(1, t0 + wg, 1); }
  if (tid == 0 && seg == 5) TLS(902);
  {
    const float LOG2E = 1.4426950408889634f;
#pragma unroll
    for (int m = 0; m < 2; m++) {
      float sm_[4];
      uint4 sxx[4];
      {
        const uint4* p = (const uint4*)g_SXM + (((seg * NH + w) * 4) * 4 + m) * 32 + lane;
        uint4 t0_ = ldg128(p), t1_ = ldg128(p + 128), t2_ = ldg128(p + 256), t3_ = ldg128(p + 384);
#pragma unroll
        for (int kg = 0; kg < 4; kg++) if (kg < 2 + 2 * m) sxx[kg] = ldg128(p + kg * 128 + 64);
        sm_[0] = (__uint_as_float(t0_.x) + __uint_as_float(t1_.x)) + (__uint_as_float(t2_.x) + __uint_as_float(t3_.x));
        sm_[1] = (__uint_as_float(t0_.y) + __uint_as_float(t1_.y)) + (__uint_as_float(t2_.y) + __uint_as_float(t3_.y));
        sm_[2] = (__uint_as_float(t0_.z) + __uint_as_float(t1_.z)) + (__uint_as_float(t2_.z) + __uint_as_float(t3_.z));
        sm_[3] = (__uint_as_float(t0_.w) + __uint_as_float(t1_.w)) + (__uint_as_float(t2_.w) + __uint_as_float(t3_.w));
      }
#pragma unroll
      for (int hf = 0; hf < 2; hf++) {
        const int tg = m * 2 + hf;
        float v[10];
        v[0] = sm_[hf * 2]; v[1] = sm_[hf * 2 + 1];
        float mx = fmaxf(v[0], v[1]);
#pragma unroll
        for (int kg = 0; kg < 4; kg++) if (kg <= tg) {
          float a = __uint_as_float(hf ? sxx[kg].z : sxx[kg].x), b = __uint_as_float(hf ? sxx[kg].w : sxx[kg].y);
          if (kg == tg) { if (tq * 2 > g) a = -INFINITY; if (tq * 2 + 1 > g) b = -INFINITY; }
          v[2 + 2 * kg] = a; v[3 + 2 * kg] = b; mx = fmaxf(mx, fmaxf(a, b));
        }
        mx = fmaxf(mx, __shfl_xor_sync(0xffffffffu, mx, 1)); mx = fmaxf(mx, __shfl_xor_sync(0xffffffffu, mx, 2));
        mx *= LOG2E;
        float z = 0.f;
#pragma unroll
        for (int i = 0; i < 10; i++) if (i < 4 + 2 * tg) { v[i] = ex2(fmaf(v[i], LOG2E, -mx)); z += v[i]; }
        z += __shfl_xor_sync(0xffffffffu, z, 1); z += __shfl_xor_sync(0xffffffffu, z, 2);
        const float sc = __fdividef(gate[tg], z);
        const uint32_t pa = sP + tg * 128 + lane * 4;
        sts32(pa + (32 + (w >> 1)) * 1024 + (w & 1) * 512, pack_bf16(v[0] * sc, v[1] * sc));
#pragma unroll
        for (int kg = 0; kg < 4; kg++) sts32(pa + (2 * w + (kg >> 1)) * 1024 + (kg & 1) * 512, kg <= tg ? pack_bf16(v[2 + 2 * kg] * sc, v[3 + 2 * kg] * sc) : 0u);
      }
    }
  }
  asm volatile("fence.proxy.async.shared::cta;" ::: "memory");
  __syncthreads();
  if (tid == 0 && seg == 5) TLS(903);
#pragma unroll 1
  for (int tile = t0 + wg; tile < t1; tile += 4) {
    const uint64_t db = make_desc(sP + (tile & 0x4000), 512, 128, 0);
    float d[16];
    uint4 f0, f1;
    if (seg >= SEG_REV) { const uint4* af = g_AF + ((seg * 28 + tile * 4 + warp) * 2) * 32 + lane; f0 = ldg128(af); f1 = ldg128(af + 32); }
#pragma unroll
    for (int hq = 0; hq < 4; hq++) {
      wait_bar1(vbar + (hq & 1) * 8, (hq >> 1) & 1);
      const uint32_t vb = vring + (hq & 1) * 20480;
      uint4 A[8], U[2];
#pragma unroll
      for (int i = 0; i < 4; i++) {
        const uint4 x0 = lds128(vb + i * 4096 + warp * 1024 + lane * 16), x1 = lds128(vb + i * 4096 + warp * 1024 + 512 + lane * 16);
        A[2 * i] = make_uint4(x0.x, x1.x, x0.y, x1.y); A[2 * i + 1] = make_uint4(x0.z, x1.z, x0.w, x1.w);
      }
#pragma unroll
      for (int i = 0; i < 2; i++) { const uint32_t u = vb + 16384 + i * 2048 + warp * 256 + lane * 4; U[i] = make_uint4(lds32(u), lds32(u + 128), lds32(u + 1024), lds32(u + 1152)); }
      wg_fence();
#pragma unroll
      for (int i = 0; i < 8; i++) wg_rs32(d, A[i], db + (uint64_t)((hq * 8 + i) * 64), hq | i);
#pragma unroll
      for (int i = 0; i < 2; i++) wg_rs32(d, U[i], db + (uint64_t)((32 + hq * 2 + i) * 64), 1);
      wg_commit();
      BAR_SYNC_R(1 + wg, 128);
      if (lead) {
        if (hq < 2) { load_v(hq & 1, tile, hq + 2, true); load_u(hq & 1, tile, hq + 2); }
        else if (tile + 4 < t1) { load_v(hq & 1, tile + 4, hq - 2, true); load_u(hq & 1, tile + 4, hq - 2); }
      }
      __syncwarp();
      wg_wait0();
    }
    if (seg < SEG_REV) frag_store(d, seg, tile * 4 + warp, lane);
    else mix_store(d, f0, f1, out, seg, tile * 4 + warp, lane);
  }
  if (tid == 0 && seg == 5) TLS(904);
  if (seg < SEG_REV) { __syncthreads(); if (tid == 0) { __threadfence(); atomicAdd(&g_a2done[seg >> 2], 1); } }
}

__device__ __forceinline__ void phi_map(const float (&acc)[28], int hb, uint32_t sF, int lane, uint32_t (&ph)[16]) {
  const int tq = lane & 3;
  float p[4][4];
  uint32_t a[14];
#pragma unroll
  for (int i = 0; i < 14; i++) a[i] = pack_bf16(acc[2 * i], acc[2 * i + 1]);
  if (hb == 0) {
#pragma unroll
    for (int nt = 0; nt < 4; nt++) {
      const uint4 b = lds128(sF + nt * 512 + lane * 16);
      mma_z(p[nt], a[0], a[1], a[2], a[3], b.x, b.y); mma16816(p[nt], a[4], a[5], a[6], a[7], b.z, b.w);
    }
  } else {
#pragma unroll
    for (int nt = 0; nt < 4; nt++) {
      const uint4 b = lds128(sF + 2048 + nt * 512 + lane * 16);
      mma_z(p[nt], a[6], a[7], a[8], a[9], b.x, b.y); mma16816(p[nt], a[10], a[11], a[12], a[13], b.z, b.w);
    }
  }
  const float LOG2E = 1.4426950408889634f;
#pragma unroll
  for (int hf = 0; hf < 2; hf++) {
    float v[8]; float mx = -INFINITY, mn = INFINITY;
#pragma unroll
    for (int i = 0; i < 8; i++) {
      v[i] = p[i >> 1][hf * 2 + (i & 1)] * LOG2E;
      if (i < 6 || tq < 2) { mx = fmaxf(mx, v[i]); mn = fminf(mn, v[i]); }
    }
    mx = fmaxf(mx, __shfl_xor_sync(0xffffffffu, mx, 1)); mx = fmaxf(mx, __shfl_xor_sync(0xffffffffu, mx, 2));
    mn = fminf(mn, __shfl_xor_sync(0xffffffffu, mn, 1)); mn = fminf(mn, __shfl_xor_sync(0xffffffffu, mn, 2));
    float e1[8], e2[8], z1 = 0.f, z2 = 0.f;
#pragma unroll
    for (int i = 0; i < 8; i++) {
      const bool ok = i < 6 || tq < 2;
      e1[i] = ok ? ex2(v[i] - mx) : 0.f; e2[i] = ok ? ex2(mn - v[i]) : 0.f; z1 += e1[i]; z2 += e2[i];
    }
    z1 += __shfl_xor_sync(0xffffffffu, z1, 1); z1 += __shfl_xor_sync(0xffffffffu, z1, 2);
    z2 += __shfl_xor_sync(0xffffffffu, z2, 1); z2 += __shfl_xor_sync(0xffffffffu, z2, 2);
    z1 = __frcp_rn(z1); z2 = __frcp_rn(z2);
#pragma unroll
    for (int nt = 0; nt < 4; nt++) { ph[nt * 2 + hf] = pack_bf16(e1[2 * nt] * z1, e1[2 * nt + 1] * z1); ph[8 + nt * 2 + hf] = pack_bf16(e2[2 * nt] * z2, e2[2 * nt + 1] * z2); }
  }
}
__device__ __forceinline__ void a1_job(uint32_t sb, uint32_t bars, int rt, int half, const CUtensorMap* mX, const CUtensorMap* mW, const bf16* __restrict__ wphi) {
  const int tid = threadIdx.x, w = __shfl_sync(0xffffffffu, tid >> 5, 0);
  const int wg = w >> 2, warp = w & 3, mt = wg & 1, hp = wg >> 1;
  const uint32_t sX = sb, sW = sb + 114688 + hp * 49152, sF0 = sb + 114688 + 98304 + hp * 8192, wbar = bars + 32 + hp * 32;
  const bool lead = (tid & 255) == 0;
  if (tid == 0) {
    arm_bar(bars, 114688);
#pragma unroll
    for (int i = 0; i < 14; i++) tma2d(sX + i * 8192, mX, (i % 7) * 64, rt * 128 + (i / 7) * 64, bars);
  }
  auto load_w = [&](int pr, int c) {
    const uint32_t bar = wbar + 8 * (c & 3);
    arm_bar(bar, 12288);
#pragma unroll
    for (int i = 0; i < 3; i++) tma2d(sW + (c & 3) * 12288 + i * 4096, mW, i * 448 + pr * 56, c * 32, bar);
  };
  if (lead) { for (int c = 0; c < 4; c++) load_w(half * 2 + hp, c); }
#pragma unroll
  for (int u = 0; u < 1; u++) {
    const int lane = tid & 31, g = lane >> 2, tq = lane & 3;
    const int hb = mt, nt = warp, hh = (half * 2 + hp) * 2 + hb, f = nt * 8 + g;
    uint32_t r[4];
#pragma unroll
    for (int i = 0; i < 4; i++) {
      const int d0 = i * 8 + tq * 2 - (hb ? 4 : 0);
      const float lo = (f < 28 && d0 >= 0 && d0 < 28) ? b2f(wphi[(hh * 28 + d0) * 28 + f]) : 0.f, hi = (f < 28 && d0 + 1 >= 0 && d0 + 1 < 28) ? b2f(wphi[(hh * 28 + d0 + 1) * 28 + f]) : 0.f;
      r[i] = pack_bf16(lo, hi);
    }
    sts128(sF0 + u * 4096 + (w & 7) * 512 + lane * 16, r[0], r[1], r[2], r[3]);
  }
  {
    const int u = 0, pr = half * 2 + hp;
    const uint32_t sF = sF0 + u * 4096;
    float aq[28] = {}, ak[28] = {}, av[28] = {};
    if (u == 0) wait_bar1(bars, 0);
    if (lead && rt == 7 && half == 0) TLS(930 + hp * 8 + u * 4);
#pragma unroll 1
    for (int c = 0; c < 14; c++) {
      wait_bar1(wbar + 8 * (c & 3), ((c >> 2) + u * ((c & 3) < 2 ? 0 : 1)) & 1);
      const uint64_t da = make_desc(sX + (mt * 7 + (c >> 1)) * 8192 + (c & 1) * 64, 16, 1024, 1), db = make_desc(sW + (c & 3) * 12288, 16, 1024, 1);
      wg_fence();
#pragma unroll
      for (int ks = 0; ks < 2; ks++) {
        wg_ss56_tb(aq, da + (uint64_t)(ks * 2), db + (uint64_t)(ks * 128), c | ks);
        wg_ss56_tb(ak, da + (uint64_t)(ks * 2), db + (uint64_t)(ks * 128 + 256), c | ks);
        wg_ss56_tb(av, da + (uint64_t)(ks * 2), db + (uint64_t)(ks * 128 + 512), c | ks);
      }
      wg_commit();
      if (c >= 1 && c + 3 < 14) {
        asm volatile("wgmma.wait_group.sync.aligned 1;" ::: "memory");
        BAR_SYNC_R(1 + hp, 256);
        if (lead) load_w(pr, c + 3);
        __syncwarp();
      }
    }
    wg_wait0();
    if (lead && rt == 7 && half == 0) TLS(931 + hp * 8 + u * 4);
    BAR_SYNC_R(1 + hp, 256);
    int lane; asm volatile("mov.u32 %0, %%laneid;" : "=r"(lane)); const int g = lane >> 2, tq = lane & 3;
    const uint32_t sK = sW, sV = sW + 32768;
    const int row = mt * 64 + warp * 16 + g;
    {
      const uint32_t va = sV + row * 128 + tq * 4;
#pragma unroll
      for (int nt = 0; nt < 8; nt++) {
        const uint32_t lo = nt < 7 ? pack_bf16(av[4 * (nt % 7)], av[4 * (nt % 7) + 1]) : (tq == 0 ? 0x00003f80u : 0u), hi = nt < 7 ? pack_bf16(av[4 * (nt % 7) + 2], av[4 * (nt % 7) + 3]) : (tq == 0 ? 0x00003f80u : 0u);
        sts32(va + ((nt ^ g) << 4), lo); sts32(va + 1024 + ((nt ^ g) << 4), hi);
      }
    }
#pragma unroll 1
    for (int hb = 0; hb < 2; hb++) {
      uint32_t p[16];
      const uint32_t ka = sK + hb * 16384 + row * 128 + tq * 4;
      phi_map(ak, hb, sF, lane, p);
#pragma unroll
      for (int nt = 0; nt < 8; nt++) { sts32(ka + ((nt ^ g) << 4), p[2 * nt]); sts32(ka + 1024 + ((nt ^ g) << 4), p[2 * nt + 1]); }
      phi_map(aq, hb, sF, lane, p);
      uint4* pq = g_PQ + (((rt * 8 + mt * 4 + warp) * NH + pr * 2 + hb) * 4) * 32 + lane;
#pragma unroll
      for (int ks = 0; ks < 4; ks++) pq[ks * 32] = make_uint4(p[4 * ks], p[4 * ks + 1], p[4 * ks + 2], p[4 * ks + 3]);
    }
    asm volatile("fence.proxy.async.shared::cta;" ::: "memory");
    BAR_SYNC_R(1 + hp, 256);
    {
      if (lead && rt == 7 && half == 0) TLS(932 + hp * 8 + u * 4);
      float d[32] = {};
      const uint64_t db = make_desc(sK + mt * 16384 + (pr & 0x4000), 16, 1024, 1), da = make_desc(sV + (pr & 0x4000), 16, 1024, 1);
      wg_fence();
#pragma unroll
      for (int ks = 0; ks < 8; ks++) wg_ss64_tab(d, da + (uint64_t)(ks * 128), db + (uint64_t)(ks * 128), ks);
      wg_commit(); wg_wait0();
#pragma unroll
      for (int hf = 0; hf < 2; hf++) {
        const int col = warp * 16 + hf * 8 + g, dd = col == 56 ? 28 : col - mt * 28;
        if (dd >= 0 && (dd < 28 || col == 56)) {
          float* kv = g_kv + (pr * 2 + mt) * 2048 + dd * 64 + tq * 16;
#pragma unroll
          for (int ks = 0; ks < 4; ks++) red4(kv + ks * 4, d[8 * ks + 2 * hf], d[8 * ks + 2 * hf + 1], d[8 * ks + 4 + 2 * hf], d[8 * ks + 5 + 2 * hf]);
        }
      }
    }
  }
  __syncthreads();
  if (tid == 0) { __threadfence(); atomicAdd(g_a1done, 1); }
}
__device__ __forceinline__ void a2_job(uint32_t sb, uint32_t bars, uint32_t ph, int rt, const CUtensorMap* mWo, bf16* __restrict__ out) {
  const int tid = threadIdx.x, w = __shfl_sync(0xffffffffu, tid >> 5, 0), lane = tid & 31, g = lane >> 2, tq = lane & 3;
  const int wg = w >> 2, warp = w & 3;
  const uint32_t sO = sb, sW = sb + 114688;
  auto load_w = [&](int t) {
    const uint32_t bar = bars + 8 + 8 * (t & 1);
    arm_bar(bar, 57344);
    tma2d(sW + (t & 1) * 57344, mWo, t * 64, 0, bar); tma2d(sW + (t & 1) * 57344 + 28672, mWo, t * 64, 224, bar);
  };
  const uint32_t pring = sW + 57344 + w * 3584 - (w * 3584) % 16 * 0, pbar = bars + 32 + w * 24;
  (void)pring;
  auto load_pq = [&](int t16) { const uint32_t bar = pbar + 8 * (t16 % 3); arm_bar(bar, 2048); bulk_g2s(sW + 16384 + (w * 3 + t16 % 3) * 2048, g_PQ + ((rt * 8 + t16) * NH + w) * 128, 2048, bar); };
  if (w == 0) wait_flags(g_a1done, 1, 64);
  __syncthreads();
  if (lane == 0) {
    asm volatile("fence.proxy.async.global;" ::: "memory");
    if (w == 0) arm_bar(bars, 16 * 7424);
  }
  __syncthreads();
  if (lane == 0) { bulk_g2s(sO + w * 8192, g_kv + w * 2048, 7424, bars); load_pq(0); load_pq(1); load_pq(2); }
  wait_bar1(bars, 0);
  {
    if (tid == 0 && rt == 12) TLS(920);
    uint32_t kb[4][4][2];
#pragma unroll
    for (int nt = 0; nt < 4; nt++)
#pragma unroll
      for (int ks = 0; ks < 4; ks++) {
        const float4 t = lds128f(sO + w * 8192 + min(nt * 8 + g, 28) * 256 + tq * 64 + ks * 16);
        kb[ks][nt][0] = pack_bf16(t.x, t.y); kb[ks][nt][1] = pack_bf16(t.z, t.w);
      }
    __syncthreads();
    if (kb[0][0][0] == 0x12345 || (tid == 0 && rt == 12)) TLS(921);
#pragma unroll 1
    for (int t16 = 0; t16 < 8; t16++) {
      const float g0 = __ldcg(g_gate + rt * 128 + t16 * 16 + g), g1 = __ldcg(g_gate + rt * 128 + t16 * 16 + g + 8);
      wait_bar1(pbar + 8 * (t16 % 3), (t16 / 3) & 1);
      uint4 a[4];
#pragma unroll
      for (int ks = 0; ks < 4; ks++) a[ks] = lds128v(sW + 16384 + (w * 3 + t16 % 3) * 2048 + ks * 512 + lane * 16);
      float o[4][4] = {};
#pragma unroll
      for (int ks = 0; ks < 4; ks++)
#pragma unroll
        for (int nt = 0; nt < 4; nt++) mma16816(o[nt], a[ks].x, a[ks].y, a[ks].z, a[ks].w, kb[ks][nt][0], kb[ks][nt][1]);
      __syncwarp();
      if (lane == 0 && t16 + 3 < 8) load_pq(t16 + 3);
      const int row = t16 * 16 + g;
      const float s0 = g0 * __frcp_rn(__shfl_sync(0xffffffffu, o[3][0], (lane & ~3) | 2) + 1e-6f);
      const float s1 = g1 * __frcp_rn(__shfl_sync(0xffffffffu, o[3][2], (lane & ~3) | 2) + 1e-6f);
#pragma unroll
      for (int nt = 0; nt < 4; nt++) if (nt < 3 || tq < 2) {
        const int col = w * 28 + nt * 8 + tq * 2;
        const uint32_t oa = sO + ((row >> 6) * 7 + (col >> 6)) * 8192 + (row & 63) * 128 + ((((col >> 3) & 7) ^ g) << 4) + (col & 7) * 2;
        sts32(oa, pack_bf16(o[nt][0] * s0, o[nt][1] * s0)); sts32(oa + 1024, pack_bf16(o[nt][2] * s1, o[nt][3] * s1));
      }
    }
  }
  const bool fin = rt * 4 < SEG_REV;
  if (fin && w == 0) wait_flags(g_a2done + rt, 1, 4);
  asm volatile("fence.proxy.async.shared::cta;" ::: "memory");
  __syncthreads();
  if (tid == 0) { load_w(0); load_w(1); }
  if (tid == 0 && rt == 12) TLS(922);
  const int par = wg & 1, rh = wg >> 1;
  uint32_t myph = (ph >> (1 + par)) & 1;
#pragma unroll 1
  for (int t = par; t < 7; t += 2) {
    wait_bar1(bars + 8 + 8 * par, myph); myph ^= 1;
    if (t > 0) BAR_SYNC_R(3 + par, 512);
    float d[32];
    const uint32_t tz = (uint32_t)(t * rt) & 0x4000u;
    const uint64_t da = make_desc(sW + par * 57344 + tz, 16, 1024, 1), db = make_desc(sO + rh * 57344 + tz, 16, 1024, 1);
    wg_fence();
#pragma unroll
    for (int ks = 0; ks < 28; ks++) wg_ss64_ta(d, da + (uint64_t)(ks * 128), db + (uint64_t)(((ks >> 2) * 8192 + (ks & 3) * 32) >> 4), ks);
    wg_commit();
    uint4 ff[4];
    if (fin) {
#pragma unroll
      for (int i = 0; i < 4; i++) ff[i] = ldg128(g_AF + (((rt * 4 + rh * 2 + (i >> 1)) * 28 + t * 4 + warp) * 2 + (i & 1)) * 32 + lane);
    }
    wg_wait0();
    if (t < 6) BAR_ARRIVE_R(4 - par, 512);
    BAR_SYNC_R(1 + par, 256);
    if (rh == 0 && (tid & 127) == 0 && t + 2 < 7) load_w(t + 2);
#pragma unroll
    for (int sg = 0; sg < 2; sg++) {
      const int seg = rt * 4 + rh * 2 + sg;
      if (fin) mix_store(d + sg * 16, ff[2 * sg], ff[2 * sg + 1], out, seg, t * 4 + warp, lane);
      else frag_store(d + sg * 16, seg, t * 4 + warp, lane);
    }
  }
  if (tid == 0 && rt == 12) TLS(923);
  if (!fin) { __syncthreads(); if (tid == 0) { __threadfence(); atomicAdd(&g_a2done[rt], 1); } }
}
#ifndef M_LAG
#define M_LAG 3000
#endif
#define X3_SPLIT 4
#define N_JOBS (64 + 16 + (NSEG - X3_SPLIT) + 4 * X3_SPLIT)
__constant__ unsigned char c_order[N_JOBS] = {0, 1, 2, 3, 4, 5, 6, 7, 8, 9, 10, 11, 12, 13, 14, 15, 16, 17, 18, 19, 20, 21, 22, 80, 81, 82, 83, 84, 85, 86, 23, 24, 25, 26, 27, 28, 29, 30, 31, 32, 33, 34, 35, 36, 37, 38, 87, 88, 89, 90, 91, 92, 93, 94, 95, 96, 97, 98, 39, 40, 41, 42, 43, 44, 45, 46, 47, 48, 49, 99, 100, 101, 50, 51, 52, 53, 102, 103, 104, 105, 106, 107, 108, 109, 110, 54, 55, 56, 57, 58, 59, 60, 61, 62, 63, 111, 112, 113, 114, 115, 116, 117, 118, 119, 74, 75, 76, 77, 120, 121, 78, 79, 122, 64, 65, 66, 67, 68, 69, 70, 71, 72, 73, 123, 124, 125, 126, 127, 128, 129, 130, 131, 132, 133, 134, 135, 136, 137, 138, 139, 140, 141, 142, 143, 144, 145, 146, 147, 148, 149, 150, 151, 152, 153, 154, 155};
__global__ void __launch_bounds__(512, 1) x_kernel(const __grid_constant__ CUtensorMap mX, const __grid_constant__ CUtensorMap mW, const __grid_constant__ CUtensorMap mWo, const bf16* wphi, bf16* out) {
  extern __shared__ unsigned char smem_raw[];
  const uint32_t sb = __shfl_sync(0xffffffffu, (smem_u32(smem_raw) + 1023) & ~1023u, 0);
  const uint32_t bars = sb + 4 * 57344;
  if (threadIdx.x >= 32 && threadIdx.x < 96) { mbar_init(bars + 8 * (threadIdx.x - 32), 1); asm volatile("fence.mbarrier_init.release.cluster;" ::: "memory"); }
  if (threadIdx.x == 0) { wait_go(); if (blockIdx.x < 23) lag(M_LAG); asm volatile("fence.proxy.async.global;" ::: "memory"); }
  __syncthreads();
  const int job = c_order[blockIdx.x];
  if (threadIdx.x == 0) TLS(400 + 2 * job);
  if (job < 64) a1_job(sb, bars, job >> 2, job & 3, &mX, &mW, wphi);
  else if (job < 80) a2_job(sb, bars, 0, job - 64, &mWo, out);
  else {
    const int k = job - 80;
    const bool full = k < NSEG - X3_SPLIT;
    const int k2 = k - (NSEG - X3_SPLIT);
    x3_job(sb, bars, full ? k : NSEG - X3_SPLIT + (k2 >> 2), full ? 0 : (k2 & 3) * 2, full ? 7 : min((k2 & 3) * 2 + 2, 7), out);
  }
  if (threadIdx.x == 0) TLS(401 + 2 * job);
  if (threadIdx.x == 0 && atomicAdd(g_job, 1) == gridDim.x - 1) { g_go[0] = 0; g_reg[0] = 0; g_reg[1] = 0; }
}

static PFN_cuTensorMapEncodeTiled get_encode() {
  void* fn = nullptr; cudaDriverEntryPointQueryResult qr;
  cudaGetDriverEntryPoint("cuTensorMapEncodeTiled", &fn, cudaEnableDefault, &qr);
  return (PFN_cuTensorMapEncodeTiled)fn;
}
static CUtensorMap make_map(PFN_cuTensorMapEncodeTiled enc, const void* p, int rank, const cuuint64_t* dims, const cuuint64_t* strides, const cuuint32_t* box, CUtensorMapSwizzle swz) {
  CUtensorMap m; cuuint32_t es[5] = {1, 1, 1, 1, 1};
  enc(&m, CU_TENSOR_MAP_DATA_TYPE_BFLOAT16, rank, (void*)p, dims, strides, box, es, CU_TENSOR_MAP_INTERLEAVE_NONE, swz, CU_TENSOR_MAP_L2_PROMOTION_L2_256B, CU_TENSOR_MAP_FLOAT_OOB_FILL_NONE);
  return m;
}
int g_poll_delay = POLL_DELAY;
extern "C" void kernel_launch(void* const* d_in, const int* in_sizes, int n_in, void* d_out, int out_size) {
  const bf16* x = (const bf16*)d_in[0];
  const bf16* wqkv = (const bf16*)d_in[1];
  const bf16* wphi = (const bf16*)d_in[2];
  const bf16* wo_a = (const bf16*)d_in[3];
  const bf16* mem0 = (const bf16*)d_in[5];
  const bf16* Wq = (const bf16*)d_in[6];
  const bf16* Wk = (const bf16*)d_in[7];
  const bf16* Wv = (const bf16*)d_in[8];
  const bf16* Wo = (const bf16*)d_in[9];
  const bf16* gate_w = (const bf16*)d_in[11];
  bf16* out = (bf16*)d_out;
  cudaFuncSetAttribute(r_kernel, cudaFuncAttributeMaxDynamicSharedMemorySize, (int)sizeof(RSmem));
  cudaFuncSetAttribute(k0_prep, cudaFuncAttributeMaxDynamicSharedMemorySize, K0_SMEM);
  cudaFuncSetAttribute(x_kernel, cudaFuncAttributeMaxDynamicSharedMemorySize, G_SMEM);
  cudaFuncSetAttribute(g_kernel, cudaFuncAttributeMaxDynamicSharedMemorySize, G_SMEM);
  PFN_cuTensorMapEncodeTiled enc = get_encode();
  CUtensorMap mWq, mWk, mWv, mWo, mX;
  { cuuint64_t dims[3] = {64, 448, 64}, str[2] = {8192, 128}; cuuint32_t box[3] = {64, 8, 4};
    mWq = make_map(enc, Wq, 3, dims, str, box, CU_TENSOR_MAP_SWIZZLE_128B); mWk = make_map(enc, Wk, 3, dims, str, box, CU_TENSOR_MAP_SWIZZLE_128B); mWv = make_map(enc, Wv, 3, dims, str, box, CU_TENSOR_MAP_SWIZZLE_128B); }
  { cuuint64_t dims[2] = {448, 4096}, str[1] = {896}; cuuint32_t box[2] = {64, 256}; mWo = make_map(enc, Wo, 2, dims, str, box, CU_TENSOR_MAP_SWIZZLE_128B); }
  { cuuint64_t dims[2] = {448, 2048}, str[1] = {896}; cuuint32_t box[2] = {64, 64}; mX = make_map(enc, x, 2, dims, str, box, CU_TENSOR_MAP_SWIZZLE_128B); }
  CUtensorMap mW, mWoA;
  { cuuint64_t dims[2] = {1344, 448}, str[1] = {2688}; cuuint32_t box[2] = {64, 32}; mW = make_map(enc, wqkv, 2, dims, str, box, CU_TENSOR_MAP_SWIZZLE_128B); }
  { cuuint64_t dims[2] = {448, 448}, str[1] = {896}; cuuint32_t box[2] = {64, 224}; mWoA = make_map(enc, wo_a, 2, dims, str, box, CU_TENSOR_MAP_SWIZZLE_128B); }
  k0_prep<<<K0_GRID, 640, K0_SMEM, cudaStreamPerThread>>>(mWq, mWk, mWv, mWo, x, mem0, gate_w);
  cudaLaunchAttribute at[1]; at[0].id = cudaLaunchAttributeProgrammaticStreamSerialization; at[0].val.programmaticStreamSerializationAllowed = 1;
  {
    static int ncl = 0;
    if (!ncl) {
      cudaLaunchConfig_t oc = {}; oc.gridDim = dim3(64); oc.blockDim = dim3(384); oc.dynamicSmemBytes = sizeof(RSmem);
      cudaLaunchAttribute ca[1]; ca[0].id = cudaLaunchAttributeClusterDimension; ca[0].val.clusterDim.x = 4; ca[0].val.clusterDim.y = 1; ca[0].val.clusterDim.z = 1;
      oc.attrs = ca; oc.numAttrs = 1;
      if (cudaOccupancyMaxActiveClusters(&ncl, r_kernel, &oc) != cudaSuccess || ncl < NH) { ncl = NH; cudaGetLastError(); }
      if (ncl > 32) ncl = 32;
    }
    cudaLaunchConfig_t cfg = {}; cfg.gridDim = dim3(4 * ncl); cfg.blockDim = dim3(384); cfg.dynamicSmemBytes = sizeof(RSmem); cfg.stream = cudaStreamPerThread; cfg.attrs = at; cfg.numAttrs = 1;
    cudaLaunchKernelEx(&cfg, r_kernel, mem0, g_poll_delay);
  }
  {
    cudaLaunchConfig_t cfg = {}; cfg.gridDim = dim3(G_CTAS); cfg.blockDim = dim3(512); cfg.dynamicSmemBytes = G_SMEM; cfg.stream = cudaStreamPerThread; cfg.attrs = at; cfg.numAttrs = 1;
    cudaLaunchKernelEx(&cfg, g_kernel, mX);
  }
  {
    cudaLaunchConfig_t cfg = {}; cfg.gridDim = dim3(N_JOBS); cfg.blockDim = dim3(512); cfg.dynamicSmemBytes = G_SMEM; cfg.stream = cudaStreamPerThread; cfg.attrs = at; cfg.numAttrs = 1;
    cudaLaunchKernelEx(&cfg, x_kernel, mX, mW, mWoA, wphi, out);
  }
}
```
